```python
import torch

def _softmax(x, axis=-1):
    return torch.softmax(x, dim=axis)

def _gelu(x):
    return torch.nn.functional.gelu(x, approximate='tanh')

def _silu(x):
    return torch.nn.functional.silu(x)

def _sigmoid(x):
    return torch.sigmoid(x)

def _layernorm(x, axis=-1, eps=1e-05):
    m = x.mean(dim=axis, keepdim=True)
    v = x.var(dim=axis, keepdim=True, unbiased=False)
    return (x - m) / torch.sqrt(v + eps)

def _scatter_add(tgt, idx, src, axis=0):
    return tgt.clone().index_add_(axis, idx, src)

def _segment_sum(src, seg, n):
    out = torch.zeros((n,) + src.shape[1:], dtype=src.dtype)
    return out.index_add_(0, seg, src)

def _pad(x, pw):
    flat = tuple((v for pair in reversed(pw) for v in pair))
    return torch.nn.functional.pad(x, flat)
kernel_name = 'adaLN_cond__sliding_local_dilated__glu_gated_swiglu__prompt'

def setup_inputs():

    _w = lambda a: (lambda t: t.to(torch.bfloat16) if t.is_floating_point() else t)(torch.as_tensor(a))

    def _A_setup():
        B, S, D = (1, 2048, 1024)
        return {'x': _w((lambda *s: torch.randn(*s, dtype=torch.bfloat16) * 0.05)(B, S, D)), 'wqkv': _w((lambda *s: torch.randn(*s, dtype=torch.bfloat16) * 0.05)(D, 3 * D)), 'wo': _w((lambda *s: torch.randn(*s, dtype=torch.bfloat16) * 0.05)(D, D))}
    _A_in = _A_setup()

    def _B_setup():
        B, S, D, F = (1, 2048, 1024, 3584)
        return {'x': _w((lambda *s: torch.randn(*s, dtype=torch.bfloat16) * 0.05)(B, S, D)), 'w1': _w((lambda *s: torch.randn(*s, dtype=torch.bfloat16) * 0.8)(D, F) * (2.0 / D) ** 0.5), 'w3': _w((lambda *s: torch.randn(*s, dtype=torch.bfloat16) * 0.8)(D, F) * (2.0 / D) ** 0.5), 'w2': _w((lambda *s: torch.randn(*s, dtype=torch.bfloat16) * 0.8)(F, D) * (2.0 / F) ** 0.5)}
    _B_in = _B_setup()
    return {'A_x': _A_in['x'], 'A_wqkv': _A_in['wqkv'], 'A_wo': _A_in['wo'], 'B_x': _B_in['x'], 'B_w1': _B_in['w1'], 'B_w3': _B_in['w3'], 'B_w2': _B_in['w2'], 'c': _w((lambda *s: torch.randn(*s, dtype=torch.bfloat16) * 0.1)(1, 1024) * 8.0), 'w_mod': _w((lambda *s: torch.randn(*s, dtype=torch.bfloat16) * 0.1)(1024, 6 * 1024) * 1024 ** (-0.5) * 8.0)}

def reference(A_x, A_wqkv, A_wo, B_x, B_w1, B_w3, B_w2, c, w_mod):

    def _A_ref(x, wqkv, wo):
        B, S, D = x.shape
        H = 32
        Dh = D // H
        W, dil = (8, 2)
        qkv = (lambda x, *d: x.permute(*d))((x @ wqkv).reshape(B, S, 3, H, Dh), 2, 0, 3, 1, 4)
        q, k, v = (qkv[0], qkv[1], qkv[2])
        scale = Dh ** (-0.5)
        pos = torch.arange(S)
        off = torch.arange(W) * dil
        idx = pos[:, None] - off[None, :]
        mask = idx >= 0
        idx_c = torch.where(mask, idx, 0).reshape(-1)
        kg = k[:, :, idx_c, :].reshape(B, H, S, W, Dh)
        vg = v[:, :, idx_c, :].reshape(B, H, S, W, Dh)
        logits = torch.einsum('bhsd,bhswd->bhsw', q, kg) * scale
        logits = torch.where(mask[None, None, :, :], logits, -1000000000.0)
        attn = _softmax(logits, axis=-1)
        o = torch.einsum('bhsw,bhswd->bhsd', attn, vg)
        return (lambda x, *d: x.permute(*d))(o, 0, 2, 1, 3).reshape(B, S, D) @ wo

    def _B_ref(x, w1, w3, w2):
        gate = torch.einsum('bsd,df->bsf', x, w1)
        up = torch.einsum('bsd,df->bsf', x, w3)
        h = _silu(gate) * up
        out = torch.einsum('bsf,fd->bsd', h, w2)
        return out
    x = A_x
    mod = (_silu(c) @ w_mod).reshape(c.shape[0], 6, 1, -1)
    sa, ca, ga, sb, cb, gb = (mod[:, 0].clone(), mod[:, 1].clone(), mod[:, 2].clone(), mod[:, 3].clone(), mod[:, 4].clone(), mod[:, 5].clone())
    h = _layernorm(x, axis=-1) * (1 + ca) + sa
    x = x + ga * _A_ref(h, A_wqkv, A_wo)
    h = _layernorm(x, axis=-1) * (1 + cb) + sb
    x = x + gb * _B_ref(h, B_w1, B_w3, B_w2)
    return x
```

```cpp
#include <cuda.h>
#include <cuda_runtime.h>
#include <cuda_bf16.h>
#include <stdint.h>

namespace {

typedef __nv_bfloat16 bf16;

constexpr int S_ = 2048, D_ = 1024, F_ = 3584;
constexpr int NCTA = 128, NAUX = 4;

__device__ __align__(1024) bf16 g_o[S_ * D_];
__device__ __align__(1024) bf16 g_hh[S_ * F_];
__device__ __align__(1024) float g_mod[8 * 6 * D_];
__device__ __align__(1024) uint2 g_ln1[16 * 8 * 16];
__device__ __align__(1024) uint4 g_halo[16 * 16 * 2 * 4 * 32];
__device__ __align__(1024) uint4 g_st2[16 * 8 * 8 * 8];
constexpr int FO_EPOCH = 0, FO_O = 1, FO_HH = 4, FO_H1 = 11, FL_EPOCH = 16 * 32, FL_RESET = FL_EPOCH + 1, FL_LN1 = FL_EPOCH + 2, FL_H2 = FL_EPOCH + 3;
__device__ __align__(1024) unsigned g_flags[17 * 32];

#define PROF(slot, on) do {} while (0)
#define PROFN(slot, on) do {} while (0)
#define PROFW_DECL do {} while (0)
#define PROFW(stmt) do {} while (0)
#define PROFW_OUT(slot, on) do {} while (0)

__device__ __forceinline__ uint32_t smem_u32(const void* p) { return (uint32_t)__cvta_generic_to_shared(p); }
__device__ __forceinline__ void mbar_init(uint32_t bar, uint32_t count) {
  asm volatile("mbarrier.init.shared::cta.b64 [%0], %1;" :: "r"(bar), "r"(count));
}
#define ELECT "{\n.reg .pred p;\nelect.sync _|p, 0xffffffff;\n@p "
__device__ __forceinline__ void mbar_expect_tx_e(uint32_t bar, uint32_t bytes) {
  asm volatile(ELECT "mbarrier.arrive.expect_tx.shared::cta.b64 _, [%0], %1;\n}" :: "r"(bar), "r"(bytes) : "memory");
}
__device__ __forceinline__ void mbar_arrive_e(uint32_t bar) {
  asm volatile(ELECT "mbarrier.arrive.shared::cta.b64 _, [%0];\n}" :: "r"(bar) : "memory");
}
__device__ __forceinline__ void mbar_wait(uint32_t bar, uint32_t parity, uint32_t dl_addr) {
  asm volatile("{\n.reg .pred p;\n.reg .b32 t, d;\n"
               "LAB_WAIT:\n"
               "mbarrier.try_wait.parity.shared::cta.b64 p, [%0], %1;\n"
               "@p bra LAB_DONE;\n"
               "mov.u32 t, %%clock;\n"
               "ld.shared.b32 d, [%2];\n"
               "sub.s32 t, t, d;\n"
               "setp.lt.s32 p, t, 0;\n"
               "@p bra LAB_WAIT;\n"
               "LAB_DONE:\n}" :: "r"(bar), "r"(parity), "r"(dl_addr) : "memory");
}
__device__ __forceinline__ bool before_deadline(uint32_t dl_addr) {
  uint32_t t, d;
  asm volatile("mov.u32 %0, %%clock;" : "=r"(t));
  asm volatile("ld.shared.b32 %0, [%1];" : "=r"(d) : "r"(dl_addr));
  return (int)(t - d) < 0;
}
__device__ __forceinline__ bool poll_done(bool ok, uint32_t dl_addr) {
  return __all_sync(0xffffffffu, ok) || __any_sync(0xffffffffu, !before_deadline(dl_addr));
}
__device__ __forceinline__ unsigned ld_relaxed(const unsigned* p) {
  unsigned v; asm volatile("ld.relaxed.gpu.global.u32 %0, [%1];" : "=r"(v) : "l"(p) : "memory"); return v;
}
__device__ __forceinline__ void red_add_e(unsigned* p, unsigned v) {
  asm volatile(ELECT "red.relaxed.gpu.global.add.u32 [%0], %1;\n}" :: "l"(p), "r"(v) : "memory");
}
__device__ __forceinline__ void wait_flag(const unsigned* p, unsigned target, uint32_t dl_addr) {
  asm volatile("{\n.reg .pred p;\n.reg .b32 t, d;\n"
               "LAB_WAIT:\n"
               "ld.relaxed.gpu.global.u32 t, [%0];\n"
               "sub.s32 t, t, %1;\n"
               "setp.ge.s32 p, t, 0;\n"
               "@p bra LAB_DONE;\n"
               "mov.u32 t, %%clock;\n"
               "ld.shared.b32 d, [%2];\n"
               "sub.s32 t, t, d;\n"
               "setp.lt.s32 p, t, 0;\n"
               "@p bra LAB_WAIT;\n"
               "LAB_DONE:\n}" :: "l"(p), "r"(target), "r"(dl_addr) : "memory");
}
__device__ __forceinline__ uint32_t clock32() { uint32_t t; asm volatile("mov.u32 %0, %%clock;" : "=r"(t)); return t; }
__device__ __forceinline__ void wait_until(uint32_t t) { while ((int)(clock32() - t) < 0) {} }
__device__ __forceinline__ void fence_proxy_async_smem() { asm volatile("fence.proxy.async.shared::cta;" ::: "memory"); }

__device__ __forceinline__ void tma_load_2d(uint32_t dst, const CUtensorMap* m, uint32_t bar, int c0, int c1) {
  asm volatile(ELECT "cp.async.bulk.tensor.2d.shared::cluster.global.mbarrier::complete_tx::bytes [%0], [%1, {%3, %4}], [%2];\n}"
               :: "r"(dst), "l"(m), "r"(bar), "r"(c0), "r"(c1) : "memory");
}
__device__ __forceinline__ void tma_load_3d(uint32_t dst, const CUtensorMap* m, uint32_t bar, int c0, int c1, int c2) {
  asm volatile(ELECT "cp.async.bulk.tensor.3d.shared::cluster.global.mbarrier::complete_tx::bytes [%0], [%1, {%3, %4, %5}], [%2];\n}"
               :: "r"(dst), "l"(m), "r"(bar), "r"(c0), "r"(c1), "r"(c2) : "memory");
}
__device__ __forceinline__ void tma_load_4d(uint32_t dst, const CUtensorMap* m, uint32_t bar, int c0, int c1, int c2, int c3) {
  asm volatile(ELECT "cp.async.bulk.tensor.4d.shared::cluster.global.mbarrier::complete_tx::bytes [%0], [%1, {%3, %4, %5, %6}], [%2];\n}"
               :: "r"(dst), "l"(m), "r"(bar), "r"(c0), "r"(c1), "r"(c2), "r"(c3) : "memory");
}
__device__ __forceinline__ void tma_store_2d(const CUtensorMap* m, uint32_t src, int c0, int c1) {
  asm volatile(ELECT "cp.async.bulk.tensor.2d.global.shared::cta.bulk_group [%0, {%2, %3}], [%1];\n}"
               :: "l"(m), "r"(src), "r"(c0), "r"(c1) : "memory");
}
__device__ __forceinline__ void tma_store_3d(const CUtensorMap* m, uint32_t src, int c0, int c1, int c2) {
  asm volatile(ELECT "cp.async.bulk.tensor.3d.global.shared::cta.bulk_group [%0, {%2, %3, %4}], [%1];\n}"
               :: "l"(m), "r"(src), "r"(c0), "r"(c1), "r"(c2) : "memory");
}
__device__ __forceinline__ void bulk_load(uint32_t dst, const void* src, uint32_t bytes, uint32_t bar) {
  asm volatile(ELECT "cp.async.bulk.shared::cluster.global.mbarrier::complete_tx::bytes [%0], [%1], %2, [%3];\n}"
               :: "r"(dst), "l"(src), "r"(bytes), "r"(bar) : "memory");
}
__device__ __forceinline__ void bulk_prefetch(const void* src, uint32_t bytes) {
  asm volatile(ELECT "cp.async.bulk.prefetch.L2.global [%0], %1;\n}" :: "l"(src), "r"(bytes) : "memory");
}
__device__ __forceinline__ void bulk_commit() { asm volatile("cp.async.bulk.commit_group;" ::: "memory"); }
__device__ __forceinline__ void bulk_wait0() { asm volatile("cp.async.bulk.wait_group 0;" ::: "memory"); }
__device__ __forceinline__ void bulk_wait_read0() { asm volatile("cp.async.bulk.wait_group.read 0;" ::: "memory"); }
__device__ __forceinline__ void prefetch_tmap(const CUtensorMap* m) { asm volatile("prefetch.tensormap [%0];" :: "l"(m) : "memory"); }
__device__ __forceinline__ void wgmma_fence() { asm volatile("wgmma.fence.sync.aligned;" ::: "memory"); }
__device__ __forceinline__ void wgmma_commit() { asm volatile("wgmma.commit_group.sync.aligned;" ::: "memory"); }
template <int N> __device__ __forceinline__ void wgmma_wait() { asm volatile("wgmma.wait_group.sync.aligned %0;" :: "n"(N) : "memory"); }
template <int R> __device__ __forceinline__ void reg_alloc() { asm volatile("setmaxnreg.inc.sync.aligned.u32 %0;" :: "n"(R)); }
template <int R> __device__ __forceinline__ void reg_dealloc() { asm volatile("setmaxnreg.dec.sync.aligned.u32 %0;" :: "n"(R)); }
__device__ __forceinline__ void bar_sync(int id, int n) { asm volatile("bar.sync %0, %1;" :: "r"(id), "r"(n) : "memory"); }
__device__ __forceinline__ void sched_fence() {
  asm volatile("{\n.reg .pred p;\n.reg .b32 t;\nLAB_F:\nmov.u32 t, %%clock;\nsetp.eq.u32 p, t, %0;\n@p bra LAB_F;\n}" :: "n"(0) : "memory");
}
template <int N> __device__ __forceinline__ void fence_regs(float (&a)[N]) {
  #pragma unroll
  for (int i = 0; i < N; i++) asm volatile("" : "+f"(a[i]) :: "memory");
}
template <int N> __device__ __forceinline__ void undef_regs(float (&a)[N]) {
  #pragma unroll
  for (int i = 0; i < N; i++) asm volatile("" : "=f"(a[i]));
}

__device__ __forceinline__ uint64_t desc_from_lo(uint32_t lo) { return (uint64_t)lo | ((uint64_t)0x40000040u << 32); }
__device__ __forceinline__ uint32_t pack_bf16(float lo, float hi) {
  uint32_t r; asm("cvt.rn.bf16x2.f32 %0, %1, %2;" : "=r"(r) : "f"(hi), "f"(lo)); return r;
}
__device__ __forceinline__ uint32_t fma_bf2(uint32_t a, uint32_t b, uint32_t c) {
  uint32_t d; asm("fma.rn.bf16x2 %0, %1, %2, %3;" : "=r"(d) : "r"(a), "r"(b), "r"(c)); return d;
}
__device__ __forceinline__ float bf_lo(uint32_t v) { return __uint_as_float(v << 16); }
__device__ __forceinline__ float bf_hi(uint32_t v) { return __uint_as_float(v & 0xFFFF0000u); }
__device__ __forceinline__ float bf16_round(float x) { return bf_lo(pack_bf16(x, 0.f)); }
__device__ __forceinline__ void stmatrix_x4(uint32_t addr, uint32_t r0, uint32_t r1, uint32_t r2, uint32_t r3) {
  asm volatile("stmatrix.sync.aligned.m8n8.x4.shared.b16 [%0], {%1, %2, %3, %4};" :: "r"(addr), "r"(r0), "r"(r1), "r"(r2), "r"(r3) : "memory");
}
__device__ __forceinline__ void ldmatrix_x4(uint32_t addr, uint32_t& r0, uint32_t& r1, uint32_t& r2, uint32_t& r3) {
  asm volatile("ldmatrix.sync.aligned.m8n8.x4.shared.b16 {%0, %1, %2, %3}, [%4];" : "=r"(r0), "=r"(r1), "=r"(r2), "=r"(r3) : "r"(addr) : "memory");
}
__device__ __forceinline__ void ldmatrix_x4_t(uint32_t addr, uint32_t& r0, uint32_t& r1, uint32_t& r2, uint32_t& r3) {
  asm volatile("ldmatrix.sync.aligned.m8n8.x4.trans.shared.b16 {%0, %1, %2, %3}, [%4];" : "=r"(r0), "=r"(r1), "=r"(r2), "=r"(r3) : "r"(addr) : "memory");
}
__device__ __forceinline__ uint32_t tagf(float v, unsigned par) { return (__float_as_uint(v) & ~1u) | par; }
__device__ __forceinline__ void st_rlx(void* p, uint32_t a, bool on) {
  asm volatile("{\n.reg .pred p;\nsetp.ne.b32 p, %2, 0;\n@p st.relaxed.gpu.global.u32 [%0], %1;\n}" :: "l"(p), "r"(a), "r"((int)on) : "memory");
}
__device__ __forceinline__ void st_rlx_v2(void* p, uint32_t a, uint32_t b, bool on) {
  asm volatile("{\n.reg .pred p;\nsetp.ne.b32 p, %3, 0;\n@p st.relaxed.gpu.global.v2.u32 [%0], {%1, %2};\n}" :: "l"(p), "r"(a), "r"(b), "r"((int)on) : "memory");
}
__device__ __forceinline__ uint2 ld_rlx_v2(const void* p) {
  uint2 v; asm volatile("ld.relaxed.gpu.global.v2.u32 {%0,%1}, [%2];" : "=r"(v.x), "=r"(v.y) : "l"(p) : "memory"); return v;
}
__device__ __forceinline__ void st_rlx_v4(void* p, uint32_t a, uint32_t b, uint32_t c, uint32_t d, bool on) {
  asm volatile("{\n.reg .pred p;\nsetp.ne.b32 p, %5, 0;\n@p st.relaxed.gpu.global.v4.u32 [%0], {%1, %2, %3, %4};\n}"
               :: "l"(p), "r"(a), "r"(b), "r"(c), "r"(d), "r"((int)on) : "memory");
}
__device__ __forceinline__ uint4 ld_rlx_v4(const void* p) {
  uint4 v; asm volatile("ld.relaxed.gpu.global.v4.u32 {%0,%1,%2,%3}, [%4];" : "=r"(v.x), "=r"(v.y), "=r"(v.z), "=r"(v.w) : "l"(p) : "memory"); return v;
}
__device__ __forceinline__ uint32_t movmatrix_t(uint32_t a) {
  uint32_t d; asm volatile("movmatrix.sync.aligned.m8n8.trans.b16 %0, %1;" : "=r"(d) : "r"(a)); return d;
}
__device__ __forceinline__ void mma16(float (&c)[4], uint32_t a0, uint32_t a1, uint32_t a2, uint32_t a3, uint32_t b0, uint32_t b1) {
  asm volatile("mma.sync.aligned.m16n8k16.row.col.f32.bf16.bf16.f32 {%0,%1,%2,%3}, {%4,%5,%6,%7}, {%8,%9}, {%0,%1,%2,%3};"
               : "+f"(c[0]), "+f"(c[1]), "+f"(c[2]), "+f"(c[3]) : "r"(a0), "r"(a1), "r"(a2), "r"(a3), "r"(b0), "r"(b1));
}
__device__ __forceinline__ void mma8(float (&c)[4], uint32_t a0, uint32_t a1, uint32_t b0) {
  asm volatile("mma.sync.aligned.m16n8k8.row.col.f32.bf16.bf16.f32 {%0,%1,%2,%3}, {%4,%5}, {%6}, {%0,%1,%2,%3};"
               : "+f"(c[0]), "+f"(c[1]), "+f"(c[2]), "+f"(c[3]) : "r"(a0), "r"(a1), "r"(b0));
}
__device__ __forceinline__ void sts128(uint32_t addr, uint32_t a, uint32_t b, uint32_t c, uint32_t d) {
  asm volatile("st.shared.v4.b32 [%0], {%1,%2,%3,%4};" :: "r"(addr), "r"(a), "r"(b), "r"(c), "r"(d) : "memory");
}
__device__ __forceinline__ uint4 lds128(uint32_t addr) {
  uint4 v; asm volatile("ld.shared.v4.b32 {%0,%1,%2,%3}, [%4];" : "=r"(v.x), "=r"(v.y), "=r"(v.z), "=r"(v.w) : "r"(addr) : "memory"); return v;
}
__device__ __forceinline__ float2 lds64f(uint32_t addr) {
  float2 v; asm volatile("ld.shared.v2.f32 {%0,%1}, [%2];" : "=f"(v.x), "=f"(v.y) : "r"(addr) : "memory"); return v;
}
__device__ __forceinline__ void sts32f(uint32_t addr, float v, bool on) {
  asm volatile("{\n.reg .pred p;\nsetp.ne.b32 p, %2, 0;\n@p st.shared.f32 [%0], %1;\n}" :: "r"(addr), "f"(v), "r"((int)on) : "memory");
}
__device__ __forceinline__ void sts64(uint32_t addr, uint32_t a, uint32_t b) {
  asm volatile("st.shared.v2.b32 [%0], {%1, %2};" :: "r"(addr), "r"(a), "r"(b) : "memory");
}
__device__ __forceinline__ float fast_ex2(float x) { float y; asm("ex2.approx.ftz.f32 %0, %1;" : "=f"(y) : "f"(x)); return y; }
__device__ __forceinline__ float fast_rcp(float x) { float y; asm("rcp.approx.ftz.f32 %0, %1;" : "=f"(y) : "f"(x)); return y; }
__device__ __forceinline__ float silu_f(float g) { return g * fast_rcp(1.f + fast_ex2(g * -1.4426950408889634f)); }
__device__ __forceinline__ float swiglu(float g, float u) {
  const float h = 0.5f * g;
  float t; asm("tanh.approx.f32 %0, %1;" : "=f"(t) : "f"(h));
  return fmaf(h, t, h) * u;
}

__device__ __forceinline__ void wgmma_m64n128k16_ss(float (&d)[64], uint64_t descA, uint64_t descB, int scaleD) {
  asm volatile("{\n.reg .pred p;\nsetp.ne.b32 p, %66, 0;\n"
    "wgmma.mma_async.sync.aligned.m64n128k16.f32.bf16.bf16 "
    "{%0, %1, %2, %3, %4, %5, %6, %7, %8, %9, %10, %11, %12, %13, %14, %15, "
    "%16, %17, %18, %19, %20, %21, %22, %23, %24, %25, %26, %27, %28, %29, %30, %31, "
    "%32, %33, %34, %35, %36, %37, %38, %39, %40, %41, %42, %43, %44, %45, %46, %47, "
    "%48, %49, %50, %51, %52, %53, %54, %55, %56, %57, %58, %59, %60, %61, %62, %63}, "
    "%64, %65, p, 1, 1, 0, 1;\n}\n"
    : "+f"(d[0]), "+f"(d[1]), "+f"(d[2]), "+f"(d[3]), "+f"(d[4]), "+f"(d[5]), "+f"(d[6]), "+f"(d[7]),
      "+f"(d[8]), "+f"(d[9]), "+f"(d[10]), "+f"(d[11]), "+f"(d[12]), "+f"(d[13]), "+f"(d[14]), "+f"(d[15]),
      "+f"(d[16]), "+f"(d[17]), "+f"(d[18]), "+f"(d[19]), "+f"(d[20]), "+f"(d[21]), "+f"(d[22]), "+f"(d[23]),
      "+f"(d[24]), "+f"(d[25]), "+f"(d[26]), "+f"(d[27]), "+f"(d[28]), "+f"(d[29]), "+f"(d[30]), "+f"(d[31]),
      "+f"(d[32]), "+f"(d[33]), "+f"(d[34]), "+f"(d[35]), "+f"(d[36]), "+f"(d[37]), "+f"(d[38]), "+f"(d[39]),
      "+f"(d[40]), "+f"(d[41]), "+f"(d[42]), "+f"(d[43]), "+f"(d[44]), "+f"(d[45]), "+f"(d[46]), "+f"(d[47]),
      "+f"(d[48]), "+f"(d[49]), "+f"(d[50]), "+f"(d[51]), "+f"(d[52]), "+f"(d[53]), "+f"(d[54]), "+f"(d[55]),
      "+f"(d[56]), "+f"(d[57]), "+f"(d[58]), "+f"(d[59]), "+f"(d[60]), "+f"(d[61]), "+f"(d[62]), "+f"(d[63])
    : "l"(descA), "l"(descB), "r"(scaleD));
}
__device__ __forceinline__ void wgmma_m64n256k16_rs(float (&d)[128], uint32_t a0, uint32_t a1, uint32_t a2, uint32_t a3, uint64_t descB, int scaleD) {
  asm volatile("{\n.reg .pred p;\nsetp.ne.b32 p, %133, 0;\n"
    "wgmma.mma_async.sync.aligned.m64n256k16.f32.bf16.bf16 "
    "{%0, %1, %2, %3, %4, %5, %6, %7, %8, %9, %10, %11, %12, %13, %14, %15, "
    "%16, %17, %18, %19, %20, %21, %22, %23, %24, %25, %26, %27, %28, %29, %30, %31, "
    "%32, %33, %34, %35, %36, %37, %38, %39, %40, %41, %42, %43, %44, %45, %46, %47, "
    "%48, %49, %50, %51, %52, %53, %54, %55, %56, %57, %58, %59, %60, %61, %62, %63, "
    "%64, %65, %66, %67, %68, %69, %70, %71, %72, %73, %74, %75, %76, %77, %78, %79, "
    "%80, %81, %82, %83, %84, %85, %86, %87, %88, %89, %90, %91, %92, %93, %94, %95, "
    "%96, %97, %98, %99, %100, %101, %102, %103, %104, %105, %106, %107, %108, %109, %110, %111, "
    "%112, %113, %114, %115, %116, %117, %118, %119, %120, %121, %122, %123, %124, %125, %126, %127}, "
    "{%128, %129, %130, %131}, %132, p, 1, 1, 1;\n}\n"
    : "+f"(d[0]), "+f"(d[1]), "+f"(d[2]), "+f"(d[3]), "+f"(d[4]), "+f"(d[5]), "+f"(d[6]), "+f"(d[7]),
      "+f"(d[8]), "+f"(d[9]), "+f"(d[10]), "+f"(d[11]), "+f"(d[12]), "+f"(d[13]), "+f"(d[14]), "+f"(d[15]),
      "+f"(d[16]), "+f"(d[17]), "+f"(d[18]), "+f"(d[19]), "+f"(d[20]), "+f"(d[21]), "+f"(d[22]), "+f"(d[23]),
      "+f"(d[24]), "+f"(d[25]), "+f"(d[26]), "+f"(d[27]), "+f"(d[28]), "+f"(d[29]), "+f"(d[30]), "+f"(d[31]),
      "+f"(d[32]), "+f"(d[33]), "+f"(d[34]), "+f"(d[35]), "+f"(d[36]), "+f"(d[37]), "+f"(d[38]), "+f"(d[39]),
      "+f"(d[40]), "+f"(d[41]), "+f"(d[42]), "+f"(d[43]), "+f"(d[44]), "+f"(d[45]), "+f"(d[46]), "+f"(d[47]),
      "+f"(d[48]), "+f"(d[49]), "+f"(d[50]), "+f"(d[51]), "+f"(d[52]), "+f"(d[53]), "+f"(d[54]), "+f"(d[55]),
      "+f"(d[56]), "+f"(d[57]), "+f"(d[58]), "+f"(d[59]), "+f"(d[60]), "+f"(d[61]), "+f"(d[62]), "+f"(d[63]),
      "+f"(d[64]), "+f"(d[65]), "+f"(d[66]), "+f"(d[67]), "+f"(d[68]), "+f"(d[69]), "+f"(d[70]), "+f"(d[71]),
      "+f"(d[72]), "+f"(d[73]), "+f"(d[74]), "+f"(d[75]), "+f"(d[76]), "+f"(d[77]), "+f"(d[78]), "+f"(d[79]),
      "+f"(d[80]), "+f"(d[81]), "+f"(d[82]), "+f"(d[83]), "+f"(d[84]), "+f"(d[85]), "+f"(d[86]), "+f"(d[87]),
      "+f"(d[88]), "+f"(d[89]), "+f"(d[90]), "+f"(d[91]), "+f"(d[92]), "+f"(d[93]), "+f"(d[94]), "+f"(d[95]),
      "+f"(d[96]), "+f"(d[97]), "+f"(d[98]), "+f"(d[99]), "+f"(d[100]), "+f"(d[101]), "+f"(d[102]), "+f"(d[103]),
      "+f"(d[104]), "+f"(d[105]), "+f"(d[106]), "+f"(d[107]), "+f"(d[108]), "+f"(d[109]), "+f"(d[110]), "+f"(d[111]),
      "+f"(d[112]), "+f"(d[113]), "+f"(d[114]), "+f"(d[115]), "+f"(d[116]), "+f"(d[117]), "+f"(d[118]), "+f"(d[119]),
      "+f"(d[120]), "+f"(d[121]), "+f"(d[122]), "+f"(d[123]), "+f"(d[124]), "+f"(d[125]), "+f"(d[126]), "+f"(d[127])
    : "r"(a0), "r"(a1), "r"(a2), "r"(a3), "l"(descB), "r"(scaleD));
}

constexpr uint32_t MSLOT = 32768, QSLOT = 49152;
constexpr int NM = 6, NQ = 4;
constexpr uint32_t SM_X0 = 3 * QSLOT;
constexpr uint32_t SM_XR = SM_X0 + 16384;
constexpr uint32_t SM_STG = 196608;
constexpr uint32_t SM_MODT = SM_STG + 16384;
constexpr uint32_t SM_XCH = SM_STG + 16384;
constexpr uint32_t SM_BAR = SM_STG + 32768;
constexpr uint32_t SM_VEC = SM_BAR + 512;
constexpr uint32_t SM_TOTAL = SM_VEC + 1024;
constexpr uint32_t B_FQ = SM_BAR, B_EQ = SM_BAR + 32, B_FM = SM_BAR + 64, B_EM = SM_BAR + 112, B_MOD = SM_BAR + 160,
                   B_STREQ = SM_BAR + 224, B_STFREE = SM_BAR + 232, B_VEC = SM_BAR + 240  , B_X = SM_BAR + 256  , B_LN = SM_BAR + 320,
                   B_FLG = SM_BAR + 328  , B_DL = SM_BAR + 416;
constexpr int NB_WG = 1  , NB_CONS = 3;
#define PF_BYTES 256
#define PF2_BYTES 0
#define Q_GAP 0
#define X_UP 3
#define X_GAP 200
#define X_PER 2
#define NEARLY 2

struct Maps {
  CUtensorMap x, out;
  CUtensorMap o, h2, hh;
  CUtensorMap wqk, wvv, wo, w1, w3, w2;
  CUtensorMap wmod;
};

struct Ring { int st; uint32_t ph; int prev; };
__device__ __forceinline__ void ring_next(Ring& r) { if (++r.st == NM) { r.st = 0; r.ph ^= 1; } }

__device__ __forceinline__ void retire_prev(uint32_t rel) {
  wgmma_commit();
  wgmma_wait<1>();
  if (rel) mbar_arrive_e(rel);
}
__device__ __forceinline__ void mma_step(float (&acc)[64], uint32_t a, uint32_t b, bool first, uint32_t rel) {
  const uint32_t alo = (a >> 4) + (1u << 16), blo = (b >> 4) + (512u << 16);
  wgmma_fence();
  #pragma unroll
  for (int k = 0; k < 4; k++) {
    wgmma_m64n128k16_ss(acc, desc_from_lo(alo + k * 2), desc_from_lo(blo + k * 128), k > 0 || !first);
    if (k == 0) retire_prev(rel);
  }
  wgmma_commit();
}
__device__ __forceinline__ uint32_t m_wait(uint32_t sbase, const Ring& r) {
  mbar_wait(sbase + B_FM + 8 * r.st, r.ph, sbase + B_DL);
  return sbase + r.st * MSLOT;
}
__device__ __forceinline__ uint32_t m_prev(uint32_t sbase, const Ring& r) { return sbase + B_EM + 8 * r.prev; }
__device__ __forceinline__ void m_next(Ring& r) { r.prev = r.st; ring_next(r); }
__device__ __forceinline__ void m_step(float (&acc)[64], uint32_t sbase, uint32_t wgoff, Ring& r, bool first = false) {
  const uint32_t slot = m_wait(sbase, r);
  mma_step(acc, slot + wgoff, slot + 16384, first, m_prev(sbase, r));
  m_next(r);
}

struct LnRow { uint32_t rs[2], nb[2]; };
__device__ __forceinline__ void ln_row(LnRow& l, int h, float mean, float rstd) {
  l.rs[h] = pack_bf16(rstd, rstd);
  const float nb = -mean * bf_lo(l.rs[h]);
  l.nb[h] = pack_bf16(nb, nb);
}
__device__ __forceinline__ uint32_t ln_mod(uint32_t x, const LnRow& l, int h, uint32_t c1, uint32_t s) {
  return fma_bf2(fma_bf2(x, l.rs[h], l.nb[h]), c1, s);
}

__device__ __forceinline__ uint32_t q_wait(int u, uint32_t sbase) {
  mbar_wait(sbase + B_FQ + 8 * (u & 3), (u >> 2) & 1, sbase + B_DL);
  return sbase + (u & 3) * QSLOT;
}
__device__ __forceinline__ uint32_t q_empty(int u, uint32_t sbase) { return sbase + B_EQ + 8 * (u & 3); }
__device__ __forceinline__ void q_load(uint32_t (&A)[16], uint4 (&p)[4], int kk, uint32_t a, uint32_t t) {
  ldmatrix_x4(a ^ (kk << 5), A[4 * kk], A[4 * kk + 1], A[4 * kk + 2], A[4 * kk + 3]);
  p[kk] = lds128(t + kk * 64);
}
__device__ __forceinline__ void q_norm(uint32_t (&A)[16], const uint4 (&p)[4], int kk, const LnRow& l) {
  A[4 * kk + 0] = ln_mod(A[4 * kk + 0], l, 0, p[kk].x, p[kk].z); A[4 * kk + 1] = ln_mod(A[4 * kk + 1], l, 1, p[kk].x, p[kk].z);
  A[4 * kk + 2] = ln_mod(A[4 * kk + 2], l, 0, p[kk].y, p[kk].w); A[4 * kk + 3] = ln_mod(A[4 * kk + 3], l, 1, p[kk].y, p[kk].w);
}
template <bool NEXT>
__device__ __forceinline__ void q_step_rs(float (&acc)[128], uint32_t (&A)[16], uint32_t (&N)[16], uint4 (&p)[4], uint32_t slot, uint32_t frag,
                                          uint32_t t, const LnRow& l, bool first, uint32_t rel) {
  const uint32_t blo = ((slot + 16384) >> 4) + (512u << 16);
  #pragma unroll
  for (int kk = 0; kk < 4; kk++) q_norm(A, p, kk, l);
  wgmma_fence();
  #pragma unroll
  for (int kk = 0; kk < 4; kk++) {
    wgmma_m64n256k16_rs(acc, A[4 * kk], A[4 * kk + 1], A[4 * kk + 2], A[4 * kk + 3], desc_from_lo(blo + kk * 128), kk > 0 || !first);
    if (kk == 0) retire_prev(rel);
    if (NEXT && kk < 2) { q_load(N, p, 2 * kk, slot + frag, t); q_load(N, p, 2 * kk + 1, slot + frag, t); }
  }
  wgmma_commit();
}
__device__ __forceinline__ void q_stage_h1(const uint32_t (&A)[16], int u, uint32_t sbase, uint32_t frag) {
  if (u >= 8) mbar_wait(sbase + B_STFREE, 0, sbase + B_DL);
  #pragma unroll
  for (int kk = 0; kk < 4; kk++) stmatrix_x4((sbase + SM_STG + frag) ^ (kk << 5), A[4 * kk], A[4 * kk + 1], A[4 * kk + 2], A[4 * kk + 3]);
  fence_proxy_async_smem();
  mbar_arrive_e(sbase + B_STREQ);
}

typedef uint32_t Frag8[8];
template <int N> __device__ __forceinline__ void pack_half(Frag8& f, const float (&acc)[N], int off, int half) {
  #pragma unroll
  for (int e = 0; e < 8; e++) { f[e] = pack_bf16(acc[off + 4 * e + 2 * half], acc[off + 4 * e + 2 * half + 1]); asm volatile("" : "+r"(f[e])); }
}
__device__ __forceinline__ void transpose8(Frag8& f) {
  #pragma unroll
  for (int e = 0; e < 8; e++) f[e] = movmatrix_t(f[e]);
}
__device__ __forceinline__ void attn_send(const Frag8& f, int kv, uint32_t xch, int warp, uint4* halo_out, bool has_next) {
  if (warp == 3) {
    st_rlx_v4(halo_out + kv * 64, f[0], f[1], f[2], f[3], has_next); st_rlx_v4(halo_out + kv * 64 + 32, f[4], f[5], f[6], f[7], has_next);
  } else {
    sts128(xch + 2048 + kv * 1024, f[0], f[1], f[2], f[3]); sts128(xch + 2048 + kv * 1024 + 512, f[4], f[5], f[6], f[7]);
  }
}
template <int N>
__device__ __forceinline__ void attn_recv(uint4* p, int first, uint32_t xch, int wg, int warp, const uint4* halo_in, bool has_prev, uint32_t dl) {
  bar_sync(NB_WG + wg, 128);
  if (warp > 0) {
    #pragma unroll
    for (int e = 0; e < N; e++) p[e] = lds128(xch + (first + e) * 512);
  } else if (has_prev) {
    while (true) {
      bool ok = true;
      #pragma unroll
      for (int e = 0; e < N; e++) {
        p[e] = ld_rlx_v4(halo_in + (first + e) * 32);
        ok = ok && p[e].x != ~0u && p[e].y != ~0u && p[e].z != ~0u && p[e].w != ~0u;
      }
      if (poll_done(ok, dl)) break;
    }
  } else {
    #pragma unroll
    for (int e = 0; e < N; e++) p[e] = make_uint4(0, 0, 0, 0);
  }
}
__device__ __forceinline__ void attn_core(const Frag8& qA, const Frag8& qB, const Frag8& kA, const Frag8& kB, const Frag8& vA, const Frag8& vB,
                                          const uint4* kP, const uint4* vP, bool noprev, int lane, float (&o)[2][5][4]) {
  const int g = lane >> 2, qd = lane & 3;
  const bool s0 = 2 * qd > g, s1 = 2 * qd + 1 > g;
  const uint32_t msk = (s0 ? 0xFFFFu : 0u) | (s1 ? 0xFFFF0000u : 0u);
  constexpr float SC = 0.17677669529663687f * 1.4426950408889634f;
  float s[2][3][4];
  #pragma unroll
  for (int h = 0; h < 2; h++)
    #pragma unroll
    for (int nb = 0; nb < 3; nb++) s[h][nb][0] = s[h][nb][1] = s[h][nb][2] = s[h][nb][3] = 0.f;
  #pragma unroll
  for (int kk = 0; kk < 2; kk++)
    #pragma unroll
    for (int h = 0; h < 2; h++) {
      const int e = 4 * h + 2 * kk;
      mma16(s[h][1], qA[e], qB[e], qA[e + 1], qB[e + 1], kA[e], kA[e + 1]);
      mma16(s[h][2], qA[e], qB[e], qA[e + 1], qB[e + 1], kB[e], kB[e + 1]);
      mma16(s[h][0], qA[e], qB[e], qA[e + 1], qB[e + 1], kk ? kP[h].z : kP[h].x, kk ? kP[h].w : kP[h].y);
    }
  float l[2][4], m[2][2];
  #pragma unroll
  for (int h = 0; h < 2; h++) {
    l[h][0] = s0 ? (noprev ? -INFINITY : s[h][0][0]) : s[h][1][0];
    l[h][1] = s1 ? (noprev ? -INFINITY : s[h][0][1]) : s[h][1][1];
    l[h][2] = s0 ? s[h][1][2] : s[h][2][2];
    l[h][3] = s1 ? s[h][1][3] : s[h][2][3];
    m[h][0] = fmaxf(l[h][0], l[h][1]); m[h][1] = fmaxf(l[h][2], l[h][3]);
  }
  #pragma unroll
  for (int x = 1; x <= 2; x <<= 1)
    #pragma unroll
    for (int e = 0; e < 4; e++) m[e >> 1][e & 1] = fmaxf(m[e >> 1][e & 1], __shfl_xor_sync(0xffffffffu, m[e >> 1][e & 1], x));
  #pragma unroll
  for (int h = 0; h < 2; h++) {
    #pragma unroll
    for (int e = 0; e < 4; e++) l[h][e] = fast_ex2((l[h][e] - m[h][e >> 1]) * SC);
    const uint32_t plo = pack_bf16(l[h][0], l[h][1]), phi = pack_bf16(l[h][2], l[h][3]);
    const uint32_t vp[4] = {vP[h].x, vP[h].y, vP[h].z, vP[h].w};
    #pragma unroll
    for (int d = 0; d < 5; d++) o[h][d][0] = o[h][d][1] = o[h][d][2] = o[h][d][3] = 0.f;
    mma8(o[h][4], plo, phi, 0x3F803F80u);
    #pragma unroll
    for (int d = 0; d < 4; d++) mma16(o[h][d], plo & ~msk, phi & msk, 0u, phi & ~msk, vA[4 * h + d], vB[4 * h + d]);
    #pragma unroll
    for (int d = 0; d < 4; d++) mma8(o[h][d], plo & msk, 0u, vp[d]);
  }
}
__device__ __forceinline__ void attn_store(const float (&o)[2][5][4], int h, uint32_t sbase, uint32_t frag) {
  const float r0 = fast_rcp(o[h][4][0]), r1 = fast_rcp(o[h][4][2]);
  #pragma unroll
  for (int d = 0; d < 4; d += 2)
    stmatrix_x4((sbase + SM_STG + frag) ^ ((2 * h + (d >> 1)) << 5),
                pack_bf16(o[h][d][0] * r0, o[h][d][1] * r0), pack_bf16(o[h][d][2] * r1, o[h][d][3] * r1),
                pack_bf16(o[h][d + 1][0] * r0, o[h][d + 1][1] * r0), pack_bf16(o[h][d + 1][2] * r1, o[h][d + 1][3] * r1));
}

__device__ __forceinline__ void g_switch(float (&cur)[64], float (&prv)[64], int nrest, bool first, int n, uint32_t sbase, uint32_t wgoff,
                                         uint32_t frag, Ring& r) {
  #pragma unroll 1
  for (int i = 1; i < nrest; i++) m_step(prv, sbase, wgoff, r);
  m_step(prv, sbase, wgoff, r);
  m_step(cur, sbase, wgoff, r, first);
  mbar_wait(sbase + B_STFREE, (n - 1) & 1, sbase + B_DL);
  fence_regs(prv);
  PROF(28 + n, threadIdx.x == 0);
  #pragma unroll
  for (int jj = 0; jj < 4; jj++) {
    uint32_t p[4];
    #pragma unroll
    for (int e = 0; e < 4; e++) {
      const int i = jj * 8 + e * 2;
      p[e] = pack_bf16(swiglu(prv[i], prv[i + 32]), swiglu(prv[i + 1], prv[i + 33]));
    }
    stmatrix_x4((sbase + SM_STG + frag) ^ (jj << 5), p[0], p[1], p[2], p[3]);
    m_step(cur, sbase, wgoff, r);
  }
  fence_proxy_async_smem();
  mbar_arrive_e(sbase + B_STREQ);
}

__device__ __forceinline__ uint32_t bad_tag(const uint4& v, unsigned par) { return ((v.x ^ par) | (v.y ^ par) | (v.z ^ par) | (v.w ^ par)) & 1; }
__device__ __forceinline__ uint2 pack_mod(const uint4& v, float add) {
  return make_uint2(pack_bf16(add + __uint_as_float(v.x & ~1u), add + __uint_as_float(v.y & ~1u)),
                    pack_bf16(add + __uint_as_float(v.z & ~1u), add + __uint_as_float(v.w & ~1u)));
}

__device__ __forceinline__ int aux_col(int a, int u) { return u < 8 ? (a & 1) * 1024 + (2 * u + (a >> 1)) * 64 : 2048 + ((u - 8) * 4 + a) * 64; }
__device__ __forceinline__ void aux_role(const Maps& maps, const bf16* __restrict__ cvec, int a, uint32_t sbase, int wid) {
  const int tid = threadIdx.x, lane = tid & 31;
  const uint32_t dl = sbase + B_DL;
  if (wid == 8) {
    if (lane == 0) {
      prefetch_tmap(&maps.wmod);
      uint32_t t; asm volatile("mov.u32 %0, %%clock;" : "=r"(t));
      asm volatile("st.shared.b32 [%0], %1;" :: "r"(dl), "r"(t + 800000000u) : "memory");
      for (int s = 0; s < NM; s++) { mbar_init(sbase + B_FM + 8 * s, 1); mbar_init(sbase + B_EM + 8 * s, 4); }
      for (int s = 0; s < 2; s++) { mbar_init(sbase + B_FQ + 8 * s, 8); mbar_init(sbase + B_EQ + 8 * s, 2); }
      asm volatile("fence.mbarrier_init.release.cluster;" ::: "memory");
      fence_proxy_async_smem();
    }
    __syncwarp();
    Ring r{0, 1, 0};
    #pragma unroll 1
    for (int i = 0; i < 96; i++) {
      if (i == NM) bar_sync(0, 352);
      mbar_wait(sbase + B_EM + 8 * r.st, r.ph, dl);
      mbar_expect_tx_e(sbase + B_FM + 8 * r.st, 32768);
      tma_load_2d(sbase + r.st * MSLOT, &maps.wmod, sbase + B_FM + 8 * r.st, aux_col(a, i >> 2), (i & 3) * 256);
      ring_next(r);
    }
  } else if (wid < 8) {
    PROFN(0, tid == 0);
    const int g = lane >> 2, qd = lane & 3, wg = wid >> 2, warp = wid & 3;
    uint32_t sc[16];
    #pragma unroll
    for (int i = 0; i < 16; i++) sc[i] = *reinterpret_cast<const uint32_t*>(cvec + ((i >> 3) * 2 + wg) * 256 + warp * 64 + (i & 7) * 8 + qd * 2);
    #pragma unroll
    for (int i = 0; i < 16; i++) sc[i] = pack_bf16(silu_f(bf_lo(sc[i])), silu_f(bf_hi(sc[i])));
    bar_sync(0, 352);
    const uint32_t aoff = (warp * 64 + (lane & 7) + (lane >> 4) * 8) * 128 + ((((lane >> 3) & 1) ^ (lane & 7)) << 4);
    Ring r{wg, 0, 0};
    #pragma unroll 1
    for (int u = 0; u < 24; u++) {
      float acc[4][4];
      #pragma unroll
      for (int m = 0; m < 4; m++) acc[m][0] = acc[m][1] = acc[m][2] = acc[m][3] = 0.f;
      #pragma unroll
      for (int q = 0; q < 2; q++) {
        mbar_wait(sbase + B_FM + 8 * r.st, r.ph, dl);
        PROF(30 + r.st, u == 0 && (tid & 127) == 0);
        #pragma unroll
        for (int e = 0; e < 16; e++) {
          uint32_t w0, w1, w2, w3;
          ldmatrix_x4_t((sbase + r.st * MSLOT + aoff + (e >> 2) * 2048) ^ ((e & 3) << 5), w0, w1, w2, w3);
          mma16(acc[e & 3], w0, w1, w2, w3, sc[8 * q + 2 * (e >> 2)], sc[8 * q + 2 * (e >> 2) + 1]);
        }
        mbar_arrive_e(sbase + B_EM + 8 * r.st);
        ring_next(r); ring_next(r);
      }
      const uint32_t red = sbase + SM_STG + (u & 1) * 2048;
      mbar_wait(sbase + B_EQ + 8 * (u & 1), ((u >> 1) & 1) ^ 1, dl);
      #pragma unroll
      for (int m = 0; m < 4; m++) {
        sts32f(red + (wid * 64 + m * 16 + g) * 4, acc[m][0], qd == 0);
        sts32f(red + (wid * 64 + m * 16 + 8 + g) * 4, acc[m][2], qd == 0);
      }
      mbar_arrive_e(sbase + B_FQ + 8 * (u & 1));
    }
  } else if (wid < 11) {
    const unsigned par = (1 + ld_relaxed(&g_flags[FL_EPOCH])) & 1;
    float* const mail = &g_mod[(wid - 9) * 4 * 6 * D_ + 2 * lane];
    const int col2 = (lane >> 3) * 16 + (lane & 1) * 8 + (lane & 6);
    bar_sync(0, 352);
    #pragma unroll 1
    for (int u = -2; u < 24; u++) {
      if (u >= 0) {
        mbar_wait(sbase + B_FQ + 8 * (u & 1), (u >> 1) & 1, dl);
        float t0 = 0.f, t1 = 0.f;
        #pragma unroll
        for (int w = 0; w < 8; w++) { const float2 v = lds64f(sbase + SM_STG + (u & 1) * 2048 + (w * 64 + col2) * 4); t0 += v.x; t1 += v.y; }
        #pragma unroll
        for (int c = 0; c < 4; c++) st_rlx_v2(mail + c * 6 * D_ + aux_col(a, u), tagf(bf16_round(t0), par), tagf(bf16_round(t1), par), true);
        mbar_arrive_e(sbase + B_EQ + 8 * (u & 1));
        PROF(1 + u, tid == 288);
      }
      #pragma unroll 1
      for (int v = 3 * (u + 2); v < 3 * (u + 3) && v < 24; v++)
        #pragma unroll
        for (int c = 0; c < 4; c++) st_rlx_v2(mail + c * 6 * D_ + aux_col(a, v), par ^ 1, par ^ 1, true);
    }
  }
}

__global__ void __launch_bounds__(384, 1)
fused_block_kernel(const __grid_constant__ Maps maps, const bf16* __restrict__ x, const bf16* __restrict__ cvec, const bf16* __restrict__ wmod,
                   int role0) {
  extern __shared__ __align__(1024) uint8_t smem_raw[];
  const uint32_t sbase = smem_u32(smem_raw);
  const int tid = threadIdx.x, lane = tid & 31;
  const int wid = __shfl_sync(0xffffffffu, tid >> 5, 0);
  const int b = blockIdx.x + role0 - NAUX;
  if (b < 0) { aux_role(maps, cvec, b + NAUX, sbase, wid); return; }
  const int jg = b >> 6, mb = jg ? 31 - (b >> 2) : (b >> 2), j = 4 * jg + (b & 3);
  const uint32_t dl = sbase + B_DL;
  unsigned* const flags = &g_flags[mb * 32];
  const unsigned e1 = 1 + ld_relaxed(wid >= 10 ? &g_flags[FL_EPOCH] : flags + FO_EPOCH);
  const unsigned par = e1 & 1;
  const int row0 = mb * 128;

  if (wid >= 8) {
    if (wid == 8) {
      if (lane == 0) {
        for (int s = 0; s < 8; s++) mbar_init(sbase + B_X + 8 * s, 1);
        asm volatile("fence.mbarrier_init.release.cluster;" ::: "memory");
        fence_proxy_async_smem();
      }
      #pragma unroll 1
      for (int q = 0; q < X_UP; q++) {
        mbar_expect_tx_e(sbase + B_X + 8 * q, 4096);
        bulk_load(sbase + SM_XR + q * 4096, x + (size_t)(row0 + j * 16 + 2 * q) * D_, 4096, sbase + B_X + 8 * q);
      }
    } else if (tid == 288) {
      uint32_t t; asm volatile("mov.u32 %0, %%clock;" : "=r"(t));
      asm volatile("st.shared.b32 [%0], %1;" :: "r"(dl), "r"(t + 800000000u) : "memory");
      for (int s = 0; s < NQ; s++) { mbar_init(sbase + B_FQ + 8 * s, 1); mbar_init(sbase + B_EQ + 8 * s, 8); }
      for (int s = 0; s < NM; s++) { mbar_init(sbase + B_FM + 8 * s, 1); mbar_init(sbase + B_EM + 8 * s, 8); }
      for (int s = 0; s < 8; s++) mbar_init(sbase + B_MOD + 8 * s, s == 0 ? 2 : 1);
      mbar_init(sbase + B_STREQ, 8); mbar_init(sbase + B_STFREE, 1); mbar_init(sbase + B_VEC, 1); mbar_init(sbase + B_VEC + 8, 1); mbar_init(sbase + B_LN, 8);
      for (int s = 0; s < 11; s++) mbar_init(sbase + B_FLG + 8 * s, 1);
      asm volatile("fence.mbarrier_init.release.cluster;" ::: "memory");
      fence_proxy_async_smem();
    } else if (tid >= 320 && tid < 331) {
      prefetch_tmap(&maps.x + (tid - 320));
    }
    bar_sync(0, 384);
    reg_dealloc<40>();
    if (wid == 8) {
      uint32_t tnext = clock32();
      int xq = X_UP;
      #pragma unroll 1
      for (int u = 0; u < 16; u++) {
        const int st = u & 3;
        if (u <= NEARLY) {
          #pragma unroll 1
          for (; xq < 8 && (xq < X_UP + u * X_PER || u == NEARLY); xq++) {
            tnext += X_GAP; wait_until(tnext);
            mbar_expect_tx_e(sbase + B_X + 8 * xq, 4096);
            bulk_load(sbase + SM_XR + xq * 4096, x + (size_t)(row0 + j * 16 + 2 * xq) * D_, 4096, sbase + B_X + 8 * xq);
          }
          if (u == NEARLY) { mbar_wait(sbase + B_MOD, 0, dl); PROFN(60, lane == 0); tnext = clock32(); }
        } else if (u < NQ) { tnext += Q_GAP; wait_until(tnext); }
        if (u == 3) mbar_wait(sbase + B_EQ, 0, dl);
        mbar_wait(sbase + B_EQ + 8 * st, ((u >> 2) & 1) ^ 1, dl);
        const uint32_t slot = sbase + st * QSLOT, fb = sbase + B_FQ + 8 * st;
        mbar_expect_tx_e(fb, u == 0 ? 65536 : u == 15 ? 32768 : 49152);
        if (u == 0) tma_load_3d(sbase + SM_X0, &maps.x, fb, 0, mb * 64, 0);
        tma_load_4d(slot + 16384, &maps.wqk, fb, 0, u * 64, j, 0);
        tma_load_4d(slot + 32768, &maps.wvv, fb, 0, u * 64, j, 0);
        if (u < 15) tma_load_3d(slot, &maps.x, fb, u * 64 + 64, mb * 64, 0);
      }
      Ring r{0, 1, 0};
      uint32_t slot, fb;
      auto acquire = [&](uint32_t bytes) {
        mbar_wait(sbase + B_EM + 8 * r.st, r.ph, dl);
        slot = sbase + r.st * MSLOT; fb = sbase + B_FM + 8 * r.st;
        mbar_expect_tx_e(fb, bytes);
        ring_next(r);
      };
      #pragma unroll 1
      for (int kt = 0; kt < 16; kt++) {
        if (kt < 5) mbar_wait(sbase + B_EQ + 8 * (kt - (kt >= 2)), 1, dl);
        if (kt == 0 || kt == 8 || kt == 12) mbar_wait(sbase + B_FLG + (kt == 0 ? 0 : 2 * kt - 8), 0, dl);
        acquire(32768);
        tma_load_4d(slot + 16384, &maps.wqk, fb, 0, kt * 64, j + 8, 0);
        tma_load_3d(slot, &maps.hh, fb, (kt & 7) * 64, row0, kt >> 3);
      }
      mbar_wait(sbase + B_FLG + 24, 0, dl);
      #pragma unroll 1
      for (int kt = 0; kt < 8; kt++) {
        acquire(32768);
        tma_load_3d(slot + 16384, &maps.wo, fb, 0, kt * 64, 2 * j);
        tma_load_2d(slot, &maps.o, fb, kt * 64, row0);
      }
      acquire(32768);
      tma_load_3d(slot, &maps.x, fb, j * 128, mb * 64, 0);
      tma_load_3d(slot + 16384, &maps.x, fb, j * 128 + 64, mb * 64, 0);
      acquire(16384);
      tma_load_3d(slot + 16384, &maps.wo, fb, 0, (8 + j) * 64, 2 * j);
      {
        constexpr int NPRE = 3;
        Ring ra = r;
        #pragma unroll 1
        for (int i = 0; i < 7; i++) {
          const int kt = 8 + i + (i >= j);
          acquire(32768);
          tma_load_3d(slot + 16384, &maps.wo, fb, 0, kt * 64, 2 * j);
          if (i == NPRE - 1) {
            wait_flag(flags + FO_O + 1, e1 * 8, dl);
            PROF(61, lane == 0);
            #pragma unroll 1
            for (int q = 0; q < NPRE - 1; q++) { tma_load_2d(sbase + ra.st * MSLOT, &maps.o, sbase + B_FM + 8 * ra.st, (8 + q + (q >= j)) * 64, row0); ring_next(ra); }
          }
          if (i >= NPRE - 1) tma_load_2d(slot, &maps.o, fb, kt * 64, row0);
        }
      }
      #pragma unroll 1
      for (int t = 0; t < 2; t++) {
        acquire(32768);
        tma_load_2d(slot, &maps.w1, fb, j * 64, (2 * j + t) * 64);
        tma_load_2d(slot + 8192, &maps.w3, fb, j * 64, (2 * j + t) * 64);
        tma_load_2d(slot + 16384, &maps.w1, fb, (8 + j) * 64, (2 * j + t) * 64);
        tma_load_2d(slot + 24576, &maps.w3, fb, (8 + j) * 64, (2 * j + t) * 64);
      }
      {
        Ring ra = r;
        #pragma unroll 1
        for (int i = 0; i < 4; i++) {
          const int kt = i + (i >= 2 * j ? 2 : 0);
          acquire(32768);
          tma_load_2d(slot + 16384, &maps.w1, fb, j * 64, kt * 64);
          tma_load_2d(slot + 24576, &maps.w3, fb, j * 64, kt * 64);
        }
        wait_flag(&g_flags[FL_H2], e1 * NCTA, dl);
        PROFN(62, lane == 0);
        #pragma unroll 1
        for (int i = 0; i < 4; i++) { tma_load_2d(sbase + ra.st * MSLOT, &maps.h2, sbase + B_FM + 8 * ra.st, (i + (i >= 2 * j ? 2 : 0)) * 64, row0); ring_next(ra); }
      }
      #pragma unroll 1
      for (int gt = 0; gt < 7; gt++) {
        const int ncol = (8 * gt + j) * 64, skip = gt < 2 ? 2 * j : 16;
        #pragma unroll 1
        for (int i = (gt == 0 ? 4 : 0); i < (gt < 2 ? 14 : 16); i++) {
          const int kt = i + (i >= skip ? 2 : 0);
          acquire(32768);
          tma_load_2d(slot + 16384, &maps.w1, fb, ncol, kt * 64);
          tma_load_2d(slot + 24576, &maps.w3, fb, ncol, kt * 64);
          tma_load_2d(slot, &maps.h2, fb, kt * 64, row0);
        }
      }
      #pragma unroll 1
      for (int kt = 0; kt < 56; kt++) {
        if ((kt & 7) == 0) mbar_wait(sbase + B_FLG + 32 + kt, 0, dl);
        acquire(32768);
        tma_load_3d(slot + 16384, &maps.w2, fb, 0, kt * 64, 2 * j);
        tma_load_3d(slot, &maps.hh, fb, (kt & 7) * 64, row0, kt >> 3);
      }
    } else {
      if (wid == 9) {
        mbar_wait(sbase + B_LN, 0, dl);
        red_add_e(&g_flags[FL_LN1], 1);
        mbar_wait(sbase + B_MOD, 0, dl);
        #pragma unroll 1
        for (int e = 0; e < 16; e++) st_rlx_v4(g_halo + (mb * 16 + j + (e & 8)) * 256 + (e & 7) * 32 + lane, ~0u, ~0u, ~0u, ~0u, true);
        #pragma unroll 1
        for (int e = 0; e < 2; e++) st_rlx_v4(g_st2 + ((mb * 8 + e * 4 + (lane >> 3)) * 8 + j) * 8 + (lane & 7), ~0u, ~0u, ~0u, ~0u, true);
        __threadfence();
        red_add_e(&g_flags[FL_RESET], 1);
        #pragma unroll 1
        for (int n = 0; n < 12; n++) {
          mbar_wait(sbase + B_STREQ, n & 1, dl);
          if (n == 2 || n == 3) tma_store_2d(&maps.o, sbase + SM_STG, (j + 8 * (n - 2)) * 64, row0);
          else if (n == 4) { tma_store_2d(&maps.h2, sbase + SM_STG, j * 128, row0); tma_store_2d(&maps.h2, sbase + SM_STG + 16384, j * 128 + 64, row0); }
          else tma_store_3d(&maps.hh, sbase + SM_STG, j * 64, row0, n < 2 ? n : n - 5);
          bulk_commit();
          bulk_wait0();
          red_add_e(n == 4 ? &g_flags[FL_H2] : flags + (n < 2 ? FO_H1 + n + (n & (j >> 2)) : n - 1), 1);
          mbar_arrive_e(sbase + B_STFREE);
          PROFN(70 + n, lane == 0 && n > 0);
        }
      } else {
        mbar_wait(sbase + B_X + 56, 0, dl);
        const float* const mail = &g_mod[(b & 7) * 6 * D_ + lane * 4];
        if (wid == 11) {
          mbar_wait(sbase + B_LN, 0, dl);
          wait_flag(&g_flags[FL_LN1], e1 * NCTA, dl);
          mbar_arrive_e(sbase + B_MOD);
          PROF(41, lane == 0);
        }
        #pragma unroll 1
        for (int p = 2 * (wid - 10); p < 8; p += (p == 0 ? 1 : 2)) {
          uint4 sa, ca;
          while (true) {
            sa = ld_rlx_v4(mail + p * 128); ca = ld_rlx_v4(mail + 1024 + p * 128);
            if (poll_done((bad_tag(sa, par) | bad_tag(ca, par)) == 0, dl)) break;
            if (p > 1) __nanosleep(100);
          }
          const uint2 c1 = pack_mod(ca, 1.f), s = pack_mod(sa, 0.f);
          sts128(sbase + SM_MODT + p * 512 + lane * 16, c1.x, c1.y, s.x, s.y);
          if (p == 7) wait_flag(&g_flags[FL_RESET], e1 * NCTA, dl);
          mbar_arrive_e(sbase + B_MOD + 8 * p);
          PROF(63 + p, lane == 0 && p < 7);
        }
        if (wid == 10) {
          #pragma unroll 1
          for (int v = 0; v < 4; v++) {
            uint4 m;
            while (true) {
              m = ld_rlx_v4(mail + (2 + v) * 1024 + j * 128);
              if (poll_done(bad_tag(m, par) == 0, dl)) break;
              __nanosleep(500);
            }
            const uint2 w = pack_mod(m, v == 2 ? 1.f : 0.f);
            sts64(sbase + SM_VEC + v * 256 + (lane >> 3) * 64 + (lane & 3) * 16 + ((lane >> 2) & 1) * 8, w.x, w.y);
            if (v >= 2) mbar_arrive_e(sbase + B_VEC + 8 * (v - 2));
          }
          PROF(70, lane == 0);
        } else {
          #pragma unroll 1
          for (int i = 0; i < 11; i++) {
            const unsigned* f = flags + (i < 3 ? FO_H1 + i : i == 3 ? FO_O : FO_HH + i - 4);
            while (!poll_done((int)(ld_relaxed(f) - e1 * (i == 1 || i == 2 ? 4 : 8)) >= 0, dl)) __nanosleep(100);
            mbar_arrive_e(sbase + B_FLG + 8 * i);
          }
        }
      }
    }
  } else {
    PROFN(0, tid == 0);
    const int wg = wid >> 2, warp = wid & 3;
    const int g = lane >> 2, qd = lane & 3;
    bulk_prefetch(wmod + (size_t)(b * 8 + wid) * (6 * D_), PF_BYTES);
    bulk_prefetch(wmod + (size_t)(b * 8 + wid) * (6 * D_) + D_, PF_BYTES);
    bar_sync(0, 384);
    reg_alloc<232>();
    const uint32_t wgoff = wg * 8192;
    const uint32_t frag = wid * 2048 + (lane & 15) * 128 + (((lane >> 4) ^ (lane & 7)) << 4);
    const uint32_t slab = sbase + SM_STG + wid * 2048;

    LnRow ln;
    {
      uint2* const lmail = &g_ln1[(mb * 8 + (lane & 1) * 4 + (j >> 1)) * 16 + (j & 1) * 8 + wid];
      st_rlx_v2(lmail, par ^ 1, par ^ 1, lane < 2);
      mbar_wait(sbase + B_X + 8 * wid, 0, dl);
      PROF(3, tid == 224);
      if (PF2_BYTES) {
        bulk_prefetch(wmod + (size_t)(b * 8 + wid) * (6 * D_) + PF_BYTES / 2, PF2_BYTES);
        bulk_prefetch(wmod + (size_t)(b * 8 + wid) * (6 * D_) + PF_BYTES / 2 + D_, PF2_BYTES);
      }
      float s[2][2] = {{0.f, 0.f}, {0.f, 0.f}}, q2[2][2] = {{0.f, 0.f}, {0.f, 0.f}};
      #pragma unroll
      for (int c = 0; c < 8; c++) {
        const uint4 v = lds128(sbase + SM_XR + wid * 4096 + c * 512 + lane * 16);
        const uint32_t vv[4] = {v.x, v.y, v.z, v.w};
        #pragma unroll
        for (int e = 0; e < 4; e++) {
          const float lo = bf_lo(vv[e]), hi = bf_hi(vv[e]);
          s[c >> 2][0] += lo; s[c >> 2][1] += hi; q2[c >> 2][0] = fmaf(lo, lo, q2[c >> 2][0]); q2[c >> 2][1] = fmaf(hi, hi, q2[c >> 2][1]);
        }
      }
      const bool odd = lane & 1;
      float sm = (s[0][0] + s[0][1]), so = (s[1][0] + s[1][1]), qm = (q2[0][0] + q2[0][1]), qo = (q2[1][0] + q2[1][1]);
      { const float a = odd ? so : sm, c = odd ? qo : qm;
        sm = a + __shfl_xor_sync(0xffffffffu, odd ? sm : so, 1); qm = c + __shfl_xor_sync(0xffffffffu, odd ? qm : qo, 1); }
      #pragma unroll
      for (int o = 2; o < 32; o <<= 1) { sm += __shfl_xor_sync(0xffffffffu, sm, o); qm += __shfl_xor_sync(0xffffffffu, qm, o); }
      sm *= (1.f / D_);
      st_rlx_v2(lmail, tagf(rsqrtf(fmaxf(qm * (1.f / D_) - sm * sm, 0.f) + 1e-5f), par), tagf(sm, par), lane < 2);
      mbar_arrive_e(sbase + B_LN);
      PROF(4, tid == 224);
      mbar_wait(sbase + B_LN, 0, dl);
      uint2 v0, v1;
      do { v0 = ld_rlx_v2(&g_ln1[(mb * 8 + wid) * 16 + g]); v1 = ld_rlx_v2(&g_ln1[(mb * 8 + wid) * 16 + 8 + g]); }
      while (!poll_done((((v0.x ^ par) | (v0.y ^ par) | (v1.x ^ par) | (v1.y ^ par)) & 1) == 0, dl));
      ln_row(ln, 0, __uint_as_float(v0.y), __uint_as_float(v0.x));
      ln_row(ln, 1, __uint_as_float(v1.y), __uint_as_float(v1.x));
      PROF(5, tid == 0);
    }

    uint4* const halo_out = g_halo + ((mb * 16 + j) * 2 + wg) * 128 + lane;
    const uint4* const halo_in = halo_out - 16 * 256;
    const uint32_t xch = sbase + SM_XCH + wid * 2048 + lane * 16;
    const bool noprev = mb == 0 && warp == 0;
    float a0[64], a1[64];
    uint32_t x2[32];
    Ring r{role0 >> 8, 0, 0};
    Frag8 qA, qB, kA, kB, vA, vB, wA, wB;
    {
      float acc[128];
      uint32_t A0[16], A1[16];
      undef_regs(acc);
      const uint32_t tab = sbase + SM_MODT + qd * 16;
      uint4 p[4];
      q_wait(0, sbase);
      mbar_wait(sbase + B_MOD, 0, dl);
      #pragma unroll
      for (int kk = 0; kk < 4; kk++) q_load(A0, p, kk, sbase + SM_X0 + frag, tab);
      PROF(6, tid == 0);
      q_step_rs<true>(acc, A0, A1, p, sbase, frag, tab + 256, ln, true, 0);
      #pragma unroll 1
      for (int u = 1; u < 15; u += 2) {
        if (((u - 1) & 7) == j) q_stage_h1(A0, u - 1, sbase, frag);
        mbar_wait(sbase + B_MOD + 4 * (u + 1), 0, dl);
        q_step_rs<true>(acc, A1, A0, p, q_wait(u, sbase), frag, tab + (u + 1) * 256, ln, false, q_empty(u - 1, sbase));
        if ((u & 7) == j) q_stage_h1(A1, u, sbase, frag);
        q_step_rs<true>(acc, A0, A1, p, q_wait(u + 1, sbase), frag, tab + (u + 2) * 256, ln, false, q_empty(u, sbase));
      }
      if (j == 6) q_stage_h1(A0, 14, sbase, frag);
      q_step_rs<false>(acc, A1, A0, p, q_wait(15, sbase), frag, 0, ln, false, q_empty(14, sbase));
      if (j == 7) q_stage_h1(A1, 15, sbase, frag);
      wgmma_wait<0>();
      undef_regs(a0);
      { const uint32_t slot = m_wait(sbase, r); mma_step(a0, slot + wgoff, slot + 16384, true, q_empty(15, sbase)); m_next(r); }
      fence_regs(acc);
      PROF(8, tid == 0);
      bar_sync(NB_CONS, 256);
      pack_half(kB, acc, 32, 1); pack_half(vB, acc, 64, 1); transpose8(vB);
      m_step(a0, sbase, wgoff, r);
      sched_fence();
      attn_send(kB, 0, xch, warp, halo_out, mb < 15); attn_send(vB, 1, xch, warp, halo_out, mb < 15);
      pack_half(qA, acc, 0, 0); pack_half(qB, acc, 0, 1); pack_half(kA, acc, 32, 0);
      m_step(a0, sbase, wgoff, r);
      sched_fence();
      pack_half(vA, acc, 64, 0); pack_half(wB, acc, 96, 1); pack_half(wA, acc, 96, 0); transpose8(vA);
    }
    uint4 wP[2];
    {
      m_step(a0, sbase, wgoff, r);
      sched_fence();
      transpose8(wB);
      m_step(a0, sbase, wgoff, r);
      uint4 pv[4];
      attn_recv<4>(pv, 0, xch, wg, warp, halo_in, mb > 0, dl);
      m_step(a0, sbase, wgoff, r);
      wgmma_wait<0>();
      PROF(9, tid == 0);
      float o[2][5][4];
      mbar_wait(sbase + B_STFREE, 1, dl);
      attn_core(qA, qB, kA, kB, vA, vB, pv, pv + 2, noprev, lane, o);
      sched_fence();
      bar_sync(NB_CONS, 256);
      PROF(10, tid == 0);
      m_step(a0, sbase, wgoff, r);
      sched_fence();
      attn_store(o, 0, sbase, frag);
      m_step(a0, sbase, wgoff, r);
      sched_fence();
      attn_store(o, 1, sbase, frag);
      fence_proxy_async_smem();
      mbar_arrive_e(sbase + B_STREQ);
      m_step(a0, sbase, wgoff, r);
      sched_fence();
      attn_send(wB, 1, xch, warp, halo_out + 8 * 256, mb < 15);
      transpose8(wA);
      #pragma unroll 1
      for (int i = 9; i < 14; i++) m_step(a0, sbase, wgoff, r);
      attn_recv<2>(wP, 2, xch, wg, warp, halo_in + 8 * 256, mb > 0, dl);
      m_step(a0, sbase, wgoff, r);
      m_step(a0, sbase, wgoff, r);
    }
    {
      undef_regs(a1);
      m_step(a1, sbase, wgoff, r, true);
      fence_regs(a0);
      PROF(14, tid == 0);
      sched_fence();
      pack_half(kB, a0, 32, 1);
      attn_send(kB, 0, xch, warp, halo_out + 8 * 256, mb < 15);
      pack_half(kA, a0, 32, 0);
      m_step(a1, sbase, wgoff, r);
      sched_fence();
      pack_half(qA, a0, 0, 0); pack_half(qB, a0, 0, 1);
      m_step(a1, sbase, wgoff, r);
      uint4 kP[2];
      attn_recv<2>(kP, 0, xch, wg, warp, halo_in + 8 * 256, mb > 0, dl);
      wgmma_wait<0>();
      PROF(15, tid == 0);
      float o[2][5][4];
      mbar_wait(sbase + B_STFREE, 0, dl);
      attn_core(qA, qB, kA, kB, wA, wB, kP, wP, noprev, lane, o);
      attn_store(o, 0, sbase, frag);
      attn_store(o, 1, sbase, frag);
      fence_proxy_async_smem();
      mbar_arrive_e(sbase + B_STREQ);
      bar_sync(NB_CONS, 256);
      PROF(16, tid == 0);
      #pragma unroll 1
      for (int i = 3; i < 8; i++) m_step(a1, sbase, wgoff, r);
      mbar_wait(sbase + B_FM + 8 * r.st, r.ph, dl);
      #pragma unroll
      for (int jj = 0; jj < 8; jj++)
        ldmatrix_x4((sbase + r.st * MSLOT + (jj >> 2) * 16384 + frag) ^ ((jj & 3) << 5), x2[4 * jj], x2[4 * jj + 1], x2[4 * jj + 2], x2[4 * jj + 3]);
      mbar_arrive_e(sbase + B_EM + 8 * r.st);
      ring_next(r);
      mma_step(a1, sbase + SM_STG + wgoff, m_wait(sbase, r) + 16384, false, m_prev(sbase, r));
      m_next(r);
      PROF(17, tid == 0);
      #pragma unroll 1
      for (int i = 0; i < 7; i++) m_step(a1, sbase, wgoff, r);
      mbar_wait(sbase + B_VEC, 0, dl);
      mbar_wait(sbase + B_STFREE, 1, dl);
      const uint32_t vec = sbase + SM_VEC + qd * 16;
      uint4 ga[4];
      #pragma unroll
      for (int q = 0; q < 4; q++) ga[q] = lds128(vec + q * 64);
      wgmma_wait<0>();
      mbar_arrive_e(m_prev(sbase, r));
      fence_regs(a1);
      PROF(18, tid == 0);
      float s[2] = {0.f, 0.f}, q2[2] = {0.f, 0.f};
      #pragma unroll
      for (int i = 0; i < 32; i++) {
        const uint4& gv = ga[i >> 3];
        const uint32_t gw = (i & 4) ? ((i & 2) ? gv.w : gv.z) : ((i & 2) ? gv.y : gv.x);
        x2[i] = fma_bf2(gw, pack_bf16(a1[2 * i], a1[2 * i + 1]), x2[i]);
        const float v0 = bf_lo(x2[i]), v1 = bf_hi(x2[i]);
        s[i & 1] += v0 + v1; q2[i & 1] = fmaf(v0, v0, fmaf(v1, v1, q2[i & 1]));
      }
      #pragma unroll
      for (int o2 = 1; o2 <= 2; o2 <<= 1)
        #pragma unroll
        for (int h = 0; h < 2; h++) { s[h] += __shfl_xor_sync(0xffffffffu, s[h], o2); q2[h] += __shfl_xor_sync(0xffffffffu, q2[h], o2); }
      uint4* const sm = g_st2 + (mb * 8 + wid) * 64 + g;
      st_rlx_v4(sm + j * 8, __float_as_uint(s[0]), __float_as_uint(q2[0]), __float_as_uint(s[1]), __float_as_uint(q2[1]), qd == 0);
      PROF(19, tid == 0);
      uint4 sb[4], cb[4];
      #pragma unroll
      for (int q = 0; q < 4; q++) { sb[q] = lds128(vec + 256 + q * 64); cb[q] = lds128(vec + 512 + q * 64); }
      uint4 p0, p1;
      while (true) {
        p0 = ld_rlx_v4(sm + qd * 16); p1 = ld_rlx_v4(sm + qd * 16 + 8);
        const bool ok = p0.x != ~0u && p0.y != ~0u && p0.z != ~0u && p0.w != ~0u && p1.x != ~0u && p1.y != ~0u && p1.z != ~0u && p1.w != ~0u;
        if (poll_done(ok, dl)) break;
      }
      PROF(20, tid == 0);
      s[0] = __uint_as_float(p0.x) + __uint_as_float(p1.x); q2[0] = __uint_as_float(p0.y) + __uint_as_float(p1.y);
      s[1] = __uint_as_float(p0.z) + __uint_as_float(p1.z); q2[1] = __uint_as_float(p0.w) + __uint_as_float(p1.w);
      #pragma unroll
      for (int o2 = 1; o2 <= 2; o2 <<= 1)
        #pragma unroll
        for (int h = 0; h < 2; h++) { s[h] += __shfl_xor_sync(0xffffffffu, s[h], o2); q2[h] += __shfl_xor_sync(0xffffffffu, q2[h], o2); }
      #pragma unroll
      for (int h = 0; h < 2; h++) {
        const float m = s[h] * (1.f / D_);
        ln_row(ln, h, m, rsqrtf(fmaxf(q2[h] * (1.f / D_) - m * m, 0.f) + 1e-5f));
      }
      #pragma unroll
      for (int jj = 0; jj < 8; jj++) {
        const uint32_t cl = (jj & 1) ? cb[jj >> 1].z : cb[jj >> 1].x, ch = (jj & 1) ? cb[jj >> 1].w : cb[jj >> 1].y;
        const uint32_t sl = (jj & 1) ? sb[jj >> 1].z : sb[jj >> 1].x, sh = (jj & 1) ? sb[jj >> 1].w : sb[jj >> 1].y;
        stmatrix_x4((sbase + SM_STG + (jj >> 2) * 16384 + frag) ^ ((jj & 3) << 5), ln_mod(x2[4 * jj], ln, 0, cl, sl), ln_mod(x2[4 * jj + 1], ln, 1, cl, sl),
                    ln_mod(x2[4 * jj + 2], ln, 0, ch, sh), ln_mod(x2[4 * jj + 3], ln, 1, ch, sh));
      }
      fence_proxy_async_smem();
      mbar_arrive_e(sbase + B_STREQ);
      bar_sync(NB_WG + wg, 128);
      PROF(21, tid == 0);
    }

    undef_regs(a0);
    #pragma unroll
    for (int t = 0; t < 2; t++) {
      const uint32_t slot = m_wait(sbase, r);
      mma_step(a0, sbase + SM_STG + t * 16384 + wgoff, slot, t == 0, t == 0 ? 0 : m_prev(sbase, r));
      mma_step(a1, sbase + SM_STG + t * 16384 + wgoff, slot + 16384, t == 0, 0);
      m_next(r);
    }
    PROF(22, tid == 0);
    #pragma unroll 1
    for (int t = 0; t < 7; t += 2) {
      g_switch(a1, a0, t == 0 ? 14 : 11, t > 0, 5 + t, sbase, wgoff, frag, r);
      if (t == 6) break;
      g_switch(a0, a1, t == 0 ? 9 : 11, true, 6 + t, sbase, wgoff, frag, r);
    }
    #pragma unroll 1
    for (int i = 5; i < 56; i++) m_step(a1, sbase, wgoff, r);
    {
      mbar_wait(sbase + B_STFREE, 1, dl);
      mbar_wait(sbase + B_VEC + 8, 0, dl);
      uint4 gb[4];
      #pragma unroll
      for (int q = 0; q < 4; q++) gb[q] = lds128(sbase + SM_VEC + 768 + qd * 16 + q * 64);
      wgmma_wait<0>();
      fence_regs(a1);
      PROF(50, tid == 0);
      #pragma unroll
      for (int t = 0; t < 2; t++) {
        #pragma unroll
        for (int jj = 4 * t; jj < 4 * t + 4; jj++) {
          const uint32_t gl = (jj & 1) ? gb[jj >> 1].z : gb[jj >> 1].x, gh = (jj & 1) ? gb[jj >> 1].w : gb[jj >> 1].y;
          const int i = 8 * jj;
          stmatrix_x4((sbase + SM_STG + t * 16384 + frag) ^ ((jj & 3) << 5),
                      fma_bf2(gl, pack_bf16(a1[i], a1[i + 1]), x2[4 * jj]), fma_bf2(gl, pack_bf16(a1[i + 2], a1[i + 3]), x2[4 * jj + 1]),
                      fma_bf2(gh, pack_bf16(a1[i + 4], a1[i + 5]), x2[4 * jj + 2]), fma_bf2(gh, pack_bf16(a1[i + 6], a1[i + 7]), x2[4 * jj + 3]));
        }
        fence_proxy_async_smem();
        tma_store_3d(&maps.out, slab + t * 16384, j * 128 + t * 64, mb * 64 + warp * 16, wg);
      }
      bulk_commit();
      st_rlx(tid == 0 ? flags + FO_EPOCH : &g_flags[FL_EPOCH], e1, j == 0 && (tid == 0 || (tid == 1 && mb == 0)));
      bulk_wait_read0();
      PROFN(51, tid == 0);
    }
  }
}

typedef CUresult (*PFN_encodeTiled)(CUtensorMap*, CUtensorMapDataType, cuuint32_t, void*, const cuuint64_t*, const cuuint64_t*,
                                    const cuuint32_t*, const cuuint32_t*, CUtensorMapInterleave, CUtensorMapSwizzle,
                                    CUtensorMapL2promotion, CUtensorMapFloatOOBfill);

void encode(PFN_encodeTiled fn, CUtensorMap* m, const void* ptr, int rank, const cuuint64_t* dims, const cuuint64_t* strides,
            const cuuint32_t* box) {
  const cuuint32_t es[5] = {1, 1, 1, 1, 1};
  fn(m, CU_TENSOR_MAP_DATA_TYPE_BFLOAT16, rank, const_cast<void*>(ptr), dims, strides, box, es, CU_TENSOR_MAP_INTERLEAVE_NONE,
     CU_TENSOR_MAP_SWIZZLE_128B, CU_TENSOR_MAP_L2_PROMOTION_L2_256B, CU_TENSOR_MAP_FLOAT_OOB_FILL_NONE);
}
void map2d(PFN_encodeTiled fn, CUtensorMap* m, const void* ptr, int cols, int rows, int boxrows) {
  const cuuint64_t dims[2] = {(cuuint64_t)cols, (cuuint64_t)rows}, strides[1] = {(cuuint64_t)cols * 2};
  const cuuint32_t box[2] = {64, (cuuint32_t)boxrows};
  encode(fn, m, ptr, 2, dims, strides, box);
}
void map_w2chunk(PFN_encodeTiled fn, CUtensorMap* m, const void* ptr, int cols, int rows) {
  const cuuint64_t dims[3] = {64, (cuuint64_t)rows, (cuuint64_t)cols / 64}, strides[2] = {(cuuint64_t)cols * 2, 128};
  const cuuint32_t box[3] = {64, 64, 2};
  encode(fn, m, ptr, 3, dims, strides, box);
}
void map_parity(PFN_encodeTiled fn, CUtensorMap* m, const void* ptr, int boxpairs, int boxpar) {
  const cuuint64_t dims[3] = {D_, S_ / 2, 2}, strides[2] = {D_ * 4, D_ * 2};
  const cuuint32_t box[3] = {64, (cuuint32_t)boxpairs, (cuuint32_t)boxpar};
  encode(fn, m, ptr, 3, dims, strides, box);
}

}

extern "C" void kernel_launch(void* const* d_in, const int* in_sizes, int n_in, void* d_out, int out_size) {
  (void)in_sizes; (void)n_in; (void)out_size;
  const bf16* x = (const bf16*)d_in[0];
  const bf16* wqkv = (const bf16*)d_in[1];
  const bf16* wo = (const bf16*)d_in[2];
  const bf16* w1 = (const bf16*)d_in[4];
  const bf16* w3 = (const bf16*)d_in[5];
  const bf16* w2 = (const bf16*)d_in[6];
  const bf16* cvec = (const bf16*)d_in[7];
  const bf16* w_mod = (const bf16*)d_in[8];

  static PFN_encodeTiled fn = nullptr;
  static Maps maps;
  static const void* cached[8] = {};
  static int sms = 0;
  if (!fn) {
    void* p = nullptr; cudaDriverEntryPointQueryResult st;
    cudaGetDriverEntryPoint("cuTensorMapEncodeTiled", &p, cudaEnableDefault, &st);
    fn = (PFN_encodeTiled)p;
    cudaFuncSetAttribute(fused_block_kernel, cudaFuncAttributeMaxDynamicSharedMemorySize, SM_TOTAL);
    int dev = 0;
    cudaGetDevice(&dev);
    cudaDeviceGetAttribute(&sms, cudaDevAttrMultiProcessorCount, dev);
  }
  const void* cur[8] = {x, wqkv, wo, w1, w3, w2, d_out, w_mod};
  bool same = true;
  for (int i = 0; i < 8; i++) same = same && cached[i] == cur[i];
  if (!same) {
    void *o, *h2, *hh;
    cudaGetSymbolAddress(&hh, g_hh); cudaGetSymbolAddress(&o, g_o);
    h2 = o;
    map_parity(fn, &maps.x, x, 64, 2); map_parity(fn, &maps.out, d_out, 16, 1);
    map2d(fn, &maps.o, o, D_, S_, 128); map2d(fn, &maps.h2, h2, D_, S_, 128);
    {
      const cuuint64_t dims[3] = {512, (cuuint64_t)S_, 7}, strides[2] = {1024, (cuuint64_t)S_ * 1024};
      const cuuint32_t box[3] = {64, 128, 1};
      encode(fn, &maps.hh, hh, 3, dims, strides, box);
    }
    {
      const cuuint64_t dims[4] = {64, 1024, 16, 2}, strides[3] = {3072 * 2, 128, 2048};
      const cuuint64_t dimv[4] = {64, 1024, 8, 2}, stridev[3] = {3072 * 2, 128, 1024};
      const cuuint32_t box[4] = {64, 64, 1, 2};
      encode(fn, &maps.wqk, wqkv, 4, dims, strides, box);
      encode(fn, &maps.wvv, wqkv + 2048, 4, dimv, stridev, box);
    }
    map_w2chunk(fn, &maps.wo, wo, D_, D_); map_w2chunk(fn, &maps.w2, w2, D_, F_);
    map2d(fn, &maps.w1, w1, F_, D_, 64); map2d(fn, &maps.w3, w3, F_, D_, 64);
    map2d(fn, &maps.wmod, w_mod, 6 * D_, D_, 256);
    for (int i = 0; i < 8; i++) cached[i] = cur[i];
  }
  if (sms >= NCTA + NAUX) {
    fused_block_kernel<<<NCTA + NAUX, 384, SM_TOTAL>>>(maps, x, cvec, w_mod, 0);
  } else {
    fused_block_kernel<<<NAUX, 384, SM_TOTAL>>>(maps, x, cvec, w_mod, 0);
    fused_block_kernel<<<NCTA, 384, SM_TOTAL>>>(maps, x, cvec, w_mod, NAUX);
  }
}
```

```cpp
#include <cuda.h>
#include <cuda_runtime.h>
#include <cuda_bf16.h>
#include <stdint.h>

namespace {

typedef __nv_bfloat16 bf16;

constexpr int S_ = 2048, D_ = 1024, F_ = 3584;
constexpr int NCTA = 128, NAUX = 4;

__device__ __align__(1024) bf16 g_o[S_ * D_];
__device__ __align__(1024) bf16 g_hh[S_ * F_];
__device__ __align__(1024) float g_mod[8 * 6 * D_];
__device__ __align__(1024) uint2 g_ln1[16 * 8 * 16];
__device__ __align__(1024) uint4 g_halo[16 * 16 * 2 * 4 * 32];
__device__ __align__(1024) uint4 g_st2[16 * 8 * 8 * 8];
constexpr int FO_EPOCH = 0, FO_O = 1, FO_HH = 4, FO_H1 = 11, FL_EPOCH = 16 * 32, FL_RESET = FL_EPOCH + 1, FL_LN1 = FL_EPOCH + 2, FL_H2 = FL_EPOCH + 3;
__device__ __align__(1024) unsigned g_flags[17 * 32];

#define PROF(slot, on) do {} while (0)
#define PROFN(slot, on) do {} while (0)
#define PROFW_DECL do {} while (0)
#define PROFW(stmt) do {} while (0)
#define PROFW_OUT(slot, on) do {} while (0)

__device__ __forceinline__ uint32_t smem_u32(const void* p) { return (uint32_t)__cvta_generic_to_shared(p); }
__device__ __forceinline__ void mbar_init(uint32_t bar, uint32_t count) {
  asm volatile("mbarrier.init.shared::cta.b64 [%0], %1;" :: "r"(bar), "r"(count));
}
#define ELECT "{\n.reg .pred p;\nelect.sync _|p, 0xffffffff;\n@p "
__device__ __forceinline__ void mbar_expect_tx_e(uint32_t bar, uint32_t bytes) {
  asm volatile(ELECT "mbarrier.arrive.expect_tx.shared::cta.b64 _, [%0], %1;\n}" :: "r"(bar), "r"(bytes) : "memory");
}
__device__ __forceinline__ void mbar_arrive_e(uint32_t bar) {
  asm volatile(ELECT "mbarrier.arrive.shared::cta.b64 _, [%0];\n}" :: "r"(bar) : "memory");
}
__device__ __forceinline__ uint32_t clock32() { uint32_t t; asm volatile("mov.u32 %0, %%clock;" : "=r"(t)); return t; }
__device__ __forceinline__ void mbar_wait(uint32_t bar, uint32_t parity, uint32_t dl) {
  asm volatile("{\n.reg .pred p;\n.reg .b32 t;\n"
               "LAB_WAIT:\n"
               "mbarrier.try_wait.parity.shared::cta.b64 p, [%0], %1;\n"
               "@p bra LAB_DONE;\n"
               "mov.u32 t, %%clock;\n"
               "sub.s32 t, t, %2;\n"
               "setp.lt.s32 p, t, 0;\n"
               "@p bra LAB_WAIT;\n"
               "LAB_DONE:\n}" :: "r"(bar), "r"(parity), "r"(dl) : "memory");
}
__device__ __forceinline__ void mbar_sleep(uint32_t bar, uint32_t parity, uint32_t dl) {
  asm volatile("{\n.reg .pred p;\n.reg .b32 t;\n"
               "LAB_WAIT:\n"
               "mbarrier.try_wait.parity.shared::cta.b64 p, [%0], %1, 20000;\n"
               "@p bra LAB_DONE;\n"
               "mov.u32 t, %%clock;\n"
               "sub.s32 t, t, %2;\n"
               "setp.lt.s32 p, t, 0;\n"
               "@p bra LAB_WAIT;\n"
               "LAB_DONE:\n}" :: "r"(bar), "r"(parity), "r"(dl) : "memory");
}
__device__ __forceinline__ bool poll_done(bool ok, uint32_t dl) {
  return __all_sync(0xffffffffu, ok || (int)(clock32() - dl) >= 0);
}
__device__ __forceinline__ unsigned ld_relaxed(const unsigned* p) {
  unsigned v; asm volatile("ld.relaxed.gpu.global.u32 %0, [%1];" : "=r"(v) : "l"(p) : "memory"); return v;
}
__device__ __forceinline__ void red_add_e(unsigned* p, unsigned v) {
  asm volatile(ELECT "red.relaxed.gpu.global.add.u32 [%0], %1;\n}" :: "l"(p), "r"(v) : "memory");
}
__device__ __forceinline__ void wait_flag(const unsigned* p, unsigned target, uint32_t dl) {
  asm volatile("{\n.reg .pred p;\n.reg .b32 t;\n"
               "LAB_WAIT:\n"
               "ld.relaxed.gpu.global.u32 t, [%0];\n"
               "sub.s32 t, t, %1;\n"
               "setp.ge.s32 p, t, 0;\n"
               "@p bra LAB_DONE;\n"
               "mov.u32 t, %%clock;\n"
               "sub.s32 t, t, %2;\n"
               "setp.lt.s32 p, t, 0;\n"
               "@p bra LAB_WAIT;\n"
               "LAB_DONE:\n}" :: "l"(p), "r"(target), "r"(dl) : "memory");
}
__device__ __forceinline__ void wait_until(uint32_t t) { while ((int)(clock32() - t) < 0) {} }
__device__ __forceinline__ void fence_proxy_async_smem() { asm volatile("fence.proxy.async.shared::cta;" ::: "memory"); }

__device__ __forceinline__ void tma_load_2d(uint32_t dst, const CUtensorMap* m, uint32_t bar, int c0, int c1) {
  asm volatile(ELECT "cp.async.bulk.tensor.2d.shared::cluster.global.mbarrier::complete_tx::bytes [%0], [%1, {%3, %4}], [%2];\n}"
               :: "r"(dst), "l"(m), "r"(bar), "r"(c0), "r"(c1) : "memory");
}
__device__ __forceinline__ void tma_load_3d(uint32_t dst, const CUtensorMap* m, uint32_t bar, int c0, int c1, int c2) {
  asm volatile(ELECT "cp.async.bulk.tensor.3d.shared::cluster.global.mbarrier::complete_tx::bytes [%0], [%1, {%3, %4, %5}], [%2];\n}"
               :: "r"(dst), "l"(m), "r"(bar), "r"(c0), "r"(c1), "r"(c2) : "memory");
}
__device__ __forceinline__ void tma_load_4d(uint32_t dst, const CUtensorMap* m, uint32_t bar, int c0, int c1, int c2, int c3) {
  asm volatile(ELECT "cp.async.bulk.tensor.4d.shared::cluster.global.mbarrier::complete_tx::bytes [%0], [%1, {%3, %4, %5, %6}], [%2];\n}"
               :: "r"(dst), "l"(m), "r"(bar), "r"(c0), "r"(c1), "r"(c2), "r"(c3) : "memory");
}
__device__ __forceinline__ void tma_store_2d(const CUtensorMap* m, uint32_t src, int c0, int c1) {
  asm volatile(ELECT "cp.async.bulk.tensor.2d.global.shared::cta.bulk_group [%0, {%2, %3}], [%1];\n}"
               :: "l"(m), "r"(src), "r"(c0), "r"(c1) : "memory");
}
__device__ __forceinline__ void tma_store_3d(const CUtensorMap* m, uint32_t src, int c0, int c1, int c2) {
  asm volatile(ELECT "cp.async.bulk.tensor.3d.global.shared::cta.bulk_group [%0, {%2, %3, %4}], [%1];\n}"
               :: "l"(m), "r"(src), "r"(c0), "r"(c1), "r"(c2) : "memory");
}
__device__ __forceinline__ void bulk_load(uint32_t dst, const void* src, uint32_t bytes, uint32_t bar) {
  asm volatile(ELECT "cp.async.bulk.shared::cluster.global.mbarrier::complete_tx::bytes [%0], [%1], %2, [%3];\n}"
               :: "r"(dst), "l"(src), "r"(bytes), "r"(bar) : "memory");
}
__device__ __forceinline__ void bulk_prefetch(const void* src, uint32_t bytes) {
  asm volatile(ELECT "cp.async.bulk.prefetch.L2.global [%0], %1;\n}" :: "l"(src), "r"(bytes) : "memory");
}
__device__ __forceinline__ void bulk_commit() { asm volatile("cp.async.bulk.commit_group;" ::: "memory"); }
__device__ __forceinline__ void bulk_wait0() { asm volatile("cp.async.bulk.wait_group 0;" ::: "memory"); }
__device__ __forceinline__ void bulk_wait_read0() { asm volatile("cp.async.bulk.wait_group.read 0;" ::: "memory"); }
__device__ __forceinline__ void prefetch_tmap(const CUtensorMap* m) { asm volatile("prefetch.tensormap [%0];" :: "l"(m) : "memory"); }
__device__ __forceinline__ void wgmma_fence() { asm volatile("wgmma.fence.sync.aligned;" ::: "memory"); }
__device__ __forceinline__ void wgmma_commit() { asm volatile("wgmma.commit_group.sync.aligned;" ::: "memory"); }
template <int N> __device__ __forceinline__ void wgmma_wait() { asm volatile("wgmma.wait_group.sync.aligned %0;" :: "n"(N) : "memory"); }
template <int R> __device__ __forceinline__ void reg_alloc() { asm volatile("setmaxnreg.inc.sync.aligned.u32 %0;" :: "n"(R)); }
template <int R> __device__ __forceinline__ void reg_dealloc() { asm volatile("setmaxnreg.dec.sync.aligned.u32 %0;" :: "n"(R)); }
__device__ __forceinline__ void bar_sync(int id, int n) { asm volatile("bar.sync %0, %1;" :: "r"(id), "r"(n) : "memory"); }
__device__ __forceinline__ void sched_fence() {
  asm volatile("{\n.reg .pred p;\n.reg .b32 t;\nLAB_F:\nmov.u32 t, %%clock;\nsetp.eq.u32 p, t, %0;\n@p bra LAB_F;\n}" :: "n"(0) : "memory");
}
template <int N> __device__ __forceinline__ void fence_regs(float (&a)[N]) {
  #pragma unroll
  for (int i = 0; i < N; i++) asm volatile("" : "+f"(a[i]) :: "memory");
}
template <int N> __device__ __forceinline__ void undef_regs(float (&a)[N]) {
  #pragma unroll
  for (int i = 0; i < N; i++) asm volatile("" : "=f"(a[i]));
}

__device__ __forceinline__ uint64_t desc_from_lo(uint32_t lo) { return (uint64_t)lo | ((uint64_t)0x40000040u << 32); }
__device__ __forceinline__ uint32_t pack_bf16(float lo, float hi) {
  uint32_t r; asm("cvt.rn.bf16x2.f32 %0, %1, %2;" : "=r"(r) : "f"(hi), "f"(lo)); return r;
}
__device__ __forceinline__ uint32_t fma_bf2(uint32_t a, uint32_t b, uint32_t c) {
  uint32_t d; asm("fma.rn.bf16x2 %0, %1, %2, %3;" : "=r"(d) : "r"(a), "r"(b), "r"(c)); return d;
}
__device__ __forceinline__ float bf_lo(uint32_t v) { return __uint_as_float(v << 16); }
__device__ __forceinline__ float bf_hi(uint32_t v) { return __uint_as_float(v & 0xFFFF0000u); }
__device__ __forceinline__ float bf16_round(float x) { return bf_lo(pack_bf16(x, 0.f)); }
__device__ __forceinline__ void stmatrix_x4(uint32_t addr, uint32_t r0, uint32_t r1, uint32_t r2, uint32_t r3) {
  asm volatile("stmatrix.sync.aligned.m8n8.x4.shared.b16 [%0], {%1, %2, %3, %4};" :: "r"(addr), "r"(r0), "r"(r1), "r"(r2), "r"(r3) : "memory");
}
__device__ __forceinline__ void ldmatrix_x4(uint32_t addr, uint32_t& r0, uint32_t& r1, uint32_t& r2, uint32_t& r3) {
  asm volatile("ldmatrix.sync.aligned.m8n8.x4.shared.b16 {%0, %1, %2, %3}, [%4];" : "=r"(r0), "=r"(r1), "=r"(r2), "=r"(r3) : "r"(addr) : "memory");
}
__device__ __forceinline__ void ldmatrix_x4_t(uint32_t addr, uint32_t (&r)[4]) {
  asm volatile("ldmatrix.sync.aligned.m8n8.x4.trans.shared.b16 {%0, %1, %2, %3}, [%4];" : "=r"(r[0]), "=r"(r[1]), "=r"(r[2]), "=r"(r[3]) : "r"(addr) : "memory");
}
__device__ __forceinline__ uint32_t tagf(float v, unsigned par) { return (__float_as_uint(v) & ~1u) | par; }
__device__ __forceinline__ void st_rlx(void* p, uint32_t a, bool on) {
  asm volatile("{\n.reg .pred p;\nsetp.ne.b32 p, %2, 0;\n@p st.relaxed.gpu.global.u32 [%0], %1;\n}" :: "l"(p), "r"(a), "r"((int)on) : "memory");
}
__device__ __forceinline__ void st_rlx_v2(void* p, uint32_t a, uint32_t b, bool on) {
  asm volatile("{\n.reg .pred p;\nsetp.ne.b32 p, %3, 0;\n@p st.relaxed.gpu.global.v2.u32 [%0], {%1, %2};\n}" :: "l"(p), "r"(a), "r"(b), "r"((int)on) : "memory");
}
__device__ __forceinline__ uint2 ld_rlx_v2(const void* p) {
  uint2 v; asm volatile("ld.relaxed.gpu.global.v2.u32 {%0,%1}, [%2];" : "=r"(v.x), "=r"(v.y) : "l"(p) : "memory"); return v;
}
__device__ __forceinline__ void st_rlx_v4(void* p, uint32_t a, uint32_t b, uint32_t c, uint32_t d, bool on) {
  asm volatile("{\n.reg .pred p;\nsetp.ne.b32 p, %5, 0;\n@p st.relaxed.gpu.global.v4.u32 [%0], {%1, %2, %3, %4};\n}"
               :: "l"(p), "r"(a), "r"(b), "r"(c), "r"(d), "r"((int)on) : "memory");
}
__device__ __forceinline__ uint4 ld_rlx_v4(const void* p) {
  uint4 v; asm volatile("ld.relaxed.gpu.global.v4.u32 {%0,%1,%2,%3}, [%4];" : "=r"(v.x), "=r"(v.y), "=r"(v.z), "=r"(v.w) : "l"(p) : "memory"); return v;
}
__device__ __forceinline__ uint32_t movmatrix_t(uint32_t a) {
  uint32_t d; asm volatile("movmatrix.sync.aligned.m8n8.trans.b16 %0, %1;" : "=r"(d) : "r"(a)); return d;
}
__device__ __forceinline__ void mma16(float (&c)[4], uint32_t a0, uint32_t a1, uint32_t a2, uint32_t a3, uint32_t b0, uint32_t b1) {
  asm volatile("mma.sync.aligned.m16n8k16.row.col.f32.bf16.bf16.f32 {%0,%1,%2,%3}, {%4,%5,%6,%7}, {%8,%9}, {%0,%1,%2,%3};"
               : "+f"(c[0]), "+f"(c[1]), "+f"(c[2]), "+f"(c[3]) : "r"(a0), "r"(a1), "r"(a2), "r"(a3), "r"(b0), "r"(b1));
}
__device__ __forceinline__ void mma8(float (&c)[4], uint32_t a0, uint32_t a1, uint32_t b0) {
  asm volatile("mma.sync.aligned.m16n8k8.row.col.f32.bf16.bf16.f32 {%0,%1,%2,%3}, {%4,%5}, {%6}, {%0,%1,%2,%3};"
               : "+f"(c[0]), "+f"(c[1]), "+f"(c[2]), "+f"(c[3]) : "r"(a0), "r"(a1), "r"(b0));
}
__device__ __forceinline__ void sts128(uint32_t addr, uint32_t a, uint32_t b, uint32_t c, uint32_t d) {
  asm volatile("st.shared.v4.b32 [%0], {%1,%2,%3,%4};" :: "r"(addr), "r"(a), "r"(b), "r"(c), "r"(d) : "memory");
}
__device__ __forceinline__ uint4 lds128(uint32_t addr) {
  uint4 v; asm volatile("ld.shared.v4.b32 {%0,%1,%2,%3}, [%4];" : "=r"(v.x), "=r"(v.y), "=r"(v.z), "=r"(v.w) : "r"(addr) : "memory"); return v;
}
__device__ __forceinline__ float2 lds64f(uint32_t addr) {
  float2 v; asm volatile("ld.shared.v2.f32 {%0,%1}, [%2];" : "=f"(v.x), "=f"(v.y) : "r"(addr) : "memory"); return v;
}
__device__ __forceinline__ void sts64(uint32_t addr, uint32_t a, uint32_t b) {
  asm volatile("st.shared.v2.b32 [%0], {%1, %2};" :: "r"(addr), "r"(a), "r"(b) : "memory");
}
__device__ __forceinline__ float fast_ex2(float x) { float y; asm("ex2.approx.ftz.f32 %0, %1;" : "=f"(y) : "f"(x)); return y; }
__device__ __forceinline__ float fast_rcp(float x) { float y; asm("rcp.approx.ftz.f32 %0, %1;" : "=f"(y) : "f"(x)); return y; }
__device__ __forceinline__ float silu_f(float g) { return g * fast_rcp(1.f + fast_ex2(g * -1.4426950408889634f)); }
__device__ __forceinline__ float swiglu(float g, float u) {
  const float h = 0.5f * g;
  float t; asm("tanh.approx.f32 %0, %1;" : "=f"(t) : "f"(h));
  return fmaf(h, t, h) * u;
}

__device__ __forceinline__ void wgmma_m64n128k16_ss(float (&d)[64], uint64_t descA, uint64_t descB, int scaleD) {
  asm volatile("{\n.reg .pred p;\nsetp.ne.b32 p, %66, 0;\n"
    "wgmma.mma_async.sync.aligned.m64n128k16.f32.bf16.bf16 "
    "{%0, %1, %2, %3, %4, %5, %6, %7, %8, %9, %10, %11, %12, %13, %14, %15, "
    "%16, %17, %18, %19, %20, %21, %22, %23, %24, %25, %26, %27, %28, %29, %30, %31, "
    "%32, %33, %34, %35, %36, %37, %38, %39, %40, %41, %42, %43, %44, %45, %46, %47, "
    "%48, %49, %50, %51, %52, %53, %54, %55, %56, %57, %58, %59, %60, %61, %62, %63}, "
    "%64, %65, p, 1, 1, 0, 1;\n}\n"
    : "+f"(d[0]), "+f"(d[1]), "+f"(d[2]), "+f"(d[3]), "+f"(d[4]), "+f"(d[5]), "+f"(d[6]), "+f"(d[7]),
      "+f"(d[8]), "+f"(d[9]), "+f"(d[10]), "+f"(d[11]), "+f"(d[12]), "+f"(d[13]), "+f"(d[14]), "+f"(d[15]),
      "+f"(d[16]), "+f"(d[17]), "+f"(d[18]), "+f"(d[19]), "+f"(d[20]), "+f"(d[21]), "+f"(d[22]), "+f"(d[23]),
      "+f"(d[24]), "+f"(d[25]), "+f"(d[26]), "+f"(d[27]), "+f"(d[28]), "+f"(d[29]), "+f"(d[30]), "+f"(d[31]),
      "+f"(d[32]), "+f"(d[33]), "+f"(d[34]), "+f"(d[35]), "+f"(d[36]), "+f"(d[37]), "+f"(d[38]), "+f"(d[39]),
      "+f"(d[40]), "+f"(d[41]), "+f"(d[42]), "+f"(d[43]), "+f"(d[44]), "+f"(d[45]), "+f"(d[46]), "+f"(d[47]),
      "+f"(d[48]), "+f"(d[49]), "+f"(d[50]), "+f"(d[51]), "+f"(d[52]), "+f"(d[53]), "+f"(d[54]), "+f"(d[55]),
      "+f"(d[56]), "+f"(d[57]), "+f"(d[58]), "+f"(d[59]), "+f"(d[60]), "+f"(d[61]), "+f"(d[62]), "+f"(d[63])
    : "l"(descA), "l"(descB), "r"(scaleD));
}
__device__ __forceinline__ void wgmma_m64n256k16_rs(float (&d)[128], uint32_t a0, uint32_t a1, uint32_t a2, uint32_t a3, uint64_t descB, int scaleD) {
  asm volatile("{\n.reg .pred p;\nsetp.ne.b32 p, %133, 0;\n"
    "wgmma.mma_async.sync.aligned.m64n256k16.f32.bf16.bf16 "
    "{%0, %1, %2, %3, %4, %5, %6, %7, %8, %9, %10, %11, %12, %13, %14, %15, "
    "%16, %17, %18, %19, %20, %21, %22, %23, %24, %25, %26, %27, %28, %29, %30, %31, "
    "%32, %33, %34, %35, %36, %37, %38, %39, %40, %41, %42, %43, %44, %45, %46, %47, "
    "%48, %49, %50, %51, %52, %53, %54, %55, %56, %57, %58, %59, %60, %61, %62, %63, "
    "%64, %65, %66, %67, %68, %69, %70, %71, %72, %73, %74, %75, %76, %77, %78, %79, "
    "%80, %81, %82, %83, %84, %85, %86, %87, %88, %89, %90, %91, %92, %93, %94, %95, "
    "%96, %97, %98, %99, %100, %101, %102, %103, %104, %105, %106, %107, %108, %109, %110, %111, "
    "%112, %113, %114, %115, %116, %117, %118, %119, %120, %121, %122, %123, %124, %125, %126, %127}, "
    "{%128, %129, %130, %131}, %132, p, 1, 1, 1;\n}\n"
    : "+f"(d[0]), "+f"(d[1]), "+f"(d[2]), "+f"(d[3]), "+f"(d[4]), "+f"(d[5]), "+f"(d[6]), "+f"(d[7]),
      "+f"(d[8]), "+f"(d[9]), "+f"(d[10]), "+f"(d[11]), "+f"(d[12]), "+f"(d[13]), "+f"(d[14]), "+f"(d[15]),
      "+f"(d[16]), "+f"(d[17]), "+f"(d[18]), "+f"(d[19]), "+f"(d[20]), "+f"(d[21]), "+f"(d[22]), "+f"(d[23]),
      "+f"(d[24]), "+f"(d[25]), "+f"(d[26]), "+f"(d[27]), "+f"(d[28]), "+f"(d[29]), "+f"(d[30]), "+f"(d[31]),
      "+f"(d[32]), "+f"(d[33]), "+f"(d[34]), "+f"(d[35]), "+f"(d[36]), "+f"(d[37]), "+f"(d[38]), "+f"(d[39]),
      "+f"(d[40]), "+f"(d[41]), "+f"(d[42]), "+f"(d[43]), "+f"(d[44]), "+f"(d[45]), "+f"(d[46]), "+f"(d[47]),
      "+f"(d[48]), "+f"(d[49]), "+f"(d[50]), "+f"(d[51]), "+f"(d[52]), "+f"(d[53]), "+f"(d[54]), "+f"(d[55]),
      "+f"(d[56]), "+f"(d[57]), "+f"(d[58]), "+f"(d[59]), "+f"(d[60]), "+f"(d[61]), "+f"(d[62]), "+f"(d[63]),
      "+f"(d[64]), "+f"(d[65]), "+f"(d[66]), "+f"(d[67]), "+f"(d[68]), "+f"(d[69]), "+f"(d[70]), "+f"(d[71]),
      "+f"(d[72]), "+f"(d[73]), "+f"(d[74]), "+f"(d[75]), "+f"(d[76]), "+f"(d[77]), "+f"(d[78]), "+f"(d[79]),
      "+f"(d[80]), "+f"(d[81]), "+f"(d[82]), "+f"(d[83]), "+f"(d[84]), "+f"(d[85]), "+f"(d[86]), "+f"(d[87]),
      "+f"(d[88]), "+f"(d[89]), "+f"(d[90]), "+f"(d[91]), "+f"(d[92]), "+f"(d[93]), "+f"(d[94]), "+f"(d[95]),
      "+f"(d[96]), "+f"(d[97]), "+f"(d[98]), "+f"(d[99]), "+f"(d[100]), "+f"(d[101]), "+f"(d[102]), "+f"(d[103]),
      "+f"(d[104]), "+f"(d[105]), "+f"(d[106]), "+f"(d[107]), "+f"(d[108]), "+f"(d[109]), "+f"(d[110]), "+f"(d[111]),
      "+f"(d[112]), "+f"(d[113]), "+f"(d[114]), "+f"(d[115]), "+f"(d[116]), "+f"(d[117]), "+f"(d[118]), "+f"(d[119]),
      "+f"(d[120]), "+f"(d[121]), "+f"(d[122]), "+f"(d[123]), "+f"(d[124]), "+f"(d[125]), "+f"(d[126]), "+f"(d[127])
    : "r"(a0), "r"(a1), "r"(a2), "r"(a3), "l"(descB), "r"(scaleD));
}

constexpr uint32_t MSLOT = 32768, QSLOT = 49152;
constexpr int NM = 6, NQ = 4;
constexpr uint32_t SM_X0 = 3 * QSLOT;
constexpr uint32_t SM_XR = SM_X0 + 16384;
constexpr uint32_t SM_STG = 196608;
constexpr uint32_t SM_MODT = SM_STG + 16384;
constexpr uint32_t SM_XCH = SM_STG + 16384;
constexpr uint32_t SM_BAR = SM_STG + 32768;
constexpr uint32_t SM_VEC = SM_BAR + 512;
constexpr uint32_t SM_TOTAL = SM_VEC + 1024;
constexpr uint32_t B_FQ = SM_BAR, B_EQ = SM_BAR + 32, B_FM = SM_BAR + 64, B_EM = SM_BAR + 112, B_MOD = SM_BAR + 160,
                   B_STREQ = SM_BAR + 224, B_STFREE = SM_BAR + 232, B_VEC = SM_BAR + 240  , B_X = SM_BAR + 256  , B_LN = SM_BAR + 320,
                   B_FLG = SM_BAR + 328  ;
constexpr int NB_WG = 1  , NB_CONS = 3;
#define PF_BYTES 512
#define PF2_BYTES 0
#define Q_GAP 0
#define X_POLL 6
#define HJ j
#define SVC_WAIT mbar_sleep
#define PRD_WAIT mbar_wait
#define X_UP 2
#define X_GAP 200
#define X_PER 2
#define NEARLY 2

struct Maps {
  CUtensorMap x, out;
  CUtensorMap o, h2, hh;
  CUtensorMap wqk, wvv, wo, w1, w3, w2;
  CUtensorMap wmod;
};

struct Ring { int st; uint32_t ph; int prev; uint32_t dl; };
__device__ __forceinline__ void ring_next(Ring& r) { if (++r.st == NM) { r.st = 0; r.ph ^= 1; } }

__device__ __forceinline__ void retire_prev(uint32_t rel) {
  wgmma_commit();
  wgmma_wait<1>();
  if (rel) mbar_arrive_e(rel);
}
__device__ __forceinline__ void mma_step(float (&acc)[64], uint32_t a, uint32_t b, bool first, uint32_t rel) {
  const uint32_t alo = (a >> 4) + (1u << 16), blo = (b >> 4) + (512u << 16);
  wgmma_fence();
  #pragma unroll
  for (int k = 0; k < 4; k++) {
    wgmma_m64n128k16_ss(acc, desc_from_lo(alo + k * 2), desc_from_lo(blo + k * 128), k > 0 || !first);
    if (k == 0) retire_prev(rel);
  }
  wgmma_commit();
}
__device__ __forceinline__ uint32_t m_wait(uint32_t sbase, const Ring& r) {
  mbar_wait(sbase + B_FM + 8 * r.st, r.ph, r.dl);
  return sbase + r.st * MSLOT;
}
__device__ __forceinline__ uint32_t m_prev(uint32_t sbase, const Ring& r) { return sbase + B_EM + 8 * r.prev; }
__device__ __forceinline__ void m_next(Ring& r) { r.prev = r.st; ring_next(r); }
__device__ __forceinline__ void m_step(float (&acc)[64], uint32_t sbase, uint32_t wgoff, Ring& r, bool first = false) {
  const uint32_t slot = m_wait(sbase, r);
  mma_step(acc, slot + wgoff, slot + 16384, first, m_prev(sbase, r));
  m_next(r);
}

struct LnRow { uint32_t rs[2], nb[2]; };
__device__ __forceinline__ void ln_row(LnRow& l, int h, float mean, float rstd) {
  l.rs[h] = pack_bf16(rstd, rstd);
  const float nb = -mean * bf_lo(l.rs[h]);
  l.nb[h] = pack_bf16(nb, nb);
}
__device__ __forceinline__ uint32_t ln_mod(uint32_t x, const LnRow& l, int h, uint32_t c1, uint32_t s) {
  return fma_bf2(fma_bf2(x, l.rs[h], l.nb[h]), c1, s);
}

__device__ __forceinline__ uint32_t q_wait(int u, uint32_t sbase, uint32_t dl) {
  mbar_wait(sbase + B_FQ + 8 * (u & 3), (u >> 2) & 1, dl);
  return sbase + (u & 3) * QSLOT;
}
__device__ __forceinline__ uint32_t q_empty(int u, uint32_t sbase) { return sbase + B_EQ + 8 * (u & 3); }
__device__ __forceinline__ void q_load(uint32_t (&A)[16], uint4 (&p)[4], int kk, uint32_t a, uint32_t t) {
  ldmatrix_x4(a ^ (kk << 5), A[4 * kk], A[4 * kk + 1], A[4 * kk + 2], A[4 * kk + 3]);
  p[kk] = lds128(t + kk * 64);
}
__device__ __forceinline__ void q_norm(uint32_t (&A)[16], const uint4 (&p)[4], int kk, const LnRow& l) {
  A[4 * kk + 0] = ln_mod(A[4 * kk + 0], l, 0, p[kk].x, p[kk].z); A[4 * kk + 1] = ln_mod(A[4 * kk + 1], l, 1, p[kk].x, p[kk].z);
  A[4 * kk + 2] = ln_mod(A[4 * kk + 2], l, 0, p[kk].y, p[kk].w); A[4 * kk + 3] = ln_mod(A[4 * kk + 3], l, 1, p[kk].y, p[kk].w);
}
template <bool NEXT>
__device__ __forceinline__ void q_step_rs(float (&acc)[128], uint32_t (&A)[16], uint32_t (&N)[16], uint4 (&p)[4], uint32_t slot, uint32_t frag,
                                          uint32_t t, const LnRow& l, bool first, uint32_t rel) {
  const uint32_t blo = ((slot + 16384) >> 4) + (512u << 16);
  #pragma unroll
  for (int kk = 0; kk < 4; kk++) q_norm(A, p, kk, l);
  wgmma_fence();
  #pragma unroll
  for (int kk = 0; kk < 4; kk++) {
    wgmma_m64n256k16_rs(acc, A[4 * kk], A[4 * kk + 1], A[4 * kk + 2], A[4 * kk + 3], desc_from_lo(blo + kk * 128), kk > 0 || !first);
    if (kk == 0) retire_prev(rel);
    if (NEXT && kk < 2) { q_load(N, p, 2 * kk, slot + frag, t); q_load(N, p, 2 * kk + 1, slot + frag, t); }
  }
  wgmma_commit();
}
__device__ __forceinline__ void q_stage_h1(const uint32_t (&A)[16], int u, uint32_t sbase, uint32_t frag, uint32_t dl) {
  if (u >= 8) mbar_wait(sbase + B_STFREE, 0, dl);
  #pragma unroll
  for (int kk = 0; kk < 4; kk++) stmatrix_x4((sbase + SM_STG + frag) ^ (kk << 5), A[4 * kk], A[4 * kk + 1], A[4 * kk + 2], A[4 * kk + 3]);
  fence_proxy_async_smem();
  mbar_arrive_e(sbase + B_STREQ);
}

typedef uint32_t Frag8[8];
template <int N> __device__ __forceinline__ void pack_half(Frag8& f, const float (&acc)[N], int off, int half) {
  #pragma unroll
  for (int e = 0; e < 8; e++) { f[e] = pack_bf16(acc[off + 4 * e + 2 * half], acc[off + 4 * e + 2 * half + 1]); asm volatile("" : "+r"(f[e])); }
}
__device__ __forceinline__ void transpose8(Frag8& f) {
  #pragma unroll
  for (int e = 0; e < 8; e++) f[e] = movmatrix_t(f[e]);
}
__device__ __forceinline__ void attn_send(const Frag8& f, int kv, uint32_t xch, int warp, uint4* halo_out, bool has_next) {
  if (warp == 3) {
    st_rlx_v4(halo_out + kv * 64, f[0], f[1], f[2], f[3], has_next); st_rlx_v4(halo_out + kv * 64 + 32, f[4], f[5], f[6], f[7], has_next);
  } else {
    sts128(xch + 2048 + kv * 1024, f[0], f[1], f[2], f[3]); sts128(xch + 2048 + kv * 1024 + 512, f[4], f[5], f[6], f[7]);
  }
}
template <int N>
__device__ __forceinline__ void attn_recv(uint4* p, int first, uint32_t xch, int wg, int warp, const uint4* halo_in, bool has_prev) {
  bar_sync(NB_WG + wg, 128);
  #pragma unroll
  for (int e = 0; e < N; e++)
    asm volatile("{\n.reg .pred p, q;\nsetp.ne.b32 p, %6, 0;\nsetp.ne.b32 q, %7, 0;\n"
                 "mov.b32 %0, 0;\nmov.b32 %1, 0;\nmov.b32 %2, 0;\nmov.b32 %3, 0;\n"
                 "@p ld.shared.v4.b32 {%0,%1,%2,%3}, [%4];\n@q ld.relaxed.gpu.global.v4.u32 {%0,%1,%2,%3}, [%5];\n}"
                 : "=&r"(p[e].x), "=&r"(p[e].y), "=&r"(p[e].z), "=&r"(p[e].w)
                 : "r"(xch + (first + e) * 512), "l"(halo_in + (first + e) * 32), "r"((int)(warp > 0)), "r"((int)(warp == 0 && has_prev)) : "memory");
}
template <int N>
__device__ __forceinline__ void attn_check(uint4* p, int first, int warp, const uint4* halo_in, uint32_t dl) {
  if (warp == 0) {
    while (true) {
      uint32_t m = 0;
      #pragma unroll
      for (int e = 0; e < N; e++) m = max(max(m, max(p[e].x, p[e].y)), max(p[e].z, p[e].w));
      if (poll_done(m != ~0u, dl)) break;
      #pragma unroll
      for (int e = 0; e < N; e++) p[e] = ld_rlx_v4(halo_in + (first + e) * 32);
    }
  }
}
__device__ __forceinline__ void attn_core(const Frag8& qA, const Frag8& qB, const Frag8& kA, const Frag8& kB, const Frag8& vA, const Frag8& vB,
                                          const uint4* kP, const uint4* vP, bool noprev, int lane, float (&o)[2][5][4]) {
  const int g = lane >> 2, qd = lane & 3;
  const bool s0 = 2 * qd > g, s1 = 2 * qd + 1 > g;
  const uint32_t msk = (s0 ? 0xFFFFu : 0u) | (s1 ? 0xFFFF0000u : 0u);
  constexpr float SC = 0.17677669529663687f * 1.4426950408889634f;
  float s[2][3][4];
  #pragma unroll
  for (int h = 0; h < 2; h++)
    #pragma unroll
    for (int nb = 0; nb < 3; nb++) s[h][nb][0] = s[h][nb][1] = s[h][nb][2] = s[h][nb][3] = 0.f;
  #pragma unroll
  for (int kk = 0; kk < 2; kk++)
    #pragma unroll
    for (int h = 0; h < 2; h++) {
      const int e = 4 * h + 2 * kk;
      mma16(s[h][1], qA[e], qB[e], qA[e + 1], qB[e + 1], kA[e], kA[e + 1]);
      mma16(s[h][2], qA[e], qB[e], qA[e + 1], qB[e + 1], kB[e], kB[e + 1]);
      mma16(s[h][0], qA[e], qB[e], qA[e + 1], qB[e + 1], kk ? kP[h].z : kP[h].x, kk ? kP[h].w : kP[h].y);
    }
  float l[2][4], m[2][2];
  #pragma unroll
  for (int h = 0; h < 2; h++) {
    l[h][0] = s0 ? (noprev ? -INFINITY : s[h][0][0]) : s[h][1][0];
    l[h][1] = s1 ? (noprev ? -INFINITY : s[h][0][1]) : s[h][1][1];
    l[h][2] = s0 ? s[h][1][2] : s[h][2][2];
    l[h][3] = s1 ? s[h][1][3] : s[h][2][3];
    m[h][0] = fmaxf(l[h][0], l[h][1]); m[h][1] = fmaxf(l[h][2], l[h][3]);
  }
  #pragma unroll
  for (int x = 1; x <= 2; x <<= 1)
    #pragma unroll
    for (int e = 0; e < 4; e++) m[e >> 1][e & 1] = fmaxf(m[e >> 1][e & 1], __shfl_xor_sync(0xffffffffu, m[e >> 1][e & 1], x));
  #pragma unroll
  for (int h = 0; h < 2; h++) {
    #pragma unroll
    for (int e = 0; e < 4; e++) l[h][e] = fast_ex2((l[h][e] - m[h][e >> 1]) * SC);
    const uint32_t plo = pack_bf16(l[h][0], l[h][1]), phi = pack_bf16(l[h][2], l[h][3]);
    const uint32_t vp[4] = {vP[h].x, vP[h].y, vP[h].z, vP[h].w};
    #pragma unroll
    for (int d = 0; d < 5; d++) o[h][d][0] = o[h][d][1] = o[h][d][2] = o[h][d][3] = 0.f;
    mma8(o[h][4], plo, phi, 0x3F803F80u);
    #pragma unroll
    for (int d = 0; d < 4; d++) mma16(o[h][d], plo & ~msk, phi & msk, 0u, phi & ~msk, vA[4 * h + d], vB[4 * h + d]);
    #pragma unroll
    for (int d = 0; d < 4; d++) mma8(o[h][d], plo & msk, 0u, vp[d]);
  }
}
__device__ __forceinline__ void attn_store(const float (&o)[2][5][4], int h, uint32_t sbase, uint32_t frag) {
  const float r0 = fast_rcp(o[h][4][0]), r1 = fast_rcp(o[h][4][2]);
  #pragma unroll
  for (int d = 0; d < 4; d += 2)
    stmatrix_x4((sbase + SM_STG + frag) ^ ((2 * h + (d >> 1)) << 5),
                pack_bf16(o[h][d][0] * r0, o[h][d][1] * r0), pack_bf16(o[h][d][2] * r1, o[h][d][3] * r1),
                pack_bf16(o[h][d + 1][0] * r0, o[h][d + 1][1] * r0), pack_bf16(o[h][d + 1][2] * r1, o[h][d + 1][3] * r1));
}

__device__ __forceinline__ void g_switch(float (&cur)[64], float (&prv)[64], int nrest, bool first, int n, uint32_t sbase, uint32_t wgoff,
                                         uint32_t frag, Ring& r) {
  #pragma unroll 1
  for (int i = 1; i < nrest; i++) m_step(prv, sbase, wgoff, r);
  m_step(prv, sbase, wgoff, r);
  m_step(cur, sbase, wgoff, r, first);
  mbar_wait(sbase + B_STFREE, (n - 1) & 1, r.dl);
  fence_regs(prv);
  PROF(28 + n, threadIdx.x == 0);
  #pragma unroll
  for (int jj = 0; jj < 4; jj++) {
    uint32_t p[4];
    #pragma unroll
    for (int e = 0; e < 4; e++) {
      const int i = jj * 8 + e * 2;
      p[e] = pack_bf16(swiglu(prv[i], prv[i + 32]), swiglu(prv[i + 1], prv[i + 33]));
    }
    stmatrix_x4((sbase + SM_STG + frag) ^ (jj << 5), p[0], p[1], p[2], p[3]);
    m_step(cur, sbase, wgoff, r);
  }
  fence_proxy_async_smem();
  mbar_arrive_e(sbase + B_STREQ);
}

__device__ __forceinline__ uint32_t bad2(uint32_t a, uint32_t b, unsigned par) {
  uint32_t d; asm("lop3.b32 %0, %1, %2, %3, 0x7E;" : "=r"(d) : "r"(a), "r"(b), "r"(par)); return d;
}
__device__ __forceinline__ uint32_t bad4(const uint4& v, unsigned par) { return bad2(v.x, v.y, par) | bad2(v.z, v.w, par); }
__device__ __forceinline__ uint32_t hi_halves(uint32_t lo, uint32_t hi) { return __byte_perm(lo, hi, 0x7632); }

__device__ __forceinline__ void gather_table(const float* src, uint32_t dst, uint32_t bar, unsigned par, uint32_t dl) {
  asm volatile("{\n.reg .pred p, e;\n.reg .b32 s<4>, c<4>, t<4>, w<4>;\n"
               "elect.sync _|e, 0xffffffff;\n"
               "LAB_POLL:\n"
               "ld.relaxed.gpu.global.v4.u32 {s0, s1, s2, s3}, [%0];\n"
               "ld.relaxed.gpu.global.v4.u32 {c0, c1, c2, c3}, [%0 + 4096];\n"
               "prmt.b32 w0, c0, c1, 0x7632;\nprmt.b32 w1, c2, c3, 0x7632;\nprmt.b32 w2, s0, s1, 0x7632;\nprmt.b32 w3, s2, s3, 0x7632;\n"
               "st.shared.v4.b32 [%1], {w0, w1, w2, w3};\n"
               "lop3.b32 t0, s0, s1, %3, 0x7E;\nlop3.b32 t1, s2, s3, %3, 0x7E;\nlop3.b32 t2, c0, c1, %3, 0x7E;\nlop3.b32 t3, c2, c3, %3, 0x7E;\n"
               "lop3.b32 t0, t0, t1, 1, 0xA8;\nlop3.b32 t2, t2, t3, 1, 0xA8;\n"
               "or.b32 t0, t0, t2;\n"
               "setp.eq.u32 p, t0, 0;\n"
               "vote.sync.all.pred p, p, 0xffffffff;\n"
               "@p bra.uni LAB_OK;\n"
               "mov.u32 t0, %%clock;\nsub.s32 t0, t0, %4;\nsetp.lt.s32 p, t0, 0;\n"
               "vote.sync.all.pred p, p, 0xffffffff;\n"
               "@p bra.uni LAB_POLL;\n"
               "LAB_OK:\n"
               "@e mbarrier.arrive.shared::cta.b64 _, [%2];\n}"
               :: "l"(src), "r"(dst), "r"(bar), "r"(par), "r"(dl) : "memory");
}

__device__ __forceinline__ int aux_col(int a, int u) { return u < 8 ? (a & 1) * 1024 + (2 * u + (a >> 1)) * 64 : 2048 + ((u - 8) * 4 + a) * 64; }
__device__ __forceinline__ void aux_role(const Maps& maps, const bf16* __restrict__ cvec, int a, uint32_t sbase, int wid) {
  const int tid = threadIdx.x, lane = tid & 31;
  const uint32_t dl = clock32() + 800000000u;
  if (wid == 8) {
    if (lane == 0) {
      prefetch_tmap(&maps.wmod);
      for (int s = 0; s < NM; s++) { mbar_init(sbase + B_FM + 8 * s, 1); mbar_init(sbase + B_EM + 8 * s, 8); }
      for (int s = 0; s < 2; s++) { mbar_init(sbase + B_FQ + 8 * s, 8); mbar_init(sbase + B_EQ + 8 * s, 2); }
      asm volatile("fence.mbarrier_init.release.cluster;" ::: "memory");
      fence_proxy_async_smem();
    }
    __syncwarp();
    Ring r{0, 1, 0, dl};
    #pragma unroll 1
    for (int i = 0; i < 96; i++) {
      if (i == NM) bar_sync(0, 352);
      mbar_wait(sbase + B_EM + 8 * r.st, r.ph, dl);
      mbar_expect_tx_e(sbase + B_FM + 8 * r.st, 32768);
      tma_load_2d(sbase + r.st * MSLOT, &maps.wmod, sbase + B_FM + 8 * r.st, aux_col(a, i >> 2), (i & 3) * 256);
      ring_next(r);
    }
  } else if (wid < 8) {
    PROFN(0, tid == 0);
    const int g = lane >> 2, qd = lane & 3;
    uint32_t sc[16];
    #pragma unroll
    for (int i = 0; i < 16; i++) sc[i] = *reinterpret_cast<const uint32_t*>(cvec + (i >> 2) * 256 + wid * 32 + (i & 3) * 8 + qd * 2);
    #pragma unroll
    for (int i = 0; i < 16; i++) sc[i] = pack_bf16(silu_f(bf_lo(sc[i])), silu_f(bf_hi(sc[i])));
    bar_sync(0, 352);
    const uint32_t aoff = (wid * 32 + (lane & 7) + (lane >> 4) * 8) * 128 + ((((lane >> 3) & 1) ^ (lane & 7)) << 4);
    Ring r{0, 0, 0, dl};
    uint32_t w[2][8][4];
    auto fetch = [&](uint32_t (&f)[8][4]) {
      const uint32_t t = m_wait(sbase, r) + aoff;
      #pragma unroll
      for (int e = 0; e < 8; e++) ldmatrix_x4_t((t + (e >> 2) * 2048) ^ ((e & 3) << 5), f[e]);
    };
    #pragma unroll 1
    for (int u = 0; u < 24; u++) {
      float acc[4][4];
      #pragma unroll
      for (int m = 0; m < 4; m++) acc[m][0] = acc[m][1] = acc[m][2] = acc[m][3] = 0.f;
      fetch(w[0]);
      #pragma unroll
      for (int q = 0; q < 4; q++) {
        PROF(30 + (u & 1) * 4 + q, u < 2 && tid == 0);
        m_next(r);
        if (q < 3) fetch(w[(q + 1) & 1]);
        #pragma unroll
        for (int e = 0; e < 8; e++) {
          const uint32_t (&f)[4] = w[q & 1][e];
          mma16(acc[e & 3], f[0], f[1], f[2], f[3], sc[4 * q + 2 * (e >> 2)], sc[4 * q + 2 * (e >> 2) + 1]);
        }
        mbar_arrive_e(m_prev(sbase, r));
      }
      const float v0 = qd & 2 ? (qd & 1 ? acc[3][0] : acc[2][0]) : (qd & 1 ? acc[1][0] : acc[0][0]);
      const float v1 = qd & 2 ? (qd & 1 ? acc[3][2] : acc[2][2]) : (qd & 1 ? acc[1][2] : acc[0][2]);
      mbar_wait(sbase + B_EQ + 8 * (u & 1), ((u >> 1) & 1) ^ 1, dl);
      sts64(sbase + SM_STG + (u & 1) * 2048 + wid * 256 + (qd * 8 + g) * 8, __float_as_uint(v0), __float_as_uint(v1));
      mbar_arrive_e(sbase + B_FQ + 8 * (u & 1));
    }
  } else if (wid < 11) {
    const unsigned par = (1 + ld_relaxed(&g_flags[FL_EPOCH])) & 1;
    float* const mail = &g_mod[(wid - 9) * 4 * 6 * D_ + 2 * lane];
    bar_sync(0, 352);
    #pragma unroll 1
    for (int u = -2; u < 24; u++) {
      if (u >= 0) {
        const int col = aux_col(a, u);
        const float add = (col >> 10) == 1 || (col >> 10) == 4 ? 1.f : 0.f;
        mbar_wait(sbase + B_FQ + 8 * (u & 1), (u >> 1) & 1, dl);
        float2 v[8];
        #pragma unroll
        for (int w = 0; w < 8; w++) v[w] = lds64f(sbase + SM_STG + (u & 1) * 2048 + w * 256 + lane * 8);
        const float t0 = ((v[0].x + v[1].x) + (v[2].x + v[3].x)) + ((v[4].x + v[5].x) + (v[6].x + v[7].x));
        const float t1 = ((v[0].y + v[1].y) + (v[2].y + v[3].y)) + ((v[4].y + v[5].y) + (v[6].y + v[7].y));
        const uint32_t w = pack_bf16(add + bf16_round(t0), add + bf16_round(t1)), o = __shfl_xor_sync(0xffffffffu, w, 1);
        const uint32_t m0 = (lane & 1) ? (o & 0xFFFF0000u) : (w << 16), m1 = (lane & 1) ? (w & 0xFFFF0000u) : (o << 16);
        #pragma unroll
        for (int c = 0; c < 4; c++) st_rlx_v2(mail + c * 6 * D_ + col, m0 | par, m1 | par, true);
        mbar_arrive_e(sbase + B_EQ + 8 * (u & 1));
        PROF(1 + u, tid == 288);
      }
      #pragma unroll 1
      for (int v = 2 * (u + 2); v < 2 * (u + 3) && v < 24; v++)
        #pragma unroll
        for (int c = 0; c < 4; c++) st_rlx_v2(mail + c * 6 * D_ + aux_col(a, v), par ^ 1, par ^ 1, true);
    }
  }
}

__global__ void __launch_bounds__(384, 1)
fused_block_kernel(const __grid_constant__ Maps maps, const bf16* __restrict__ x, const bf16* __restrict__ cvec, const bf16* __restrict__ wmod,
                   int role0) {
  extern __shared__ __align__(1024) uint8_t smem_raw[];
  const uint32_t sbase = smem_u32(smem_raw);
  const int tid = threadIdx.x, lane = tid & 31;
  const int wid = __shfl_sync(0xffffffffu, tid >> 5, 0);
  const int b = blockIdx.x + role0 - NAUX;
  if (b < 0) { aux_role(maps, cvec, b + NAUX, sbase, wid); return; }
  const int jg = b >> 6, mb = jg ? 31 - (b >> 2) : (b >> 2), j = 4 * jg + (b & 3);
  const uint32_t dl = clock32() + 800000000u;
  unsigned* const flags = &g_flags[mb * 32];
  const unsigned e1 = 1 + ld_relaxed(wid >= 10 ? &g_flags[FL_EPOCH] : flags + FO_EPOCH);
  const unsigned par = e1 & 1;
  const int row0 = mb * 128;

  if (wid >= 8) {
    if (wid == 8) {
      if (lane == 0) {
        for (int s = 0; s < 8; s++) mbar_init(sbase + B_X + 8 * s, 1);
        asm volatile("fence.mbarrier_init.release.cluster;" ::: "memory");
        fence_proxy_async_smem();
      }
      #pragma unroll 1
      for (int q = 0; q < X_UP; q++) {
        mbar_expect_tx_e(sbase + B_X + 8 * q, 4096);
        bulk_load(sbase + SM_XR + q * 4096, x + (size_t)(row0 + j * 16 + 2 * q) * D_, 4096, sbase + B_X + 8 * q);
      }
    } else if (tid == 288) {
      for (int s = 0; s < NQ; s++) { mbar_init(sbase + B_FQ + 8 * s, 1); mbar_init(sbase + B_EQ + 8 * s, 8); }
      for (int s = 0; s < NM; s++) { mbar_init(sbase + B_FM + 8 * s, 1); mbar_init(sbase + B_EM + 8 * s, 8); }
      for (int s = 0; s < 8; s++) mbar_init(sbase + B_MOD + 8 * s, s == 0 || s == 7 ? 2 : 1);
      mbar_init(sbase + B_STREQ, 8); mbar_init(sbase + B_STFREE, 1); mbar_init(sbase + B_VEC, 1); mbar_init(sbase + B_VEC + 8, 1); mbar_init(sbase + B_LN, 8);
      for (int s = 0; s < 11; s++) mbar_init(sbase + B_FLG + 8 * s, 1);
      asm volatile("fence.mbarrier_init.release.cluster;" ::: "memory");
      fence_proxy_async_smem();
    } else if (tid >= 320 && tid < 331) {
      prefetch_tmap(&maps.x + (tid - 320));
    }
    bar_sync(0, 384);
    reg_dealloc<40>();
    if (wid == 8) {
      uint32_t tnext = clock32();
      int xq = X_UP;
      #pragma unroll 1
      for (int u = 0; u < 16; u++) {
        const int st = u & 3;
        if (u <= NEARLY) {
          #pragma unroll 1
          for (; xq < 8 && (xq < X_UP + u * X_PER || u == NEARLY); xq++) {
            tnext += X_GAP; wait_until(tnext);
            mbar_expect_tx_e(sbase + B_X + 8 * xq, 4096);
            bulk_load(sbase + SM_XR + xq * 4096, x + (size_t)(row0 + j * 16 + 2 * xq) * D_, 4096, sbase + B_X + 8 * xq);
          }
          if (u == NEARLY) { PRD_WAIT(sbase + B_MOD, 0, dl); PROFN(60, lane == 0); tnext = clock32(); }
        } else if (u < NQ) { tnext += Q_GAP; wait_until(tnext); }
        if (u == 3) PRD_WAIT(sbase + B_EQ, 0, dl);
        PRD_WAIT(sbase + B_EQ + 8 * st, ((u >> 2) & 1) ^ 1, dl);
        const uint32_t slot = sbase + st * QSLOT, fb = sbase + B_FQ + 8 * st;
        mbar_expect_tx_e(fb, u == 0 ? 65536 : u == 15 ? 32768 : 49152);
        if (u == 0) tma_load_3d(sbase + SM_X0, &maps.x, fb, 0, mb * 64, 0);
        tma_load_4d(slot + 16384, &maps.wqk, fb, 0, u * 64, j, 0);
        tma_load_4d(slot + 32768, &maps.wvv, fb, 0, u * 64, j, 0);
        if (u < 15) tma_load_3d(slot, &maps.x, fb, u * 64 + 64, mb * 64, 0);
      }
      Ring r{0, 1, 0, dl};
      uint32_t slot, fb;
      auto acquire = [&](uint32_t bytes) {
        PRD_WAIT(sbase + B_EM + 8 * r.st, r.ph, dl);
        slot = sbase + r.st * MSLOT; fb = sbase + B_FM + 8 * r.st;
        mbar_expect_tx_e(fb, bytes);
        ring_next(r);
      };
      #pragma unroll 1
      for (int kt = 0; kt < 16; kt++) {
        if (kt < 5) PRD_WAIT(sbase + B_EQ + 8 * (kt - (kt >= 2)), 1, dl);
        if (kt == 0 || kt == 8 || kt == 12) PRD_WAIT(sbase + B_FLG + (kt == 0 ? 0 : 2 * kt - 8), 0, dl);
        acquire(32768);
        tma_load_4d(slot + 16384, &maps.wqk, fb, 0, kt * 64, j + 8, 0);
        tma_load_3d(slot, &maps.hh, fb, (kt & 7) * 64, row0, kt >> 3);
      }
      PRD_WAIT(sbase + B_FLG + 24, 0, dl);
      #pragma unroll 1
      for (int kt = 0; kt < 8; kt++) {
        acquire(32768);
        tma_load_3d(slot + 16384, &maps.wo, fb, 0, kt * 64, 2 * j);
        tma_load_2d(slot, &maps.o, fb, kt * 64, row0);
      }
      acquire(32768);
      tma_load_3d(slot, &maps.x, fb, j * 128, mb * 64, 0);
      tma_load_3d(slot + 16384, &maps.x, fb, j * 128 + 64, mb * 64, 0);
      acquire(16384);
      tma_load_3d(slot + 16384, &maps.wo, fb, 0, (8 + j) * 64, 2 * j);
      {
        constexpr int NPRE = 3;
        Ring ra = r;
        #pragma unroll 1
        for (int i = 0; i < 7; i++) {
          const int kt = 8 + i + (i >= j);
          acquire(32768);
          tma_load_3d(slot + 16384, &maps.wo, fb, 0, kt * 64, 2 * j);
          if (i == NPRE - 1) {
            wait_flag(flags + FO_O + 1, e1 * 8, dl);
            PROF(61, lane == 0);
            #pragma unroll 1
            for (int q = 0; q < NPRE - 1; q++) { tma_load_2d(sbase + ra.st * MSLOT, &maps.o, sbase + B_FM + 8 * ra.st, (8 + q + (q >= j)) * 64, row0); ring_next(ra); }
          }
          if (i >= NPRE - 1) tma_load_2d(slot, &maps.o, fb, kt * 64, row0);
        }
      }
      #pragma unroll 1
      for (int t = 0; t < 2; t++) {
        acquire(32768);
        tma_load_2d(slot, &maps.w1, fb, j * 64, (2 * j + t) * 64);
        tma_load_2d(slot + 8192, &maps.w3, fb, j * 64, (2 * j + t) * 64);
        tma_load_2d(slot + 16384, &maps.w1, fb, (8 + j) * 64, (2 * j + t) * 64);
        tma_load_2d(slot + 24576, &maps.w3, fb, (8 + j) * 64, (2 * j + t) * 64);
      }
      {
        Ring ra = r;
        #pragma unroll 1
        for (int i = 0; i < 4; i++) {
          const int kt = i + (i >= 2 * j ? 2 : 0);
          acquire(32768);
          tma_load_2d(slot + 16384, &maps.w1, fb, j * 64, kt * 64);
          tma_load_2d(slot + 24576, &maps.w3, fb, j * 64, kt * 64);
        }
        wait_flag(&g_flags[FL_H2], e1 * NCTA, dl);
        PROFN(62, lane == 0);
        #pragma unroll 1
        for (int i = 0; i < 4; i++) { tma_load_2d(sbase + ra.st * MSLOT, &maps.h2, sbase + B_FM + 8 * ra.st, (i + (i >= 2 * j ? 2 : 0)) * 64, row0); ring_next(ra); }
      }
      #pragma unroll 1
      for (int gt = 0; gt < 7; gt++) {
        const int ncol = (8 * gt + j) * 64, skip = gt < 2 ? 2 * j : 16;
        #pragma unroll 1
        for (int i = (gt == 0 ? 4 : 0); i < (gt < 2 ? 14 : 16); i++) {
          const int kt = i + (i >= skip ? 2 : 0);
          acquire(32768);
          tma_load_2d(slot + 16384, &maps.w1, fb, ncol, kt * 64);
          tma_load_2d(slot + 24576, &maps.w3, fb, ncol, kt * 64);
          tma_load_2d(slot, &maps.h2, fb, kt * 64, row0);
        }
      }
      #pragma unroll 1
      for (int kt = 0; kt < 56; kt++) {
        if ((kt & 7) == 0) PRD_WAIT(sbase + B_FLG + 32 + kt, 0, dl);
        acquire(32768);
        tma_load_3d(slot + 16384, &maps.w2, fb, 0, kt * 64, 2 * j);
        tma_load_3d(slot, &maps.hh, fb, (kt & 7) * 64, row0, kt >> 3);
      }
    } else {
      if (wid == 9) {
        SVC_WAIT(sbase + B_LN, 0, dl);
        red_add_e(&g_flags[FL_LN1], 1);
        SVC_WAIT(sbase + B_MOD, 0, dl);
        #pragma unroll 1
        for (int e = 0; e < 16; e++) st_rlx_v4(g_halo + (mb * 16 + j + (e & 8)) * 256 + (e & 7) * 32 + lane, ~0u, ~0u, ~0u, ~0u, true);
        #pragma unroll 1
        for (int e = 0; e < 2; e++) st_rlx_v4(g_st2 + ((mb * 8 + e * 4 + (lane >> 3)) * 8 + j) * 8 + (lane & 7), ~0u, ~0u, ~0u, ~0u, true);
        __threadfence();
        red_add_e(&g_flags[FL_RESET], 1);
        #pragma unroll 1
        for (int n = 0; n < 12; n++) {
          SVC_WAIT(sbase + B_STREQ, n & 1, dl);
          if (n == 2 || n == 3) tma_store_2d(&maps.o, sbase + SM_STG, (j + 8 * (n - 2)) * 64, row0);
          else if (n == 4) { tma_store_2d(&maps.h2, sbase + SM_STG, j * 128, row0); tma_store_2d(&maps.h2, sbase + SM_STG + 16384, j * 128 + 64, row0); }
          else tma_store_3d(&maps.hh, sbase + SM_STG, j * 64, row0, n < 2 ? n : n - 5);
          bulk_commit();
          bulk_wait0();
          red_add_e(n == 4 ? &g_flags[FL_H2] : flags + (n < 2 ? FO_H1 + n + (n & (j >> 2)) : n - 1), 1);
          mbar_arrive_e(sbase + B_STFREE);
          PROFN(70 + n, lane == 0 && n > 0);
        }
      } else {
        SVC_WAIT(sbase + B_X + 8 * X_POLL, 0, dl);
        const float* const mail = &g_mod[(b & 7) * 6 * D_ + lane * 4];
        if (wid == 10) {
          #pragma unroll 1
          for (int p = 0; p < 8; p++) {
            if (p >= 2) SVC_WAIT(p == 2 ? sbase + B_MOD : q_empty(2 * p - 5, sbase), p == 2 ? 0 : ((2 * p - 5) >> 2) & 1, dl);
            gather_table(mail + p * 128, sbase + SM_MODT + p * 512 + lane * 16, sbase + B_MOD + 8 * p, par, dl);
            PROF(63 + p, lane == 0 && p < 7);
          }
          const uint32_t vdst = sbase + SM_VEC + (lane >> 3) * 64 + (lane & 3) * 16 + ((lane >> 2) & 1) * 8;
          #pragma unroll 1
          for (int v = 0; v < 2; v++) {
            SVC_WAIT(sbase + B_FLG + 24 + 8 * v, 0, dl);
            uint4 m[3];
            while (true) {
              #pragma unroll
              for (int e = 0; e < 3; e++) m[e] = ld_rlx_v4(mail + (2 + v + e) * 1024 + j * 128);
              if (poll_done(((bad4(m[0], par) | bad4(m[1], par) | bad4(m[2], par)) & 1) == 0, dl)) break;
              __nanosleep(200);
            }
            #pragma unroll
            for (int e = 0; e < 3; e++) sts64(vdst + (v + e) * 256, hi_halves(m[e].x, m[e].y), hi_halves(m[e].z, m[e].w));
            mbar_arrive_e(sbase + B_VEC + 8 * v);
            PROF(70, lane == 0 && v == 0);
          }
        } else {
          SVC_WAIT(sbase + B_LN, 0, dl);
          wait_flag(&g_flags[FL_LN1], e1 * NCTA, dl);
          mbar_arrive_e(sbase + B_MOD);
          PROF(41, lane == 0);
          SVC_WAIT(q_empty(3, sbase), 0, dl);
          wait_flag(&g_flags[FL_RESET], e1 * NCTA, dl);
          mbar_arrive_e(sbase + B_MOD + 56);
          #pragma unroll 1
          for (int i = 0; i < 11; i++) {
            const unsigned* f = flags + (i < 3 ? FO_H1 + i : i == 3 ? FO_O : FO_HH + i - 4);
            while (!poll_done((int)(ld_relaxed(f) - e1 * (i == 1 || i == 2 ? 4 : 8)) >= 0, dl)) __nanosleep(100);
            mbar_arrive_e(sbase + B_FLG + 8 * i);
          }
        }
      }
    }
  } else {
    PROFN(0, tid == 0);
    const int wg = wid >> 2, warp = wid & 3;
    const int g = lane >> 2, qd = lane & 3;
    bulk_prefetch(wmod + (size_t)(b * 8 + wid) * (6 * D_), PF_BYTES);
    bulk_prefetch(wmod + (size_t)(b * 8 + wid) * (6 * D_) + D_, PF_BYTES);
    bar_sync(0, 384);
    reg_alloc<232>();
    const uint32_t wgoff = wg * 8192;
    const uint32_t frag = wid * 2048 + (lane & 15) * 128 + (((lane >> 4) ^ (lane & 7)) << 4);
    const uint32_t slab = sbase + SM_STG + wid * 2048;

    LnRow ln;
    {
      uint2* const lmail = &g_ln1[(mb * 8 + (lane & 1) * 4 + (j >> 1)) * 16 + (j & 1) * 8 + wid];
      st_rlx_v2(lmail, par ^ 1, par ^ 1, lane < 2);
      mbar_wait(sbase + B_X + 8 * wid, 0, dl);
      PROF(3, tid == 224);
      if (PF2_BYTES) {
        bulk_prefetch(wmod + (size_t)(b * 8 + wid) * (6 * D_) + PF_BYTES / 2, PF2_BYTES);
        bulk_prefetch(wmod + (size_t)(b * 8 + wid) * (6 * D_) + PF_BYTES / 2 + D_, PF2_BYTES);
      }
      float s[2][2] = {{0.f, 0.f}, {0.f, 0.f}}, q2[2][2] = {{0.f, 0.f}, {0.f, 0.f}};
      #pragma unroll
      for (int c = 0; c < 8; c++) {
        const uint4 v = lds128(sbase + SM_XR + wid * 4096 + c * 512 + lane * 16);
        const uint32_t vv[4] = {v.x, v.y, v.z, v.w};
        #pragma unroll
        for (int e = 0; e < 4; e++) {
          const float lo = bf_lo(vv[e]), hi = bf_hi(vv[e]);
          s[c >> 2][0] += lo; s[c >> 2][1] += hi; q2[c >> 2][0] = fmaf(lo, lo, q2[c >> 2][0]); q2[c >> 2][1] = fmaf(hi, hi, q2[c >> 2][1]);
        }
      }
      const bool odd = lane & 1;
      float sm = (s[0][0] + s[0][1]), so = (s[1][0] + s[1][1]), qm = (q2[0][0] + q2[0][1]), qo = (q2[1][0] + q2[1][1]);
      { const float a = odd ? so : sm, c = odd ? qo : qm;
        sm = a + __shfl_xor_sync(0xffffffffu, odd ? sm : so, 1); qm = c + __shfl_xor_sync(0xffffffffu, odd ? qm : qo, 1); }
      #pragma unroll
      for (int o = 2; o < 32; o <<= 1) { sm += __shfl_xor_sync(0xffffffffu, sm, o); qm += __shfl_xor_sync(0xffffffffu, qm, o); }
      sm *= (1.f / D_);
      st_rlx_v2(lmail, tagf(rsqrtf(fmaxf(qm * (1.f / D_) - sm * sm, 0.f) + 1e-5f), par), tagf(sm, par), lane < 2);
      mbar_arrive_e(sbase + B_LN);
      PROF(4, tid == 224);
      mbar_wait(sbase + B_LN, 0, dl);
      uint2 v0, v1;
      do { v0 = ld_rlx_v2(&g_ln1[(mb * 8 + wid) * 16 + g]); v1 = ld_rlx_v2(&g_ln1[(mb * 8 + wid) * 16 + 8 + g]); }
      while (!poll_done(((bad2(v0.x, v0.y, par) | bad2(v1.x, v1.y, par)) & 1) == 0, dl));
      ln_row(ln, 0, __uint_as_float(v0.y), __uint_as_float(v0.x));
      ln_row(ln, 1, __uint_as_float(v1.y), __uint_as_float(v1.x));
      PROF(5, tid == 0);
    }

    uint4* const halo_out = g_halo + ((mb * 16 + j) * 2 + wg) * 128 + lane;
    const uint4* const halo_in = halo_out - 16 * 256;
    const uint32_t xch = sbase + SM_XCH + wid * 2048 + lane * 16;
    const bool noprev = mb == 0 && warp == 0;
    float a0[64], a1[64];
    uint32_t x2[32];
    Ring r{role0 >> 8, 0, 0, dl};
    Frag8 qA, qB, kA, kB, vA, vB, wA, wB;
    {
      float acc[128];
      uint32_t A0[16], A1[16];
      undef_regs(acc);
      const uint32_t tab = sbase + SM_MODT + qd * 16;
      uint4 p[4];
      q_wait(0, sbase, dl);
      mbar_wait(sbase + B_MOD, 0, dl);
      #pragma unroll
      for (int kk = 0; kk < 4; kk++) q_load(A0, p, kk, sbase + SM_X0 + frag, tab);
      PROF(6, tid == 0);
      q_step_rs<true>(acc, A0, A1, p, sbase, frag, tab + 256, ln, true, 0);
      #pragma unroll 1
      for (int u = 1; u < 15; u += 2) {
        if (((u - 1) & 7) == HJ) q_stage_h1(A0, u - 1, sbase, frag, dl);
        mbar_wait(sbase + B_MOD + 4 * (u + 1), 0, dl);
        q_step_rs<true>(acc, A1, A0, p, q_wait(u, sbase, dl), frag, tab + (u + 1) * 256, ln, false, q_empty(u - 1, sbase));
        if ((u & 7) == HJ) q_stage_h1(A1, u, sbase, frag, dl);
        q_step_rs<true>(acc, A0, A1, p, q_wait(u + 1, sbase, dl), frag, tab + (u + 2) * 256, ln, false, q_empty(u, sbase));
      }
      if (HJ == 6) q_stage_h1(A0, 14, sbase, frag, dl);
      q_step_rs<false>(acc, A1, A0, p, q_wait(15, sbase, dl), frag, 0, ln, false, q_empty(14, sbase));
      if (HJ == 7) q_stage_h1(A1, 15, sbase, frag, dl);
      wgmma_wait<0>();
      undef_regs(a0);
      { const uint32_t slot = m_wait(sbase, r); mma_step(a0, slot + wgoff, slot + 16384, true, q_empty(15, sbase)); m_next(r); }
      fence_regs(acc);
      PROF(8, tid == 0);
      bar_sync(NB_CONS, 256);
      pack_half(kB, acc, 32, 1); pack_half(vB, acc, 64, 1); transpose8(vB);
      m_step(a0, sbase, wgoff, r);
      sched_fence();
      attn_send(kB, 0, xch, warp, halo_out, mb < 15); attn_send(vB, 1, xch, warp, halo_out, mb < 15);
      pack_half(qA, acc, 0, 0); pack_half(qB, acc, 0, 1); pack_half(kA, acc, 32, 0);
      m_step(a0, sbase, wgoff, r);
      sched_fence();
      pack_half(vA, acc, 64, 0); pack_half(wB, acc, 96, 1); pack_half(wA, acc, 96, 0); transpose8(vA);
    }
    uint4 wP[2];
    {
      m_step(a0, sbase, wgoff, r);
      uint4 pv[4];
      attn_recv<4>(pv, 0, xch, wg, warp, halo_in, mb > 0);
      m_step(a0, sbase, wgoff, r);
      sched_fence();
      transpose8(wB);
      m_step(a0, sbase, wgoff, r);
      attn_check<4>(pv, 0, warp, halo_in, dl);
      wgmma_wait<0>();
      PROF(9, tid == 0);
      float o[2][5][4];
      mbar_wait(sbase + B_STFREE, 1, dl);
      attn_core(qA, qB, kA, kB, vA, vB, pv, pv + 2, noprev, lane, o);
      sched_fence();
      bar_sync(NB_CONS, 256);
      PROF(10, tid == 0);
      m_step(a0, sbase, wgoff, r);
      sched_fence();
      attn_store(o, 0, sbase, frag);
      m_step(a0, sbase, wgoff, r);
      sched_fence();
      attn_store(o, 1, sbase, frag);
      fence_proxy_async_smem();
      mbar_arrive_e(sbase + B_STREQ);
      m_step(a0, sbase, wgoff, r);
      sched_fence();
      attn_send(wB, 1, xch, warp, halo_out + 8 * 256, mb < 15);
      transpose8(wA);
      #pragma unroll 1
      for (int i = 9; i < 15; i++) m_step(a0, sbase, wgoff, r);
      attn_recv<2>(wP, 2, xch, wg, warp, halo_in + 8 * 256, mb > 0);
      m_step(a0, sbase, wgoff, r);
    }
    {
      undef_regs(a1);
      m_step(a1, sbase, wgoff, r, true);
      fence_regs(a0);
      PROF(14, tid == 0);
      sched_fence();
      pack_half(kB, a0, 32, 1);
      attn_send(kB, 0, xch, warp, halo_out + 8 * 256, mb < 15);
      pack_half(kA, a0, 32, 0);
      m_step(a1, sbase, wgoff, r);
      sched_fence();
      pack_half(qA, a0, 0, 0); pack_half(qB, a0, 0, 1);
      attn_check<2>(wP, 2, warp, halo_in + 8 * 256, dl);
      uint4 kP[2];
      attn_recv<2>(kP, 0, xch, wg, warp, halo_in + 8 * 256, mb > 0);
      m_step(a1, sbase, wgoff, r);
      attn_check<2>(kP, 0, warp, halo_in + 8 * 256, dl);
      wgmma_wait<0>();
      PROF(15, tid == 0);
      float o[2][5][4];
      mbar_wait(sbase + B_STFREE, 0, dl);
      attn_core(qA, qB, kA, kB, wA, wB, kP, wP, noprev, lane, o);
      attn_store(o, 0, sbase, frag);
      attn_store(o, 1, sbase, frag);
      fence_proxy_async_smem();
      mbar_arrive_e(sbase + B_STREQ);
      bar_sync(NB_CONS, 256);
      PROF(16, tid == 0);
      #pragma unroll 1
      for (int i = 3; i < 8; i++) m_step(a1, sbase, wgoff, r);
      mbar_wait(sbase + B_FM + 8 * r.st, r.ph, dl);
      #pragma unroll
      for (int jj = 0; jj < 8; jj++)
        ldmatrix_x4((sbase + r.st * MSLOT + (jj >> 2) * 16384 + frag) ^ ((jj & 3) << 5), x2[4 * jj], x2[4 * jj + 1], x2[4 * jj + 2], x2[4 * jj + 3]);
      mbar_arrive_e(sbase + B_EM + 8 * r.st);
      ring_next(r);
      mma_step(a1, sbase + SM_STG + wgoff, m_wait(sbase, r) + 16384, false, m_prev(sbase, r));
      m_next(r);
      PROF(17, tid == 0);
      #pragma unroll 1
      for (int i = 0; i < 7; i++) m_step(a1, sbase, wgoff, r);
      mbar_wait(sbase + B_VEC, 0, dl);
      mbar_wait(sbase + B_STFREE, 1, dl);
      const uint32_t vec = sbase + SM_VEC + qd * 16;
      uint4 ga[4];
      #pragma unroll
      for (int q = 0; q < 4; q++) ga[q] = lds128(vec + q * 64);
      wgmma_wait<0>();
      mbar_arrive_e(m_prev(sbase, r));
      fence_regs(a1);
      PROF(18, tid == 0);
      float s[2] = {0.f, 0.f}, q2[2] = {0.f, 0.f};
      #pragma unroll
      for (int i = 0; i < 32; i++) {
        const uint4& gv = ga[i >> 3];
        const uint32_t gw = (i & 4) ? ((i & 2) ? gv.w : gv.z) : ((i & 2) ? gv.y : gv.x);
        x2[i] = fma_bf2(gw, pack_bf16(a1[2 * i], a1[2 * i + 1]), x2[i]);
        const float v0 = bf_lo(x2[i]), v1 = bf_hi(x2[i]);
        s[i & 1] += v0 + v1; q2[i & 1] = fmaf(v0, v0, fmaf(v1, v1, q2[i & 1]));
      }
      #pragma unroll
      for (int o2 = 1; o2 <= 2; o2 <<= 1)
        #pragma unroll
        for (int h = 0; h < 2; h++) { s[h] += __shfl_xor_sync(0xffffffffu, s[h], o2); q2[h] += __shfl_xor_sync(0xffffffffu, q2[h], o2); }
      uint4* const sm = g_st2 + (mb * 8 + wid) * 64 + g;
      st_rlx_v4(sm + j * 8, __float_as_uint(s[0]), __float_as_uint(q2[0]), __float_as_uint(s[1]), __float_as_uint(q2[1]), qd == 0);
      PROF(19, tid == 0);
      uint4 sb[4], cb[4];
      #pragma unroll
      for (int q = 0; q < 4; q++) { sb[q] = lds128(vec + 256 + q * 64); cb[q] = lds128(vec + 512 + q * 64); }
      uint4 p0, p1;
      while (true) {
        p0 = ld_rlx_v4(sm + qd * 16); p1 = ld_rlx_v4(sm + qd * 16 + 8);
        const bool ok = p0.x != ~0u && p0.y != ~0u && p0.z != ~0u && p0.w != ~0u && p1.x != ~0u && p1.y != ~0u && p1.z != ~0u && p1.w != ~0u;
        if (poll_done(ok, dl)) break;
      }
      PROF(20, tid == 0);
      s[0] = __uint_as_float(p0.x) + __uint_as_float(p1.x); q2[0] = __uint_as_float(p0.y) + __uint_as_float(p1.y);
      s[1] = __uint_as_float(p0.z) + __uint_as_float(p1.z); q2[1] = __uint_as_float(p0.w) + __uint_as_float(p1.w);
      #pragma unroll
      for (int o2 = 1; o2 <= 2; o2 <<= 1)
        #pragma unroll
        for (int h = 0; h < 2; h++) { s[h] += __shfl_xor_sync(0xffffffffu, s[h], o2); q2[h] += __shfl_xor_sync(0xffffffffu, q2[h], o2); }
      #pragma unroll
      for (int h = 0; h < 2; h++) {
        const float m = s[h] * (1.f / D_);
        ln_row(ln, h, m, rsqrtf(fmaxf(q2[h] * (1.f / D_) - m * m, 0.f) + 1e-5f));
      }
      #pragma unroll
      for (int jj = 0; jj < 8; jj++) {
        const uint32_t cl = (jj & 1) ? cb[jj >> 1].z : cb[jj >> 1].x, ch = (jj & 1) ? cb[jj >> 1].w : cb[jj >> 1].y;
        const uint32_t sl = (jj & 1) ? sb[jj >> 1].z : sb[jj >> 1].x, sh = (jj & 1) ? sb[jj >> 1].w : sb[jj >> 1].y;
        stmatrix_x4((sbase + SM_STG + (jj >> 2) * 16384 + frag) ^ ((jj & 3) << 5), ln_mod(x2[4 * jj], ln, 0, cl, sl), ln_mod(x2[4 * jj + 1], ln, 1, cl, sl),
                    ln_mod(x2[4 * jj + 2], ln, 0, ch, sh), ln_mod(x2[4 * jj + 3], ln, 1, ch, sh));
      }
      fence_proxy_async_smem();
      mbar_arrive_e(sbase + B_STREQ);
      bar_sync(NB_WG + wg, 128);
      PROF(21, tid == 0);
    }

    undef_regs(a0);
    #pragma unroll
    for (int t = 0; t < 2; t++) {
      const uint32_t slot = m_wait(sbase, r);
      mma_step(a0, sbase + SM_STG + t * 16384 + wgoff, slot, t == 0, t == 0 ? 0 : m_prev(sbase, r));
      mma_step(a1, sbase + SM_STG + t * 16384 + wgoff, slot + 16384, t == 0, 0);
      m_next(r);
    }
    PROF(22, tid == 0);
    #pragma unroll 1
    for (int t = 0; t < 7; t += 2) {
      g_switch(a1, a0, t == 0 ? 14 : 11, t > 0, 5 + t, sbase, wgoff, frag, r);
      if (t == 6) break;
      g_switch(a0, a1, t == 0 ? 9 : 11, true, 6 + t, sbase, wgoff, frag, r);
    }
    #pragma unroll 1
    for (int i = 5; i < 56; i++) m_step(a1, sbase, wgoff, r);
    {
      mbar_wait(sbase + B_STFREE, 1, dl);
      mbar_wait(sbase + B_VEC + 8, 0, dl);
      uint4 gb[4];
      #pragma unroll
      for (int q = 0; q < 4; q++) gb[q] = lds128(sbase + SM_VEC + 768 + qd * 16 + q * 64);
      wgmma_wait<0>();
      fence_regs(a1);
      PROF(50, tid == 0);
      #pragma unroll
      for (int t = 0; t < 2; t++) {
        #pragma unroll
        for (int jj = 4 * t; jj < 4 * t + 4; jj++) {
          const uint32_t gl = (jj & 1) ? gb[jj >> 1].z : gb[jj >> 1].x, gh = (jj & 1) ? gb[jj >> 1].w : gb[jj >> 1].y;
          const int i = 8 * jj;
          stmatrix_x4((sbase + SM_STG + t * 16384 + frag) ^ ((jj & 3) << 5),
                      fma_bf2(gl, pack_bf16(a1[i], a1[i + 1]), x2[4 * jj]), fma_bf2(gl, pack_bf16(a1[i + 2], a1[i + 3]), x2[4 * jj + 1]),
                      fma_bf2(gh, pack_bf16(a1[i + 4], a1[i + 5]), x2[4 * jj + 2]), fma_bf2(gh, pack_bf16(a1[i + 6], a1[i + 7]), x2[4 * jj + 3]));
        }
        fence_proxy_async_smem();
        tma_store_3d(&maps.out, slab + t * 16384, j * 128 + t * 64, mb * 64 + warp * 16, wg);
      }
      bulk_commit();
      st_rlx(tid == 0 ? flags + FO_EPOCH : &g_flags[FL_EPOCH], e1, j == 0 && (tid == 0 || (tid == 1 && mb == 0)));
      bulk_wait_read0();
      PROFN(51, tid == 0);
    }
  }
}

typedef CUresult (*PFN_encodeTiled)(CUtensorMap*, CUtensorMapDataType, cuuint32_t, void*, const cuuint64_t*, const cuuint64_t*,
                                    const cuuint32_t*, const cuuint32_t*, CUtensorMapInterleave, CUtensorMapSwizzle,
                                    CUtensorMapL2promotion, CUtensorMapFloatOOBfill);

void encode(PFN_encodeTiled fn, CUtensorMap* m, const void* ptr, int rank, const cuuint64_t* dims, const cuuint64_t* strides,
            const cuuint32_t* box) {
  const cuuint32_t es[5] = {1, 1, 1, 1, 1};
  fn(m, CU_TENSOR_MAP_DATA_TYPE_BFLOAT16, rank, const_cast<void*>(ptr), dims, strides, box, es, CU_TENSOR_MAP_INTERLEAVE_NONE,
     CU_TENSOR_MAP_SWIZZLE_128B, CU_TENSOR_MAP_L2_PROMOTION_L2_256B, CU_TENSOR_MAP_FLOAT_OOB_FILL_NONE);
}
void map2d(PFN_encodeTiled fn, CUtensorMap* m, const void* ptr, int cols, int rows, int boxrows) {
  const cuuint64_t dims[2] = {(cuuint64_t)cols, (cuuint64_t)rows}, strides[1] = {(cuuint64_t)cols * 2};
  const cuuint32_t box[2] = {64, (cuuint32_t)boxrows};
  encode(fn, m, ptr, 2, dims, strides, box);
}
void map_w2chunk(PFN_encodeTiled fn, CUtensorMap* m, const void* ptr, int cols, int rows) {
  const cuuint64_t dims[3] = {64, (cuuint64_t)rows, (cuuint64_t)cols / 64}, strides[2] = {(cuuint64_t)cols * 2, 128};
  const cuuint32_t box[3] = {64, 64, 2};
  encode(fn, m, ptr, 3, dims, strides, box);
}
void map_parity(PFN_encodeTiled fn, CUtensorMap* m, const void* ptr, int boxpairs, int boxpar) {
  const cuuint64_t dims[3] = {D_, S_ / 2, 2}, strides[2] = {D_ * 4, D_ * 2};
  const cuuint32_t box[3] = {64, (cuuint32_t)boxpairs, (cuuint32_t)boxpar};
  encode(fn, m, ptr, 3, dims, strides, box);
}

}

extern "C" void kernel_launch(void* const* d_in, const int* in_sizes, int n_in, void* d_out, int out_size) {
  (void)in_sizes; (void)n_in; (void)out_size;
  const bf16* x = (const bf16*)d_in[0];
  const bf16* wqkv = (const bf16*)d_in[1];
  const bf16* wo = (const bf16*)d_in[2];
  const bf16* w1 = (const bf16*)d_in[4];
  const bf16* w3 = (const bf16*)d_in[5];
  const bf16* w2 = (const bf16*)d_in[6];
  const bf16* cvec = (const bf16*)d_in[7];
  const bf16* w_mod = (const bf16*)d_in[8];

  static PFN_encodeTiled fn = nullptr;
  static Maps maps;
  static const void* cached[8] = {};
  static int sms = 0;
  if (!fn) {
    void* p = nullptr; cudaDriverEntryPointQueryResult st;
    cudaGetDriverEntryPoint("cuTensorMapEncodeTiled", &p, cudaEnableDefault, &st);
    fn = (PFN_encodeTiled)p;
    cudaFuncSetAttribute(fused_block_kernel, cudaFuncAttributeMaxDynamicSharedMemorySize, SM_TOTAL);
    int dev = 0;
    cudaGetDevice(&dev);
    cudaDeviceGetAttribute(&sms, cudaDevAttrMultiProcessorCount, dev);
  }
  const void* cur[8] = {x, wqkv, wo, w1, w3, w2, d_out, w_mod};
  bool same = true;
  for (int i = 0; i < 8; i++) same = same && cached[i] == cur[i];
  if (!same) {
    void *o, *h2, *hh;
    cudaGetSymbolAddress(&hh, g_hh); cudaGetSymbolAddress(&o, g_o);
    h2 = o;
    map_parity(fn, &maps.x, x, 64, 2); map_parity(fn, &maps.out, d_out, 16, 1);
    map2d(fn, &maps.o, o, D_, S_, 128); map2d(fn, &maps.h2, h2, D_, S_, 128);
    {
      const cuuint64_t dims[3] = {512, (cuuint64_t)S_, 7}, strides[2] = {1024, (cuuint64_t)S_ * 1024};
      const cuuint32_t box[3] = {64, 128, 1};
      encode(fn, &maps.hh, hh, 3, dims, strides, box);
    }
    {
      const cuuint64_t dims[4] = {64, 1024, 16, 2}, strides[3] = {3072 * 2, 128, 2048};
      const cuuint64_t dimv[4] = {64, 1024, 8, 2}, stridev[3] = {3072 * 2, 128, 1024};
      const cuuint32_t box[4] = {64, 64, 1, 2};
      encode(fn, &maps.wqk, wqkv, 4, dims, strides, box);
      encode(fn, &maps.wvv, wqkv + 2048, 4, dimv, stridev, box);
    }
    map_w2chunk(fn, &maps.wo, wo, D_, D_); map_w2chunk(fn, &maps.w2, w2, D_, F_);
    map2d(fn, &maps.w1, w1, F_, D_, 64); map2d(fn, &maps.w3, w3, F_, D_, 64);
    map2d(fn, &maps.wmod, w_mod, 6 * D_, D_, 256);
    for (int i = 0; i < 8; i++) cached[i] = cur[i];
  }
  if (sms >= NCTA + NAUX) {
    fused_block_kernel<<<NCTA + NAUX, 384, SM_TOTAL>>>(maps, x, cvec, w_mod, 0);
  } else {
    fused_block_kernel<<<NAUX, 384, SM_TOTAL>>>(maps, x, cvec, w_mod, 0);
    fused_block_kernel<<<NCTA, 384, SM_TOTAL>>>(maps, x, cvec, w_mod, NAUX);
  }
}
```

```cpp
#include <cuda.h>
#include <cuda_runtime.h>
#include <cuda_bf16.h>
#include <stdint.h>

namespace {

typedef __nv_bfloat16 bf16;

constexpr int S_ = 2048, D_ = 1024, F_ = 3584;
constexpr int NCTA = 128, NAUX = 4;

__device__ __align__(1024) bf16 g_o[S_ * D_];
__device__ __align__(1024) bf16 g_hh[S_ * F_];
__device__ __align__(1024) float g_mod[8 * 6 * D_];
__device__ __align__(1024) uint2 g_ln1[16 * 8 * 16];
__device__ __align__(1024) uint4 g_halo[16 * 16 * 2 * 4 * 32];
__device__ __align__(1024) uint4 g_st2[16 * 8 * 8 * 8];
constexpr int FO_EPOCH = 0, FO_O = 1, FO_H2 = 3, FO_H1 = 11, FL_EPOCH = 16 * 32, FL_RESET = FL_EPOCH + 1, FL_LN1 = FL_EPOCH + 2, FL_H2 = FL_EPOCH + 3;
__device__ __align__(1024) unsigned g_flags[17 * 32];

#define AUXPOS 16
#define PROF(slot, on) do {} while (0)
#define PROFN(slot, on) do {} while (0)
#define PROFW_DECL do {} while (0)
#define PROFW(stmt) do {} while (0)
#define PROFW_OUT(slot, on) do {} while (0)

__device__ __forceinline__ uint32_t smem_u32(const void* p) { return (uint32_t)__cvta_generic_to_shared(p); }
__device__ __forceinline__ void mbar_init(uint32_t bar, uint32_t count) {
  asm volatile("mbarrier.init.shared::cta.b64 [%0], %1;" :: "r"(bar), "r"(count));
}
#define ELECT "{\n.reg .pred p;\nelect.sync _|p, 0xffffffff;\n@p "
__device__ __forceinline__ void mbar_expect_tx_e(uint32_t bar, uint32_t bytes) {
  asm volatile(ELECT "mbarrier.arrive.expect_tx.shared::cta.b64 _, [%0], %1;\n}" :: "r"(bar), "r"(bytes) : "memory");
}
__device__ __forceinline__ void mbar_arrive_if(uint32_t bar, bool on) {
  asm volatile("{\n.reg .pred p;\nsetp.ne.b32 p, %1, 0;\n@p mbarrier.arrive.shared::cta.b64 _, [%0];\n}" :: "r"(bar), "r"((int)on) : "memory");
}
__device__ __forceinline__ void mbar_arrive_e(uint32_t bar) {
  asm volatile(ELECT "mbarrier.arrive.shared::cta.b64 _, [%0];\n}" :: "r"(bar) : "memory");
}
__device__ __forceinline__ uint32_t clock32() { uint32_t t; asm volatile("mov.u32 %0, %%clock;" : "=r"(t)); return t; }
__device__ __forceinline__ void mbar_wait(uint32_t bar, uint32_t parity, uint32_t dl) {
  asm volatile("{\n.reg .pred p, q;\n.reg .b32 t;\n"
               "mbarrier.try_wait.parity.shared::cta.b64 p, [%0], %1;\n"
               "@p bra LAB_DONE;\n"
               "LAB_WAIT:\n"
               "mbarrier.try_wait.parity.shared::cta.b64 p, [%0], %1;\n"
               "mov.u32 t, %%clock;\n"
               "sub.s32 t, t, %2;\n"
               "setp.lt.and.s32 q, t, 0, !p;\n"
               "@q bra LAB_WAIT;\n"
               "LAB_DONE:\n}" :: "r"(bar), "r"(parity), "r"(dl) : "memory");
}
__device__ __forceinline__ void mbar_sleep(uint32_t bar, uint32_t parity, uint32_t dl) {
  asm volatile("{\n.reg .pred p;\n.reg .b32 t;\n"
               "LAB_WAIT:\n"
               "mbarrier.try_wait.parity.shared::cta.b64 p, [%0], %1, 20000;\n"
               "@p bra LAB_DONE;\n"
               "mov.u32 t, %%clock;\n"
               "sub.s32 t, t, %2;\n"
               "setp.lt.s32 p, t, 0;\n"
               "@p bra LAB_WAIT;\n"
               "LAB_DONE:\n}" :: "r"(bar), "r"(parity), "r"(dl) : "memory");
}
__device__ __forceinline__ bool poll_done(bool ok, uint32_t dl) {
  return __all_sync(0xffffffffu, ok || (int)(clock32() - dl) >= 0);
}
__device__ __forceinline__ unsigned ld_relaxed(const unsigned* p) {
  unsigned v; asm volatile("ld.relaxed.gpu.global.u32 %0, [%1];" : "=r"(v) : "l"(p) : "memory"); return v;
}
__device__ __forceinline__ void red_add_e(unsigned* p, unsigned v) {
  asm volatile(ELECT "red.relaxed.gpu.global.add.u32 [%0], %1;\n}" :: "l"(p), "r"(v) : "memory");
}
__device__ __forceinline__ void wait_flag(const unsigned* p, unsigned target, uint32_t dl) {
  asm volatile("{\n.reg .pred p;\n.reg .b32 t;\n"
               "LAB_WAIT:\n"
               "ld.relaxed.gpu.global.u32 t, [%0];\n"
               "sub.s32 t, t, %1;\n"
               "setp.ge.s32 p, t, 0;\n"
               "@p bra LAB_DONE;\n"
               "mov.u32 t, %%clock;\n"
               "sub.s32 t, t, %2;\n"
               "setp.lt.s32 p, t, 0;\n"
               "@p bra LAB_WAIT;\n"
               "LAB_DONE:\n}" :: "l"(p), "r"(target), "r"(dl) : "memory");
}
__device__ __forceinline__ void wait_until(uint32_t t) { while ((int)(clock32() - t) < 0) {} }
__device__ __forceinline__ void fence_proxy_async_smem() { asm volatile("fence.proxy.async.shared::cta;" ::: "memory"); }

__device__ __forceinline__ void tma_load_2d(uint32_t dst, const CUtensorMap* m, uint32_t bar, int c0, int c1) {
  asm volatile(ELECT "cp.async.bulk.tensor.2d.shared::cluster.global.mbarrier::complete_tx::bytes [%0], [%1, {%3, %4}], [%2];\n}"
               :: "r"(dst), "l"(m), "r"(bar), "r"(c0), "r"(c1) : "memory");
}
__device__ __forceinline__ void tma_load_3d(uint32_t dst, const CUtensorMap* m, uint32_t bar, int c0, int c1, int c2) {
  asm volatile(ELECT "cp.async.bulk.tensor.3d.shared::cluster.global.mbarrier::complete_tx::bytes [%0], [%1, {%3, %4, %5}], [%2];\n}"
               :: "r"(dst), "l"(m), "r"(bar), "r"(c0), "r"(c1), "r"(c2) : "memory");
}
__device__ __forceinline__ void tma_load_4d(uint32_t dst, const CUtensorMap* m, uint32_t bar, int c0, int c1, int c2, int c3) {
  asm volatile(ELECT "cp.async.bulk.tensor.4d.shared::cluster.global.mbarrier::complete_tx::bytes [%0], [%1, {%3, %4, %5, %6}], [%2];\n}"
               :: "r"(dst), "l"(m), "r"(bar), "r"(c0), "r"(c1), "r"(c2), "r"(c3) : "memory");
}
__device__ __forceinline__ void tma_store_2d(const CUtensorMap* m, uint32_t src, int c0, int c1) {
  asm volatile(ELECT "cp.async.bulk.tensor.2d.global.shared::cta.bulk_group [%0, {%2, %3}], [%1];\n}"
               :: "l"(m), "r"(src), "r"(c0), "r"(c1) : "memory");
}
__device__ __forceinline__ void tma_store_3d(const CUtensorMap* m, uint32_t src, int c0, int c1, int c2) {
  asm volatile(ELECT "cp.async.bulk.tensor.3d.global.shared::cta.bulk_group [%0, {%2, %3, %4}], [%1];\n}"
               :: "l"(m), "r"(src), "r"(c0), "r"(c1), "r"(c2) : "memory");
}
__device__ __forceinline__ void bulk_load(uint32_t dst, const void* src, uint32_t bytes, uint32_t bar) {
  asm volatile(ELECT "cp.async.bulk.shared::cluster.global.mbarrier::complete_tx::bytes [%0], [%1], %2, [%3];\n}"
               :: "r"(dst), "l"(src), "r"(bytes), "r"(bar) : "memory");
}
__device__ __forceinline__ void bulk_prefetch(const void* src, uint32_t bytes) {
  asm volatile(ELECT "cp.async.bulk.prefetch.L2.global [%0], %1;\n}" :: "l"(src), "r"(bytes) : "memory");
}
__device__ __forceinline__ void bulk_commit() { asm volatile("cp.async.bulk.commit_group;" ::: "memory"); }
__device__ __forceinline__ void bulk_wait0() { asm volatile("cp.async.bulk.wait_group 0;" ::: "memory"); }
__device__ __forceinline__ void bulk_wait_read0() { asm volatile("cp.async.bulk.wait_group.read 0;" ::: "memory"); }
__device__ __forceinline__ void prefetch_tmap(const CUtensorMap* m) { asm volatile("prefetch.tensormap [%0];" :: "l"(m) : "memory"); }
__device__ __forceinline__ void wgmma_fence() { asm volatile("wgmma.fence.sync.aligned;" ::: "memory"); }
__device__ __forceinline__ void wgmma_commit() { asm volatile("wgmma.commit_group.sync.aligned;" ::: "memory"); }
template <int N> __device__ __forceinline__ void wgmma_wait() { asm volatile("wgmma.wait_group.sync.aligned %0;" :: "n"(N) : "memory"); }
template <int R> __device__ __forceinline__ void reg_alloc() { asm volatile("setmaxnreg.inc.sync.aligned.u32 %0;" :: "n"(R)); }
template <int R> __device__ __forceinline__ void reg_dealloc() { asm volatile("setmaxnreg.dec.sync.aligned.u32 %0;" :: "n"(R)); }
__device__ __forceinline__ void bar_sync(int id, int n) { asm volatile("bar.sync %0, %1;" :: "r"(id), "r"(n) : "memory"); }
__device__ __forceinline__ void bar_arrive(int id, int n) { asm volatile("bar.arrive %0, %1;" :: "r"(id), "r"(n) : "memory"); }
__device__ __forceinline__ void sched_fence() {
  asm volatile("{\n.reg .pred p;\n.reg .b32 t;\nLAB_F:\nmov.u32 t, %%clock;\nsetp.eq.u32 p, t, %0;\n@p bra LAB_F;\n}" :: "n"(0) : "memory");
}
template <int N> __device__ __forceinline__ void fence_regs(float (&a)[N]) {
  #pragma unroll
  for (int i = 0; i < N; i++) asm volatile("" : "+f"(a[i]) :: "memory");
}
template <int N> __device__ __forceinline__ void undef_regs(float (&a)[N]) {
  #pragma unroll
  for (int i = 0; i < N; i++) asm volatile("" : "=f"(a[i]));
}

__device__ __forceinline__ uint64_t desc_from_lo(uint32_t lo) { return (uint64_t)lo | ((uint64_t)0x40000040u << 32); }
__device__ __forceinline__ uint32_t pack_bf16(float lo, float hi) {
  uint32_t r; asm("cvt.rn.bf16x2.f32 %0, %1, %2;" : "=r"(r) : "f"(hi), "f"(lo)); return r;
}
__device__ __forceinline__ uint32_t fma_bf2(uint32_t a, uint32_t b, uint32_t c) {
  uint32_t d; asm("fma.rn.bf16x2 %0, %1, %2, %3;" : "=r"(d) : "r"(a), "r"(b), "r"(c)); return d;
}
__device__ __forceinline__ float bf_lo(uint32_t v) { return __uint_as_float(v << 16); }
__device__ __forceinline__ float bf_hi(uint32_t v) { return __uint_as_float(v & 0xFFFF0000u); }
__device__ __forceinline__ float bf16_round(float x) { return bf_lo(pack_bf16(x, 0.f)); }
__device__ __forceinline__ void stmatrix_x4(uint32_t addr, uint32_t r0, uint32_t r1, uint32_t r2, uint32_t r3) {
  asm volatile("stmatrix.sync.aligned.m8n8.x4.shared.b16 [%0], {%1, %2, %3, %4};" :: "r"(addr), "r"(r0), "r"(r1), "r"(r2), "r"(r3) : "memory");
}
__device__ __forceinline__ void stmatrix_x4_if(uint32_t addr, uint32_t r0, uint32_t r1, uint32_t r2, uint32_t r3, bool on) {
  asm volatile("{\n.reg .pred p;\nsetp.ne.b32 p, %5, 0;\n@p stmatrix.sync.aligned.m8n8.x4.shared.b16 [%0], {%1, %2, %3, %4};\n}"
               :: "r"(addr), "r"(r0), "r"(r1), "r"(r2), "r"(r3), "r"((int)on) : "memory");
}
__device__ __forceinline__ void ldmatrix_x4(uint32_t addr, uint32_t& r0, uint32_t& r1, uint32_t& r2, uint32_t& r3) {
  asm volatile("ldmatrix.sync.aligned.m8n8.x4.shared.b16 {%0, %1, %2, %3}, [%4];" : "=r"(r0), "=r"(r1), "=r"(r2), "=r"(r3) : "r"(addr) : "memory");
}
__device__ __forceinline__ void ldmatrix_x4_t(uint32_t addr, uint32_t (&r)[4]) {
  asm volatile("ldmatrix.sync.aligned.m8n8.x4.trans.shared.b16 {%0, %1, %2, %3}, [%4];" : "=r"(r[0]), "=r"(r[1]), "=r"(r[2]), "=r"(r[3]) : "r"(addr) : "memory");
}
__device__ __forceinline__ uint32_t tagf(float v, unsigned par) { return (__float_as_uint(v) & ~1u) | par; }
__device__ __forceinline__ void st_rlx(void* p, uint32_t a, bool on) {
  asm volatile("{\n.reg .pred p;\nsetp.ne.b32 p, %2, 0;\n@p st.relaxed.gpu.global.u32 [%0], %1;\n}" :: "l"(p), "r"(a), "r"((int)on) : "memory");
}
__device__ __forceinline__ void st_rlx_v2(void* p, uint32_t a, uint32_t b, bool on) {
  asm volatile("{\n.reg .pred p;\nsetp.ne.b32 p, %3, 0;\n@p st.relaxed.gpu.global.v2.u32 [%0], {%1, %2};\n}" :: "l"(p), "r"(a), "r"(b), "r"((int)on) : "memory");
}
__device__ __forceinline__ uint2 ld_rlx_v2(const void* p) {
  uint2 v; asm volatile("ld.relaxed.gpu.global.v2.u32 {%0,%1}, [%2];" : "=r"(v.x), "=r"(v.y) : "l"(p) : "memory"); return v;
}
__device__ __forceinline__ void st_rlx_v4(void* p, uint32_t a, uint32_t b, uint32_t c, uint32_t d, bool on) {
  asm volatile("{\n.reg .pred p;\nsetp.ne.b32 p, %5, 0;\n@p st.relaxed.gpu.global.v4.u32 [%0], {%1, %2, %3, %4};\n}"
               :: "l"(p), "r"(a), "r"(b), "r"(c), "r"(d), "r"((int)on) : "memory");
}
__device__ __forceinline__ uint4 ld_rlx_v4(const void* p) {
  uint4 v; asm volatile("ld.relaxed.gpu.global.v4.u32 {%0,%1,%2,%3}, [%4];" : "=r"(v.x), "=r"(v.y), "=r"(v.z), "=r"(v.w) : "l"(p) : "memory"); return v;
}
__device__ __forceinline__ uint32_t movmatrix_t(uint32_t a) {
  uint32_t d; asm volatile("movmatrix.sync.aligned.m8n8.trans.b16 %0, %1;" : "=r"(d) : "r"(a)); return d;
}
__device__ __forceinline__ void mma16(float (&c)[4], uint32_t a0, uint32_t a1, uint32_t a2, uint32_t a3, uint32_t b0, uint32_t b1) {
  asm volatile("mma.sync.aligned.m16n8k16.row.col.f32.bf16.bf16.f32 {%0,%1,%2,%3}, {%4,%5,%6,%7}, {%8,%9}, {%0,%1,%2,%3};"
               : "+f"(c[0]), "+f"(c[1]), "+f"(c[2]), "+f"(c[3]) : "r"(a0), "r"(a1), "r"(a2), "r"(a3), "r"(b0), "r"(b1));
}
__device__ __forceinline__ void mma8(float (&c)[4], uint32_t a0, uint32_t a1, uint32_t b0) {
  asm volatile("mma.sync.aligned.m16n8k8.row.col.f32.bf16.bf16.f32 {%0,%1,%2,%3}, {%4,%5}, {%6}, {%0,%1,%2,%3};"
               : "+f"(c[0]), "+f"(c[1]), "+f"(c[2]), "+f"(c[3]) : "r"(a0), "r"(a1), "r"(b0));
}
__device__ __forceinline__ void sts128(uint32_t addr, uint32_t a, uint32_t b, uint32_t c, uint32_t d) {
  asm volatile("st.shared.v4.b32 [%0], {%1,%2,%3,%4};" :: "r"(addr), "r"(a), "r"(b), "r"(c), "r"(d) : "memory");
}
__device__ __forceinline__ uint4 lds128(uint32_t addr) {
  uint4 v; asm volatile("ld.shared.v4.b32 {%0,%1,%2,%3}, [%4];" : "=r"(v.x), "=r"(v.y), "=r"(v.z), "=r"(v.w) : "r"(addr) : "memory"); return v;
}
__device__ __forceinline__ float2 lds64f(uint32_t addr) {
  float2 v; asm volatile("ld.shared.v2.f32 {%0,%1}, [%2];" : "=f"(v.x), "=f"(v.y) : "r"(addr) : "memory"); return v;
}
__device__ __forceinline__ void sts64(uint32_t addr, uint32_t a, uint32_t b) {
  asm volatile("st.shared.v2.b32 [%0], {%1, %2};" :: "r"(addr), "r"(a), "r"(b) : "memory");
}
__device__ __forceinline__ float fast_ex2(float x) { float y; asm("ex2.approx.ftz.f32 %0, %1;" : "=f"(y) : "f"(x)); return y; }
__device__ __forceinline__ float fast_rcp(float x) { float y; asm("rcp.approx.ftz.f32 %0, %1;" : "=f"(y) : "f"(x)); return y; }
__device__ __forceinline__ float silu_f(float g) { return g * fast_rcp(1.f + fast_ex2(g * -1.4426950408889634f)); }
__device__ __forceinline__ float swiglu(float g, float u) {
  const float h = 0.5f * g;
  float t; asm("tanh.approx.f32 %0, %1;" : "=f"(t) : "f"(h));
  return fmaf(h, t, h) * u;
}

__device__ __forceinline__ void wgmma_m64n128k16_ss(float (&d)[64], uint64_t descA, uint64_t descB, int scaleD) {
  asm volatile("{\n.reg .pred p;\nsetp.ne.b32 p, %66, 0;\n"
    "wgmma.mma_async.sync.aligned.m64n128k16.f32.bf16.bf16 "
    "{%0, %1, %2, %3, %4, %5, %6, %7, %8, %9, %10, %11, %12, %13, %14, %15, "
    "%16, %17, %18, %19, %20, %21, %22, %23, %24, %25, %26, %27, %28, %29, %30, %31, "
    "%32, %33, %34, %35, %36, %37, %38, %39, %40, %41, %42, %43, %44, %45, %46, %47, "
    "%48, %49, %50, %51, %52, %53, %54, %55, %56, %57, %58, %59, %60, %61, %62, %63}, "
    "%64, %65, p, 1, 1, 0, 1;\n}\n"
    : "+f"(d[0]), "+f"(d[1]), "+f"(d[2]), "+f"(d[3]), "+f"(d[4]), "+f"(d[5]), "+f"(d[6]), "+f"(d[7]),
      "+f"(d[8]), "+f"(d[9]), "+f"(d[10]), "+f"(d[11]), "+f"(d[12]), "+f"(d[13]), "+f"(d[14]), "+f"(d[15]),
      "+f"(d[16]), "+f"(d[17]), "+f"(d[18]), "+f"(d[19]), "+f"(d[20]), "+f"(d[21]), "+f"(d[22]), "+f"(d[23]),
      "+f"(d[24]), "+f"(d[25]), "+f"(d[26]), "+f"(d[27]), "+f"(d[28]), "+f"(d[29]), "+f"(d[30]), "+f"(d[31]),
      "+f"(d[32]), "+f"(d[33]), "+f"(d[34]), "+f"(d[35]), "+f"(d[36]), "+f"(d[37]), "+f"(d[38]), "+f"(d[39]),
      "+f"(d[40]), "+f"(d[41]), "+f"(d[42]), "+f"(d[43]), "+f"(d[44]), "+f"(d[45]), "+f"(d[46]), "+f"(d[47]),
      "+f"(d[48]), "+f"(d[49]), "+f"(d[50]), "+f"(d[51]), "+f"(d[52]), "+f"(d[53]), "+f"(d[54]), "+f"(d[55]),
      "+f"(d[56]), "+f"(d[57]), "+f"(d[58]), "+f"(d[59]), "+f"(d[60]), "+f"(d[61]), "+f"(d[62]), "+f"(d[63])
    : "l"(descA), "l"(descB), "r"(scaleD));
}
__device__ __forceinline__ void wgmma_m64n256k16_rs(float (&d)[128], uint32_t a0, uint32_t a1, uint32_t a2, uint32_t a3, uint64_t descB, int scaleD) {
  asm volatile("{\n.reg .pred p;\nsetp.ne.b32 p, %133, 0;\n"
    "wgmma.mma_async.sync.aligned.m64n256k16.f32.bf16.bf16 "
    "{%0, %1, %2, %3, %4, %5, %6, %7, %8, %9, %10, %11, %12, %13, %14, %15, "
    "%16, %17, %18, %19, %20, %21, %22, %23, %24, %25, %26, %27, %28, %29, %30, %31, "
    "%32, %33, %34, %35, %36, %37, %38, %39, %40, %41, %42, %43, %44, %45, %46, %47, "
    "%48, %49, %50, %51, %52, %53, %54, %55, %56, %57, %58, %59, %60, %61, %62, %63, "
    "%64, %65, %66, %67, %68, %69, %70, %71, %72, %73, %74, %75, %76, %77, %78, %79, "
    "%80, %81, %82, %83, %84, %85, %86, %87, %88, %89, %90, %91, %92, %93, %94, %95, "
    "%96, %97, %98, %99, %100, %101, %102, %103, %104, %105, %106, %107, %108, %109, %110, %111, "
    "%112, %113, %114, %115, %116, %117, %118, %119, %120, %121, %122, %123, %124, %125, %126, %127}, "
    "{%128, %129, %130, %131}, %132, p, 1, 1, 1;\n}\n"
    : "+f"(d[0]), "+f"(d[1]), "+f"(d[2]), "+f"(d[3]), "+f"(d[4]), "+f"(d[5]), "+f"(d[6]), "+f"(d[7]),
      "+f"(d[8]), "+f"(d[9]), "+f"(d[10]), "+f"(d[11]), "+f"(d[12]), "+f"(d[13]), "+f"(d[14]), "+f"(d[15]),
      "+f"(d[16]), "+f"(d[17]), "+f"(d[18]), "+f"(d[19]), "+f"(d[20]), "+f"(d[21]), "+f"(d[22]), "+f"(d[23]),
      "+f"(d[24]), "+f"(d[25]), "+f"(d[26]), "+f"(d[27]), "+f"(d[28]), "+f"(d[29]), "+f"(d[30]), "+f"(d[31]),
      "+f"(d[32]), "+f"(d[33]), "+f"(d[34]), "+f"(d[35]), "+f"(d[36]), "+f"(d[37]), "+f"(d[38]), "+f"(d[39]),
      "+f"(d[40]), "+f"(d[41]), "+f"(d[42]), "+f"(d[43]), "+f"(d[44]), "+f"(d[45]), "+f"(d[46]), "+f"(d[47]),
      "+f"(d[48]), "+f"(d[49]), "+f"(d[50]), "+f"(d[51]), "+f"(d[52]), "+f"(d[53]), "+f"(d[54]), "+f"(d[55]),
      "+f"(d[56]), "+f"(d[57]), "+f"(d[58]), "+f"(d[59]), "+f"(d[60]), "+f"(d[61]), "+f"(d[62]), "+f"(d[63]),
      "+f"(d[64]), "+f"(d[65]), "+f"(d[66]), "+f"(d[67]), "+f"(d[68]), "+f"(d[69]), "+f"(d[70]), "+f"(d[71]),
      "+f"(d[72]), "+f"(d[73]), "+f"(d[74]), "+f"(d[75]), "+f"(d[76]), "+f"(d[77]), "+f"(d[78]), "+f"(d[79]),
      "+f"(d[80]), "+f"(d[81]), "+f"(d[82]), "+f"(d[83]), "+f"(d[84]), "+f"(d[85]), "+f"(d[86]), "+f"(d[87]),
      "+f"(d[88]), "+f"(d[89]), "+f"(d[90]), "+f"(d[91]), "+f"(d[92]), "+f"(d[93]), "+f"(d[94]), "+f"(d[95]),
      "+f"(d[96]), "+f"(d[97]), "+f"(d[98]), "+f"(d[99]), "+f"(d[100]), "+f"(d[101]), "+f"(d[102]), "+f"(d[103]),
      "+f"(d[104]), "+f"(d[105]), "+f"(d[106]), "+f"(d[107]), "+f"(d[108]), "+f"(d[109]), "+f"(d[110]), "+f"(d[111]),
      "+f"(d[112]), "+f"(d[113]), "+f"(d[114]), "+f"(d[115]), "+f"(d[116]), "+f"(d[117]), "+f"(d[118]), "+f"(d[119]),
      "+f"(d[120]), "+f"(d[121]), "+f"(d[122]), "+f"(d[123]), "+f"(d[124]), "+f"(d[125]), "+f"(d[126]), "+f"(d[127])
    : "r"(a0), "r"(a1), "r"(a2), "r"(a3), "l"(descB), "r"(scaleD));
}

constexpr uint32_t MSLOT = 32768, QSLOT = 49152;
constexpr int NM = 6, NQ = 4;
constexpr uint32_t SM_X0 = 3 * QSLOT;
constexpr uint32_t SM_XR = SM_X0 + 16384;
constexpr uint32_t SM_STG = 196608;
constexpr uint32_t SM_XCH = SM_STG + 16384;
constexpr uint32_t SM_BAR = SM_STG + 32768;
constexpr uint32_t SM_VEC = SM_BAR + 512;
constexpr uint32_t SM_MODT = SM_VEC;
constexpr uint32_t SM_TOTAL = SM_VEC + 2048;
constexpr uint32_t B_FQ = SM_BAR, B_EQ = SM_BAR + 32, B_FM = SM_BAR + 64, B_EM = SM_BAR + 112, B_MOD = SM_BAR + 160,
                   B_STREQ = SM_BAR + 224, B_STFREE = SM_BAR + 232, B_VEC = SM_BAR + 240  , B_X = SM_BAR + 256  , B_LN = SM_BAR + 320,
                   B_FLG = SM_BAR + 328  , B_STH = SM_BAR + 416;
constexpr int NB_WG = 1  , NB_CONS = 3, NB_ORD = 4  ;
#define PF_BYTES 512
#define PF2_BYTES 0
#define Q_GAP 0
#define X_POLL 6
#define SVC_WAIT mbar_sleep
#define PRD_WAIT mbar_wait
#define WPRE 3
#define HOLD1 2
#define HOLD2 2
#define ST0 0
#define QORD 2
#define QPOS 1
#define AUX_SLOW 68
#define AUX_GAP 500
#define X_UP 2
#define X_GAP 200
#define X_PER 2
#define NEARLY 2

struct Maps {
  CUtensorMap x, out;
  CUtensorMap o, h2, hh;
  CUtensorMap wqk, wvv, wq1, wo, w1, w3, w2;
  CUtensorMap wmod;
};

struct Ring { int st; uint32_t ph; int prev; uint32_t dl; };
__device__ __forceinline__ void ring_next(Ring& r) { if (++r.st == NM) { r.st = 0; r.ph ^= 1; } }

__device__ __forceinline__ void retire_prev(uint32_t rel) {
  wgmma_commit();
  wgmma_wait<1>();
  if (rel) mbar_arrive_e(rel);
}
struct Nop { __device__ __forceinline__ void operator()() const {} };
template <class F = Nop>
__device__ __forceinline__ void mma_step(float (&acc)[64], uint32_t a, uint32_t b, bool first, uint32_t rel, F urgent = F()) {
  const uint32_t alo = (a >> 4) + (1u << 16), blo = (b >> 4) + (512u << 16);
  wgmma_fence();
  #pragma unroll
  for (int k = 0; k < 4; k++) {
    wgmma_m64n128k16_ss(acc, desc_from_lo(alo + k * 2), desc_from_lo(blo + k * 128), k > 0 || !first);
    if (k == 0) { retire_prev(rel); urgent(); }
  }
  wgmma_commit();
}
__device__ __forceinline__ uint32_t m_wait(uint32_t sbase, const Ring& r) {
  mbar_wait(sbase + B_FM + 8 * r.st, r.ph, r.dl);
  return sbase + r.st * MSLOT;
}
__device__ __forceinline__ uint32_t m_prev(uint32_t sbase, const Ring& r) { return sbase + B_EM + 8 * r.prev; }
__device__ __forceinline__ void m_next(Ring& r) { r.prev = r.st; ring_next(r); }
__device__ __forceinline__ void m_step(float (&acc)[64], uint32_t sbase, uint32_t wgoff, Ring& r, bool first = false) {
  const uint32_t slot = m_wait(sbase, r);
  mma_step(acc, slot + wgoff, slot + 16384, first, m_prev(sbase, r));
  m_next(r);
}

struct LnRow { uint32_t rs[2], nb[2]; };
__device__ __forceinline__ void ln_row(LnRow& l, int h, float mean, float rstd) {
  l.rs[h] = pack_bf16(rstd, rstd);
  const float nb = -mean * bf_lo(l.rs[h]);
  l.nb[h] = pack_bf16(nb, nb);
}
__device__ __forceinline__ uint32_t ln_mod(uint32_t x, const LnRow& l, int h, uint32_t c1, uint32_t s) {
  return fma_bf2(fma_bf2(x, l.rs[h], l.nb[h]), c1, s);
}

__device__ __forceinline__ uint32_t q_wait(int u, uint32_t sbase, uint32_t dl) {
  mbar_wait(sbase + B_FQ + 8 * (u & 3), (u >> 2) & 1, dl);
  return sbase + (u & 3) * QSLOT;
}
__device__ __forceinline__ uint32_t q_empty(int u, uint32_t sbase) { return sbase + B_EQ + 8 * (u & 3); }
struct Frag4 { uint32_t o[4]; };
__device__ __forceinline__ void q_load(uint32_t (&A)[16], uint4 (&p)[4], int kk, uint32_t tile, const Frag4& f, uint32_t t) {
  ldmatrix_x4(tile + f.o[kk], A[4 * kk], A[4 * kk + 1], A[4 * kk + 2], A[4 * kk + 3]);
  p[kk] = lds128(t + kk * 64);
}
__device__ __forceinline__ void q_norm(uint32_t (&A)[16], const uint4 (&p)[4], int kk, const LnRow& l) {
  A[4 * kk + 0] = ln_mod(A[4 * kk + 0], l, 0, p[kk].x, p[kk].z); A[4 * kk + 1] = ln_mod(A[4 * kk + 1], l, 1, p[kk].x, p[kk].z);
  A[4 * kk + 2] = ln_mod(A[4 * kk + 2], l, 0, p[kk].y, p[kk].w); A[4 * kk + 3] = ln_mod(A[4 * kk + 3], l, 1, p[kk].y, p[kk].w);
}
template <bool NEXT>
__device__ __forceinline__ void q_step_rs(float (&acc)[128], uint32_t (&A)[16], uint32_t (&N)[16], uint4 (&p)[4], int u, uint32_t sbase,
                                          const Frag4& f, uint32_t tab, const LnRow& l, int hq, bool first, uint32_t dl, int wg) {
  const uint32_t slot = first ? sbase : q_wait(u, sbase, dl);
  const uint32_t blo = ((slot + 16384) >> 4) + (512u << 16), t = tab + ((u + 1) & 7) * 256;
  #pragma unroll
  for (int kk = 0; kk < 4; kk++) q_norm(A, p, kk, l);
  if (QORD == 1 && first && wg == 1) bar_sync(NB_ORD, 256);
  if (QORD == 2 && !(first && wg == 0)) bar_sync(NB_ORD + wg, 256);
  wgmma_fence();
  #pragma unroll
  for (int kk = 0; kk < 4; kk++) {
    wgmma_m64n256k16_rs(acc, A[4 * kk], A[4 * kk + 1], A[4 * kk + 2], A[4 * kk + 3], desc_from_lo(blo + kk * 128), kk > 0 || !first);
    if (kk == 0) retire_prev(first ? 0 : q_empty(u - 1, sbase));
    if (NEXT && kk < 2) { q_load(N, p, 2 * kk, slot, f, t); q_load(N, p, 2 * kk + 1, slot, f, t); }
    if (QORD == 1 && first && kk == QPOS && wg == 0) bar_arrive(NB_ORD, 256);
    if (QORD == 2 && kk == QPOS && (NEXT || wg == 0)) bar_arrive(NB_ORD + (wg ^ 1), 256);
    if (kk == 1) {
      const uint32_t dst = sbase + SM_STG + (u >> 3) * 16384 + (f.o[0] ^ ((u & 6) << 4));
      #pragma unroll
      for (int q = 0; q < 4; q++) stmatrix_x4_if(dst, A[4 * q], A[4 * q + 1], A[4 * q + 2], A[4 * q + 3], hq == q);
    }
  }
  wgmma_commit();
}

typedef uint32_t Frag8[8];
template <int N> __device__ __forceinline__ void pack_half(Frag8& f, const float (&acc)[N], int off, int half) {
  #pragma unroll
  for (int e = 0; e < 8; e++) { f[e] = pack_bf16(acc[off + 4 * e + 2 * half], acc[off + 4 * e + 2 * half + 1]); asm volatile("" : "+r"(f[e])); }
}
__device__ __forceinline__ void transpose8(Frag8& f) {
  #pragma unroll
  for (int e = 0; e < 8; e++) f[e] = movmatrix_t(f[e]);
}
__device__ __forceinline__ void attn_send(const Frag8& f, int kv, uint32_t xch, int warp, uint4* halo_out, bool has_next) {
  if (warp == 3) {
    st_rlx_v4(halo_out + kv * 64, f[0], f[1], f[2], f[3], has_next); st_rlx_v4(halo_out + kv * 64 + 32, f[4], f[5], f[6], f[7], has_next);
  } else {
    sts128(xch + 2048 + kv * 1024, f[0], f[1], f[2], f[3]); sts128(xch + 2048 + kv * 1024 + 512, f[4], f[5], f[6], f[7]);
  }
}
template <int N>
__device__ __forceinline__ void attn_recv(uint4* p, int first, uint32_t xch, int wg, int warp, const uint4* halo_in, bool has_prev) {
  bar_sync(NB_WG + wg, 128);
  #pragma unroll
  for (int e = 0; e < N; e++)
    asm volatile("{\n.reg .pred p, q;\nsetp.ne.b32 p, %6, 0;\nsetp.ne.b32 q, %7, 0;\n"
                 "mov.b32 %0, 0;\nmov.b32 %1, 0;\nmov.b32 %2, 0;\nmov.b32 %3, 0;\n"
                 "@p ld.shared.v4.b32 {%0,%1,%2,%3}, [%4];\n@q ld.relaxed.gpu.global.v4.u32 {%0,%1,%2,%3}, [%5];\n}"
                 : "=&r"(p[e].x), "=&r"(p[e].y), "=&r"(p[e].z), "=&r"(p[e].w)
                 : "r"(xch + (first + e) * 512), "l"(halo_in + (first + e) * 32), "r"((int)(warp > 0)), "r"((int)(warp == 0 && has_prev)) : "memory");
}
template <int N>
__device__ __forceinline__ void attn_check(uint4* p, int first, int warp, const uint4* halo_in, uint32_t dl) {
  if (warp == 0) {
    while (true) {
      uint32_t m = 0;
      #pragma unroll
      for (int e = 0; e < N; e++) m = max(max(m, max(p[e].x, p[e].y)), max(p[e].z, p[e].w));
      if (poll_done(m != ~0u, dl)) break;
      #pragma unroll
      for (int e = 0; e < N; e++) p[e] = ld_rlx_v4(halo_in + (first + e) * 32);
    }
  }
}
__device__ __forceinline__ void attn_core(const Frag8& qA, const Frag8& qB, const Frag8& kA, const Frag8& kB, const Frag8& vA, const Frag8& vB,
                                          const uint4* kP, const uint4* vP, bool noprev, int lane, float (&o)[2][5][4]) {
  const int g = lane >> 2, qd = lane & 3;
  const bool s0 = 2 * qd > g, s1 = 2 * qd + 1 > g;
  const uint32_t msk = (s0 ? 0xFFFFu : 0u) | (s1 ? 0xFFFF0000u : 0u);
  constexpr float SC = 0.17677669529663687f * 1.4426950408889634f;
  float s[2][3][4];
  #pragma unroll
  for (int h = 0; h < 2; h++)
    #pragma unroll
    for (int nb = 0; nb < 3; nb++) s[h][nb][0] = s[h][nb][1] = s[h][nb][2] = s[h][nb][3] = 0.f;
  #pragma unroll
  for (int kk = 0; kk < 2; kk++)
    #pragma unroll
    for (int h = 0; h < 2; h++) {
      const int e = 4 * h + 2 * kk;
      mma16(s[h][1], qA[e], qB[e], qA[e + 1], qB[e + 1], kA[e], kA[e + 1]);
      mma16(s[h][2], qA[e], qB[e], qA[e + 1], qB[e + 1], kB[e], kB[e + 1]);
      mma16(s[h][0], qA[e], qB[e], qA[e + 1], qB[e + 1], kk ? kP[h].z : kP[h].x, kk ? kP[h].w : kP[h].y);
    }
  float l[2][4], m[2][2];
  #pragma unroll
  for (int h = 0; h < 2; h++) {
    l[h][0] = s0 ? (noprev ? -INFINITY : s[h][0][0]) : s[h][1][0];
    l[h][1] = s1 ? (noprev ? -INFINITY : s[h][0][1]) : s[h][1][1];
    l[h][2] = s0 ? s[h][1][2] : s[h][2][2];
    l[h][3] = s1 ? s[h][1][3] : s[h][2][3];
    m[h][0] = fmaxf(l[h][0], l[h][1]); m[h][1] = fmaxf(l[h][2], l[h][3]);
  }
  #pragma unroll
  for (int x = 1; x <= 2; x <<= 1)
    #pragma unroll
    for (int e = 0; e < 4; e++) m[e >> 1][e & 1] = fmaxf(m[e >> 1][e & 1], __shfl_xor_sync(0xffffffffu, m[e >> 1][e & 1], x));
  #pragma unroll
  for (int h = 0; h < 2; h++) {
    #pragma unroll
    for (int e = 0; e < 4; e++) l[h][e] = fast_ex2((l[h][e] - m[h][e >> 1]) * SC);
    const uint32_t plo = pack_bf16(l[h][0], l[h][1]), phi = pack_bf16(l[h][2], l[h][3]);
    const uint32_t vp[4] = {vP[h].x, vP[h].y, vP[h].z, vP[h].w};
    #pragma unroll
    for (int d = 0; d < 5; d++) o[h][d][0] = o[h][d][1] = o[h][d][2] = o[h][d][3] = 0.f;
    mma8(o[h][4], plo, phi, 0x3F803F80u);
    #pragma unroll
    for (int d = 0; d < 4; d++) mma16(o[h][d], plo & ~msk, phi & msk, 0u, phi & ~msk, vA[4 * h + d], vB[4 * h + d]);
    #pragma unroll
    for (int d = 0; d < 4; d++) mma8(o[h][d], plo & msk, 0u, vp[d]);
  }
}
__device__ __forceinline__ void attn_store(const float (&o)[2][5][4], int h, uint32_t sbase, const Frag4& f) {
  const float r0 = fast_rcp(o[h][4][0]), r1 = fast_rcp(o[h][4][2]);
  #pragma unroll
  for (int d = 0; d < 4; d += 2)
    stmatrix_x4(sbase + SM_STG + f.o[2 * h + (d >> 1)],
                pack_bf16(o[h][d][0] * r0, o[h][d][1] * r0), pack_bf16(o[h][d][2] * r1, o[h][d][3] * r1),
                pack_bf16(o[h][d + 1][0] * r0, o[h][d + 1][1] * r0), pack_bf16(o[h][d + 1][2] * r1, o[h][d + 1][3] * r1));
}

__device__ __forceinline__ void g_switch(float (&cur)[64], float (&prv)[64], int nrest, bool first, int n, uint32_t sbase, uint32_t wgoff,
                                         const Frag4& f, Ring& r) {
  #pragma unroll 1
  for (int i = 1; i < nrest; i++) m_step(prv, sbase, wgoff, r);
  m_step(prv, sbase, wgoff, r);
  m_step(cur, sbase, wgoff, r, first);
  mbar_wait(sbase + B_STFREE, (n - 1) & 1, r.dl);
  fence_regs(prv);
  PROF(28 + n, threadIdx.x == 0);
  #pragma unroll
  for (int jj = 0; jj < 4; jj++) {
    uint32_t p[4];
    #pragma unroll
    for (int e = 0; e < 4; e++) {
      const int i = jj * 8 + e * 2;
      p[e] = pack_bf16(swiglu(prv[i], prv[i + 32]), swiglu(prv[i + 1], prv[i + 33]));
    }
    stmatrix_x4(sbase + SM_STG + f.o[jj], p[0], p[1], p[2], p[3]);
    m_step(cur, sbase, wgoff, r);
  }
  mbar_arrive_e(sbase + B_STREQ);
}

__device__ __forceinline__ uint32_t bad2(uint32_t a, uint32_t b, unsigned par) {
  uint32_t d; asm("lop3.b32 %0, %1, %2, %3, 0x7E;" : "=r"(d) : "r"(a), "r"(b), "r"(par)); return d;
}
__device__ __forceinline__ uint32_t bad4(const uint4& v, unsigned par) { return bad2(v.x, v.y, par) | bad2(v.z, v.w, par); }
__device__ __forceinline__ uint32_t hi_halves(uint32_t lo, uint32_t hi) { return __byte_perm(lo, hi, 0x7632); }

__device__ __forceinline__ void gather_table(const float* src, uint32_t dst, uint32_t bar, unsigned par, uint32_t dl) {
  asm volatile("{\n.reg .pred p, e;\n.reg .b32 s<4>, c<4>, t<4>, w<4>;\n"
               "elect.sync _|e, 0xffffffff;\n"
               "LAB_POLL:\n"
               "ld.relaxed.gpu.global.v4.u32 {s0, s1, s2, s3}, [%0];\n"
               "ld.relaxed.gpu.global.v4.u32 {c0, c1, c2, c3}, [%0 + 4096];\n"
               "prmt.b32 w0, c0, c1, 0x7632;\nprmt.b32 w1, c2, c3, 0x7632;\nprmt.b32 w2, s0, s1, 0x7632;\nprmt.b32 w3, s2, s3, 0x7632;\n"
               "st.shared.v4.b32 [%1], {w0, w1, w2, w3};\n"
               "lop3.b32 t0, s0, s1, %3, 0x7E;\nlop3.b32 t1, s2, s3, %3, 0x7E;\nlop3.b32 t2, c0, c1, %3, 0x7E;\nlop3.b32 t3, c2, c3, %3, 0x7E;\n"
               "lop3.b32 t0, t0, t1, 1, 0xA8;\nlop3.b32 t2, t2, t3, 1, 0xA8;\n"
               "or.b32 t0, t0, t2;\n"
               "setp.eq.u32 p, t0, 0;\n"
               "vote.sync.all.pred p, p, 0xffffffff;\n"
               "@p bra.uni LAB_OK;\n"
               "mov.u32 t0, %%clock;\nsub.s32 t0, t0, %4;\nsetp.lt.s32 p, t0, 0;\n"
               "vote.sync.all.pred p, p, 0xffffffff;\n"
               "@p bra.uni LAB_POLL;\n"
               "LAB_OK:\n"
               "@e mbarrier.arrive.shared::cta.b64 _, [%2];\n}"
               :: "l"(src), "r"(dst), "r"(bar), "r"(par), "r"(dl) : "memory");
}

__device__ __forceinline__ int other_slot(int i, int j) { return i < 4 ? (~j & 4) + i : (j & 4) + i - 4 + (i - 4 >= (j & 3)); }

__device__ __forceinline__ int aux_col(int a, int u) { return u < 8 ? (a & 1) * 1024 + (2 * u + (a >> 1)) * 64 : 2048 + ((u - 8) * 4 + a) * 64; }
constexpr int NA = 7;
constexpr uint32_t A_FULL = SM_BAR, A_EMPTY = SM_BAR + 64, A_SUM = SM_BAR + 128, A_FREE = SM_BAR + 136, SM_RED = SM_VEC;
__device__ __forceinline__ void aux_role(const Maps& maps, const bf16* __restrict__ cvec, int a, uint32_t sbase, int wid) {
  const int tid = threadIdx.x, lane = tid & 31;
  const uint32_t dl = clock32() + 800000000u;
  int st = 0; uint32_t ph = 0;
  if (wid == 8) {
    if (lane == 0) {
      prefetch_tmap(&maps.wmod);
      for (int s = 0; s < NA; s++) { mbar_init(sbase + A_FULL + 8 * s, 1); mbar_init(sbase + A_EMPTY + 8 * s, 8); }
      mbar_init(sbase + A_SUM, 8); mbar_init(sbase + A_FREE, 2);
      asm volatile("fence.mbarrier_init.release.cluster;" ::: "memory");
      fence_proxy_async_smem();
    }
    __syncwarp();
    #pragma unroll 1
    for (int i = 0; i < 96; i++) {
      if (i == NA) bar_sync(0, 352);
      if (i >= AUX_SLOW) wait_until(clock32() + AUX_GAP);
      mbar_wait(sbase + A_EMPTY + 8 * st, ph ^ 1, dl);
      mbar_expect_tx_e(sbase + A_FULL + 8 * st, 32768);
      tma_load_2d(sbase + st * MSLOT, &maps.wmod, sbase + A_FULL + 8 * st, aux_col(a, i >> 2), (i & 3) * 256);
      if (++st == NA) { st = 0; ph ^= 1; }
    }
  } else if (wid < 8) {
    const int g = lane >> 2, qd = lane & 3;
    uint32_t sc[16];
    #pragma unroll
    for (int i = 0; i < 16; i++) sc[i] = *reinterpret_cast<const uint32_t*>(cvec + (i >> 2) * 256 + wid * 32 + (i & 3) * 8 + qd * 2);
    #pragma unroll
    for (int i = 0; i < 16; i++) sc[i] = pack_bf16(silu_f(bf_lo(sc[i])), silu_f(bf_hi(sc[i])));
    bar_sync(0, 352);
    PROFN(0, tid == 0);
    const uint32_t aoff = (wid * 32 + (lane & 7) + (lane >> 4) * 8) * 128 + ((((lane >> 3) & 1) ^ (lane & 7)) << 4);
    uint32_t w[2][8][4];
    auto fetch = [&](uint32_t (&f)[8][4]) {
      mbar_wait(sbase + A_FULL + 8 * st, ph, dl);
      #pragma unroll
      for (int e = 0; e < 8; e++) ldmatrix_x4_t((sbase + st * MSLOT + aoff + (e >> 2) * 2048) ^ ((e & 3) << 5), f[e]);
      mbar_arrive_e(sbase + A_EMPTY + 8 * st);
      if (++st == NA) { st = 0; ph ^= 1; }
    };
    #pragma unroll 1
    for (int u = 0; u < 24; u++) {
      float acc[4][4];
      #pragma unroll
      for (int m = 0; m < 4; m++) acc[m][0] = acc[m][1] = acc[m][2] = acc[m][3] = 0.f;
      fetch(w[0]);
      #pragma unroll
      for (int q = 0; q < 4; q++) {
        PROF(30 + (u & 1) * 4 + q, u < 2 && tid == 0);
        if (q < 3) fetch(w[(q + 1) & 1]);
        if (q == 1) mbar_wait(sbase + A_FREE, (u & 1) ^ 1, dl);
        #pragma unroll
        for (int e = 0; e < 8; e++) {
          const uint32_t (&f)[4] = w[q & 1][e];
          mma16(acc[e & 3], f[0], f[1], f[2], f[3], sc[4 * q + 2 * (e >> 2)], sc[4 * q + 2 * (e >> 2) + 1]);
        }
      }
      const float v0 = qd & 2 ? (qd & 1 ? acc[3][0] : acc[2][0]) : (qd & 1 ? acc[1][0] : acc[0][0]);
      const float v1 = qd & 2 ? (qd & 1 ? acc[3][2] : acc[2][2]) : (qd & 1 ? acc[1][2] : acc[0][2]);
      sts64(sbase + SM_RED + wid * 256 + (qd * 8 + g) * 8, __float_as_uint(v0), __float_as_uint(v1));
      mbar_arrive_e(sbase + A_SUM);
    }
  } else if (wid < 11) {
    const unsigned par = (1 + ld_relaxed(&g_flags[FL_EPOCH])) & 1;
    float* const mail = &g_mod[(wid - 9) * 4 * 6 * D_ + 2 * lane];
    bar_sync(0, 352);
    #pragma unroll 1
    for (int u = -2; u < 24; u++) {
      if (u >= 0) {
        const int col = aux_col(a, u);
        const float add = (col >> 10) == 1 || (col >> 10) == 4 ? 1.f : 0.f;
        mbar_wait(sbase + A_SUM, u & 1, dl);
        float2 v[8];
        #pragma unroll
        for (int w = 0; w < 8; w++) v[w] = lds64f(sbase + SM_RED + w * 256 + lane * 8);
        const float t0 = ((v[0].x + v[1].x) + (v[2].x + v[3].x)) + ((v[4].x + v[5].x) + (v[6].x + v[7].x));
        const float t1 = ((v[0].y + v[1].y) + (v[2].y + v[3].y)) + ((v[4].y + v[5].y) + (v[6].y + v[7].y));
        const uint32_t w = pack_bf16(add + bf16_round(t0), add + bf16_round(t1)), o = __shfl_xor_sync(0xffffffffu, w, 1);
        const uint32_t m0 = (lane & 1) ? (o & 0xFFFF0000u) : (w << 16), m1 = (lane & 1) ? (w & 0xFFFF0000u) : (o << 16);
        #pragma unroll
        for (int c = 0; c < 4; c++) st_rlx_v2(mail + c * 6 * D_ + col, m0 | par, m1 | par, true);
        mbar_arrive_e(sbase + A_FREE);
        PROF(1 + u, tid == 288);
      }
      #pragma unroll 1
      for (int v = 2 * (u + 2); v < 2 * (u + 3) && v < 24; v++)
        #pragma unroll
        for (int c = 0; c < 4; c++) st_rlx_v2(mail + c * 6 * D_ + aux_col(a, v), par ^ 1, par ^ 1, true);
    }
  }
}

__global__ void __launch_bounds__(384, 1)
fused_block_kernel(const __grid_constant__ Maps maps, const bf16* __restrict__ x, const bf16* __restrict__ cvec, const bf16* __restrict__ wmod,
                   int mode) {
  extern __shared__ __align__(1024) uint8_t smem_raw[];
  const uint32_t sbase = smem_u32(smem_raw);
  const int tid = threadIdx.x, lane = tid & 31;
  const int wid = __shfl_sync(0xffffffffu, tid >> 5, 0);
  int b = blockIdx.x;
  if (AUXPOS < 0) { b -= NAUX; if (b < 0) { aux_role(maps, cvec, b + NAUX, sbase, wid); return; } }
  else {
  if (mode == 1 || (mode == 0 && b % 33 == AUXPOS)) { aux_role(maps, cvec, mode == 1 ? b : b / 33, sbase, wid); return; }
  if (mode == 0) b -= (b + 32 - AUXPOS) / 33;
  }
  const int jg = b >> 6, mb = jg ? 31 - (b >> 2) : (b >> 2), j = 4 * jg + (b & 3);
  const uint32_t dl = clock32() + 800000000u;
  unsigned* const flags = &g_flags[mb * 32];
  const unsigned e1 = 1 + ld_relaxed(wid >= 10 ? &g_flags[FL_EPOCH] : flags + FO_EPOCH);
  const unsigned par = e1 & 1;
  const int row0 = mb * 128;

  if (wid >= 8) {
    if (wid == 8) {
      if (lane == 0) {
        for (int s = 0; s < 8; s++) mbar_init(sbase + B_X + 8 * s, 1);
        asm volatile("fence.mbarrier_init.release.cluster;" ::: "memory");
        fence_proxy_async_smem();
      }
      #pragma unroll 1
      for (int q = 0; q < X_UP; q++) {
        mbar_expect_tx_e(sbase + B_X + 8 * q, 4096);
        bulk_load(sbase + SM_XR + q * 4096, x + (size_t)(row0 + j * 16 + 2 * q) * D_, 4096, sbase + B_X + 8 * q);
      }
    } else if (tid == 288) {
      for (int s = 0; s < NQ; s++) { mbar_init(sbase + B_FQ + 8 * s, 1 + (s & 1)); mbar_init(sbase + B_EQ + 8 * s, 8); }
      for (int s = 0; s < NM; s++) { mbar_init(sbase + B_FM + 8 * s, 1); mbar_init(sbase + B_EM + 8 * s, 8); }
      mbar_init(sbase + B_MOD, 2);
      mbar_init(sbase + B_STREQ, 8); mbar_init(sbase + B_STFREE, 1); mbar_init(sbase + B_VEC, 1); mbar_init(sbase + B_VEC + 8, 1); mbar_init(sbase + B_LN, 8);
      for (int s = 0; s < 11; s++) mbar_init(sbase + B_FLG + 8 * s, 1);
      mbar_init(sbase + B_STH, 8);
      asm volatile("fence.mbarrier_init.release.cluster;" ::: "memory");
      fence_proxy_async_smem();
    } else if (tid >= 320 && tid < 332) {
      prefetch_tmap(&maps.x + (tid - 320));
    }
    bar_sync(0, 384);
    reg_dealloc<40>();
    if (wid == 8) {
      uint32_t tnext = clock32();
      int xq = X_UP;
      #pragma unroll 1
      for (int u = 0; u < 16; u++) {
        const int st = u & 3;
        if (u <= NEARLY) {
          #pragma unroll 1
          for (; xq < 8 && (xq < X_UP + u * X_PER || u == NEARLY); xq++) {
            tnext += X_GAP; wait_until(tnext);
            mbar_expect_tx_e(sbase + B_X + 8 * xq, 4096);
            bulk_load(sbase + SM_XR + xq * 4096, x + (size_t)(row0 + j * 16 + 2 * xq) * D_, 4096, sbase + B_X + 8 * xq);
          }
          if (u == NEARLY) { PRD_WAIT(sbase + B_MOD, 0, dl); PROFN(60, lane == 0); tnext = clock32(); }
        } else if (u < NQ) { tnext += Q_GAP; wait_until(tnext); }
        if (u == 3) PRD_WAIT(sbase + B_EQ, 0, dl);
        PRD_WAIT(sbase + B_EQ + 8 * st, ((u >> 2) & 1) ^ 1, dl);
        const uint32_t slot = sbase + st * QSLOT, fb = sbase + B_FQ + 8 * st;
        mbar_expect_tx_e(fb, u == 0 ? 65536 : u == 15 ? 32768 : 49152);
        if (u == 0) tma_load_3d(sbase + SM_X0, &maps.x, fb, 0, mb * 64, 0);
        tma_load_4d(slot + 16384, &maps.wqk, fb, 0, u * 64, j, 0);
        tma_load_4d(slot + 32768, &maps.wvv, fb, 0, u * 64, j, 0);
        if (u < 15) tma_load_3d(slot, &maps.x, fb, u * 64 + 64, mb * 64, 0);
      }
      Ring r{0, 1, 0, dl};
      uint32_t slot, fb;
      auto acquire = [&](uint32_t bytes) {
        PRD_WAIT(sbase + B_EM + 8 * r.st, r.ph, dl);
        slot = sbase + r.st * MSLOT; fb = sbase + B_FM + 8 * r.st;
        mbar_expect_tx_e(fb, bytes);
        ring_next(r);
      };
      auto hold = [&](int n) { Ring h = r; for (int i = 0; i < n; i++) ring_next(h); PRD_WAIT(sbase + B_EM + 8 * h.st, h.ph, dl); };
      #pragma unroll 1
      for (int kt = 0; kt < 16; kt++) {
        if (kt < 5) PRD_WAIT(sbase + B_EQ + 8 * (kt - (kt >= 2)), 1, dl);
        if (kt == 8) hold(HOLD1);
        if ((kt & 7) == 0) { PROF(46, lane == 0 && kt == 8); PRD_WAIT(sbase + B_FLG + kt, 0, dl); PROF(47, lane == 0 && kt == 8); }
        acquire(32768);
        tma_load_4d(slot + 16384, &maps.wq1, fb, (j + 8) * 64, (kt & 1) * 64 + (kt & 6) * 8, (kt >> 3) * 4, 0);
        tma_load_3d(slot, &maps.hh, fb, (kt & 7) * 64, row0, kt >> 3);
      }
      hold(HOLD2);
      PROF(82, lane == 0);
      PRD_WAIT(sbase + B_FLG + 16, 0, dl);
      PROF(83, lane == 0);
      #pragma unroll 1
      for (int kt = 0; kt < 8; kt++) {
        acquire(32768);
        tma_load_3d(slot + 16384, &maps.wo, fb, 0, kt * 64, 2 * j);
        tma_load_2d(slot, &maps.o, fb, kt * 64, row0);
      }
      acquire(16384);
      tma_load_3d(slot + 16384, &maps.wo, fb, 0, (8 + j) * 64, 2 * j);
      {
        constexpr int NPRE = WPRE;
        Ring ra = r;
        #pragma unroll 1
        for (int i = 0; i < 7; i++) {
          const int kt = 8 + other_slot(i, j);
          if (i == 4) {
            acquire(32768);
            tma_load_3d(slot, &maps.x, fb, j * 128, mb * 64, 0);
            tma_load_3d(slot + 16384, &maps.x, fb, j * 128 + 64, mb * 64, 0);
          }
          acquire(32768);
          tma_load_3d(slot + 16384, &maps.wo, fb, 0, kt * 64, 2 * j);
          if (i == NPRE - 1) {
            wait_flag(flags + FO_O + 1, e1 * 8, dl);
            PROF(61, lane == 0);
            #pragma unroll 1
            for (int q = 0; q < NPRE - 1; q++) { tma_load_2d(sbase + ra.st * MSLOT, &maps.o, sbase + B_FM + 8 * ra.st, (8 + other_slot(q, j)) * 64, row0); ring_next(ra); }
          }
          if (i >= NPRE - 1) tma_load_2d(slot, &maps.o, fb, kt * 64, row0);
        }
      }
      #pragma unroll 1
      for (int t = 0; t < 2; t++) {
        acquire(32768);
        tma_load_2d(slot, &maps.w1, fb, j * 64, (2 * j + t) * 64);
        tma_load_2d(slot + 8192, &maps.w3, fb, j * 64, (2 * j + t) * 64);
        tma_load_2d(slot + 16384, &maps.w1, fb, (8 + j) * 64, (2 * j + t) * 64);
        tma_load_2d(slot + 24576, &maps.w3, fb, (8 + j) * 64, (2 * j + t) * 64);
      }
      {
        Ring ra = r;
        #pragma unroll 1
        for (int i = 0; i < 4; i++) {
          const int kt = 2 * ((~j & 4) + i);
          acquire(32768);
          tma_load_2d(slot + 16384, &maps.w1, fb, j * 64, kt * 64);
          tma_load_2d(slot + 24576, &maps.w3, fb, j * 64, kt * 64);
        }
        wait_flag(&g_flags[FL_H2], e1 * NCTA, dl);
        PROFN(62, lane == 0);
        #pragma unroll 1
        for (int i = 0; i < 4; i++) { tma_load_2d(sbase + ra.st * MSLOT, &maps.h2, sbase + B_FM + 8 * ra.st, ((~j & 4) + i) * 128, row0); ring_next(ra); }
      }
      #pragma unroll 1
      for (int gt = 0; gt < 7; gt++) {
        const int ncol = (8 * gt + j) * 64;
        #pragma unroll 1
        for (int i = (gt == 0 ? 4 : 0); i < (gt < 2 ? 14 : 16); i++) {
          const int kt = gt >= 2 ? i : i < 7 ? 2 * other_slot(i, j) : 2 * other_slot(i - 7, j) + 1;
          if (gt == 0 && i == 7) PRD_WAIT(sbase + B_FLG + 24, 0, dl);
          acquire(32768);
          tma_load_2d(slot + 16384, &maps.w1, fb, ncol, kt * 64);
          tma_load_2d(slot + 24576, &maps.w3, fb, ncol, kt * 64);
          tma_load_2d(slot, &maps.h2, fb, kt * 64, row0);
        }
      }
      #pragma unroll 1
      for (int kt = 0; kt < 56; kt++) {
        if ((kt & 7) == 0) PRD_WAIT(sbase + B_FLG + 32 + kt, 0, dl);
        acquire(32768);
        tma_load_3d(slot + 16384, &maps.w2, fb, 0, kt * 64, 2 * j);
        tma_load_3d(slot, &maps.hh, fb, (kt & 7) * 64, row0, kt >> 3);
      }
    } else {
      if (wid == 9) {
        SVC_WAIT(sbase + B_LN, 0, dl);
        red_add_e(&g_flags[FL_LN1], 1);
        SVC_WAIT(sbase + B_MOD, 0, dl);
        #pragma unroll 1
        for (int e = 0; e < 16; e++) st_rlx_v4(g_halo + (mb * 16 + j + (e & 8)) * 256 + (e & 7) * 32 + lane, ~0u, ~0u, ~0u, ~0u, true);
        #pragma unroll 1
        for (int e = 0; e < 2; e++) st_rlx_v4(g_st2 + ((mb * 8 + e * 4 + (lane >> 3)) * 8 + j) * 8 + (lane & 7), ~0u, ~0u, ~0u, ~0u, true);
        __threadfence();
        red_add_e(&g_flags[FL_RESET], 1);
        #pragma unroll 1
        for (int n = 0; n < 12; n++) {
          if (n == 4) {
            mbar_wait(sbase + B_STH, 0, dl);
            fence_proxy_async_smem();
            tma_store_2d(&maps.h2, sbase + SM_STG, j * 128, row0);
            bulk_commit();
            bulk_wait0();
            red_add_e(&g_flags[FL_H2], 1);
            PROF(84, lane == 0);
          }
          SVC_WAIT(sbase + B_STREQ, n & 1, dl);
          fence_proxy_async_smem();
          if (n == 2 || n == 3) tma_store_2d(&maps.o, sbase + SM_STG, (j + 8 * (n - 2)) * 64, row0);
          else if (n == 4) tma_store_2d(&maps.h2, sbase + SM_STG + 16384, j * 128 + 64, row0);
          else tma_store_3d(&maps.hh, sbase + SM_STG + (n == 1 ? 16384 : 0), j * 64, row0, n < 2 ? n : n - 5);
          bulk_commit();
          bulk_wait0();
          red_add_e(flags + (n < 2 ? FO_H1 + n : n - 1), 1);
          mbar_arrive_e(sbase + B_STFREE);
          PROFN(70 + n, lane == 0 && n > 0);
        }
      } else {
        SVC_WAIT(sbase + B_X + 8 * X_POLL, 0, dl);
        const float* const mail = &g_mod[(b & 7) * 6 * D_ + lane * 4];
        if (wid == 10) {
          #pragma unroll 1
          for (int p = 0; p < 8; p++) {
            if (p >= 2) SVC_WAIT(p == 2 ? sbase + B_MOD : q_empty(2 * p - 5, sbase), p == 2 ? 0 : ((2 * p - 5) >> 2) & 1, dl);
            gather_table(mail + p * 128, sbase + SM_MODT + (p & 3) * 512 + lane * 16, p == 0 ? sbase + B_MOD : sbase + B_FQ + 8 * ((2 * p - 1) & 3), par, dl);
            PROF(63 + p, lane == 0 && p < 7);
          }
          const uint32_t vdst = sbase + SM_VEC + (lane >> 3) * 64 + (lane & 3) * 16 + ((lane >> 2) & 1) * 8;
          #pragma unroll 1
          for (int v = 0; v < 2; v++) {
            SVC_WAIT(sbase + B_FLG + 16 + 16 * v, 0, dl);
            uint4 m[3];
            while (true) {
              #pragma unroll
              for (int e = 0; e < 3; e++) m[e] = ld_rlx_v4(mail + (2 + v + e) * 1024 + j * 128);
              if (poll_done(((bad4(m[0], par) | bad4(m[1], par) | bad4(m[2], par)) & 1) == 0, dl)) break;
              __nanosleep(200);
            }
            #pragma unroll
            for (int e = 0; e < 3; e++) sts64(vdst + (v + e) * 256, hi_halves(m[e].x, m[e].y), hi_halves(m[e].z, m[e].w));
            mbar_arrive_e(sbase + B_VEC + 8 * v);
            PROF(70, lane == 0 && v == 0);
          }
        } else {
          SVC_WAIT(sbase + B_LN, 0, dl);
          wait_flag(&g_flags[FL_LN1], e1 * NCTA, dl);
          mbar_arrive_e(sbase + B_MOD);
          PROF(41, lane == 0);
          SVC_WAIT(q_empty(3, sbase), 0, dl);
          wait_flag(&g_flags[FL_RESET], e1 * NCTA, dl);
          SVC_WAIT(q_empty(7, sbase), 1, dl);
          SVC_WAIT(q_empty(11, sbase), 0, dl);
          mbar_arrive_e(sbase + B_FQ + 24);
          #pragma unroll 1
          for (int i = 0; i < 11; i++) {
            const unsigned* f = flags + (i < 2 ? FO_H1 + i : i == 2 ? FO_O : FO_H2 + i - 3);
            if (i == 3) SVC_WAIT(sbase + B_STH, 0, dl);
            while (!poll_done((int)(ld_relaxed(f) - e1 * 8) >= 0, dl)) { if (i > 3) __nanosleep(200); }
            mbar_arrive_e(sbase + B_FLG + 8 * i);
          }
        }
      }
    }
  } else {
    PROFN(0, tid == 0);
    const int wg = wid >> 2, warp = wid & 3;
    const int g = lane >> 2, qd = lane & 3;
    bulk_prefetch(wmod + (size_t)(b * 8 + wid) * (6 * D_), PF_BYTES);
    bulk_prefetch(wmod + (size_t)(b * 8 + wid) * (6 * D_) + D_, PF_BYTES);
    bar_sync(0, 384);
    reg_alloc<232>();
    const uint32_t wgoff = wg * 8192;
    Frag4 frag;
    #pragma unroll
    for (int q = 0; q < 4; q++) frag.o[q] = wid * 2048 + (lane & 15) * 128 + (((2 * q + (lane >> 4)) ^ (lane & 7)) << 4);
    const uint32_t slab = sbase + SM_STG + wid * 2048;

    LnRow ln;
    {
      uint2* const lmail = &g_ln1[(mb * 8 + (lane & 1) * 4 + (j >> 1)) * 16 + (j & 1) * 8 + wid];
      st_rlx_v2(lmail, par ^ 1, par ^ 1, lane < 2);
      mbar_wait(sbase + B_X + 8 * wid, 0, dl);
      PROF(3, tid == 224);
      if (PF2_BYTES) {
        bulk_prefetch(wmod + (size_t)(b * 8 + wid) * (6 * D_) + PF_BYTES / 2, PF2_BYTES);
        bulk_prefetch(wmod + (size_t)(b * 8 + wid) * (6 * D_) + PF_BYTES / 2 + D_, PF2_BYTES);
      }
      float s[2][2] = {{0.f, 0.f}, {0.f, 0.f}}, q2[2][2] = {{0.f, 0.f}, {0.f, 0.f}};
      #pragma unroll
      for (int c = 0; c < 8; c++) {
        const uint4 v = lds128(sbase + SM_XR + wid * 4096 + c * 512 + lane * 16);
        const uint32_t vv[4] = {v.x, v.y, v.z, v.w};
        #pragma unroll
        for (int e = 0; e < 4; e++) {
          const float lo = bf_lo(vv[e]), hi = bf_hi(vv[e]);
          s[c >> 2][0] += lo; s[c >> 2][1] += hi; q2[c >> 2][0] = fmaf(lo, lo, q2[c >> 2][0]); q2[c >> 2][1] = fmaf(hi, hi, q2[c >> 2][1]);
        }
      }
      const bool odd = lane & 1;
      float sm = (s[0][0] + s[0][1]), so = (s[1][0] + s[1][1]), qm = (q2[0][0] + q2[0][1]), qo = (q2[1][0] + q2[1][1]);
      { const float a = odd ? so : sm, c = odd ? qo : qm;
        sm = a + __shfl_xor_sync(0xffffffffu, odd ? sm : so, 1); qm = c + __shfl_xor_sync(0xffffffffu, odd ? qm : qo, 1); }
      #pragma unroll
      for (int o = 2; o < 32; o <<= 1) { sm += __shfl_xor_sync(0xffffffffu, sm, o); qm += __shfl_xor_sync(0xffffffffu, qm, o); }
      sm *= (1.f / D_);
      st_rlx_v2(lmail, tagf(rsqrtf(fmaxf(qm * (1.f / D_) - sm * sm, 0.f) + 1e-5f), par), tagf(sm, par), lane < 2);
      mbar_arrive_e(sbase + B_LN);
      PROF(4, tid == 224);
      mbar_wait(sbase + B_LN, 0, dl);
      uint2 v0, v1;
      do { v0 = ld_rlx_v2(&g_ln1[(mb * 8 + wid) * 16 + g]); v1 = ld_rlx_v2(&g_ln1[(mb * 8 + wid) * 16 + 8 + g]); }
      while (!poll_done(((bad2(v0.x, v0.y, par) | bad2(v1.x, v1.y, par)) & 1) == 0, dl));
      ln_row(ln, 0, __uint_as_float(v0.y), __uint_as_float(v0.x));
      ln_row(ln, 1, __uint_as_float(v1.y), __uint_as_float(v1.x));
      PROF(5, tid == 0);
    }

    uint4* const halo_out = g_halo + ((mb * 16 + j) * 2 + wg) * 128 + lane;
    const uint4* const halo_in = halo_out - 16 * 256;
    const uint32_t xch = sbase + SM_XCH + wid * 2048 + lane * 16;
    const bool noprev = mb == 0 && warp == 0;
    float a0[64], a1[64];
    uint32_t x2[32];
    Ring r{mode >> 8, 0, 0, dl};
    Frag8 qA, qB, kA, kB, vA, vB, wA, wB;
    {
      float acc[128];
      uint32_t A0[16], A1[16];
      undef_regs(acc);
      const uint32_t tab = sbase + SM_MODT + qd * 16;
      uint4 p[4];
      q_wait(0, sbase, dl);
      mbar_wait(sbase + B_MOD, 0, dl);
      #pragma unroll
      for (int kk = 0; kk < 4; kk++) q_load(A0, p, kk, sbase + SM_X0, frag, tab);
      PROF(6, tid == 0);
      const int hq0 = (j & 1) ? 4 : j >> 1, hq1 = (j & 1) ? j >> 1 : 4;
      q_step_rs<true>(acc, A0, A1, p, 0, sbase, frag, tab, ln, hq0, true, dl, wg);
      #pragma unroll 1
      for (int u = 1; u < 15; u += 2) {
        q_step_rs<true>(acc, A1, A0, p, u, sbase, frag, tab, ln, hq1, false, dl, wg);
        mbar_arrive_if(sbase + B_STREQ, u == 7 && lane == 0);
        q_step_rs<true>(acc, A0, A1, p, u + 1, sbase, frag, tab, ln, hq0, false, dl, wg);
      }
      q_step_rs<false>(acc, A1, A0, p, 15, sbase, frag, tab, ln, hq1, false, dl, wg);
      mbar_wait(sbase + B_STFREE, 0, dl);
      mbar_arrive_e(sbase + B_STREQ);
      wgmma_wait<0>();
      undef_regs(a0);
      { const uint32_t slot = m_wait(sbase, r); mma_step(a0, slot + wgoff, slot + 16384, true, q_empty(15, sbase)); m_next(r); }
      fence_regs(acc);
      PROF(8, tid == 0);
      sched_fence();
      pack_half(kB, acc, 32, 1); pack_half(vB, acc, 64, 1); transpose8(vB);
      m_step(a0, sbase, wgoff, r);
      sched_fence();
      attn_send(kB, 0, xch - 16384, warp, halo_out, mb < 15); attn_send(vB, 1, xch - 16384, warp, halo_out, mb < 15);
      pack_half(qA, acc, 0, 0); pack_half(qB, acc, 0, 1); pack_half(kA, acc, 32, 0);
      m_step(a0, sbase, wgoff, r);
      sched_fence();
      pack_half(vA, acc, 64, 0); pack_half(wB, acc, 96, 1); pack_half(wA, acc, 96, 0); transpose8(vA);
    }
    uint4 wP[2];
    {
      m_step(a0, sbase, wgoff, r);
      uint4 pv[4];
      attn_recv<4>(pv, 0, xch - 16384, wg, warp, halo_in, mb > 0);
      m_step(a0, sbase, wgoff, r);
      mbar_wait(sbase + B_STFREE, 1, dl);
      transpose8(wB);
      m_step(a0, sbase, wgoff, r);
      attn_check<4>(pv, 0, warp, halo_in, dl);
      wgmma_wait<0>();
      PROF(9, tid == 0);
      float o[2][5][4];
      sched_fence();
      attn_core(qA, qB, kA, kB, vA, vB, pv, pv + 2, noprev, lane, o);
      if (ST0 == 0) { attn_store(o, 0, sbase, frag); attn_store(o, 1, sbase, frag); mbar_arrive_e(sbase + B_STREQ); }
      if (ST0 == 1) attn_store(o, 0, sbase, frag);
      sched_fence();
      bar_sync(NB_CONS, 256);
      PROF(10, tid == 0);
      m_step(a0, sbase, wgoff, r);
      sched_fence();
      if (ST0 == 2) attn_store(o, 0, sbase, frag);
      if (ST0 >= 1) { attn_store(o, 1, sbase, frag); mbar_arrive_e(sbase + B_STREQ); }
      m_step(a0, sbase, wgoff, r);
      sched_fence();
      attn_send(wB, 1, xch, warp, halo_out + 8 * 256, mb < 15);
      transpose8(wA);
      #pragma unroll 1
      for (int i = 8; i < 15; i++) m_step(a0, sbase, wgoff, r);
      attn_recv<2>(wP, 2, xch, wg, warp, halo_in + 8 * 256, mb > 0);
      m_step(a0, sbase, wgoff, r);
    }
    {
      undef_regs(a1);
      {
        const uint32_t slot = m_wait(sbase, r);
        mma_step(a1, slot + wgoff, slot + 16384, true, m_prev(sbase, r), [&] {
          fence_regs(a0);
          pack_half(kB, a0, 32, 1);
          attn_send(kB, 0, xch, warp, halo_out + 8 * 256, mb < 15);
        });
        m_next(r);
      }
      PROF(14, tid == 0);
      sched_fence();
      pack_half(kA, a0, 32, 0); pack_half(qA, a0, 0, 0); pack_half(qB, a0, 0, 1);
      m_step(a1, sbase, wgoff, r);
      attn_check<2>(wP, 2, warp, halo_in + 8 * 256, dl);
      uint4 kP[2];
      attn_recv<2>(kP, 0, xch, wg, warp, halo_in + 8 * 256, mb > 0);
      m_step(a1, sbase, wgoff, r);
      attn_check<2>(kP, 0, warp, halo_in + 8 * 256, dl);
      wgmma_wait<0>();
      PROF(15, tid == 0);
      float o[2][5][4];
      mbar_wait(sbase + B_STFREE, 0, dl);
      attn_core(qA, qB, kA, kB, wA, wB, kP, wP, noprev, lane, o);
      attn_store(o, 0, sbase, frag);
      attn_store(o, 1, sbase, frag);
      mbar_arrive_e(sbase + B_STREQ);
      fence_proxy_async_smem();
      bar_sync(NB_CONS, 256);
      PROF(16, tid == 0);
      #pragma unroll 1
      for (int i = 3; i < 8; i++) m_step(a1, sbase, wgoff, r);
      mma_step(a1, sbase + SM_STG + wgoff, m_wait(sbase, r) + 16384, false, m_prev(sbase, r));
      m_next(r);
      PROF(17, tid == 0);
      #pragma unroll 1
      for (int i = 0; i < 4; i++) { m_step(a1, sbase, wgoff, r); PROF(42, tid == 0 && i == 0); }
      PROF(43, tid == 0);
      const uint32_t xs = m_wait(sbase, r), xe = sbase + B_EM + 8 * r.st;
      PROF(44, tid == 0);
      ring_next(r);
      #pragma unroll
      for (int t = 0; t < 2; t++) {
        #pragma unroll
        for (int jj = 4 * t; jj < 4 * t + 4; jj++) ldmatrix_x4(xs + t * 16384 + frag.o[jj & 3], x2[4 * jj], x2[4 * jj + 1], x2[4 * jj + 2], x2[4 * jj + 3]);
        if (t == 1) mbar_arrive_e(xe);
        m_step(a1, sbase, wgoff, r);
      }
      m_step(a1, sbase, wgoff, r);
      PROF(45, tid == 0);
      mbar_wait(sbase + B_VEC, 0, dl);
      mbar_wait(sbase + B_STFREE, 1, dl);
      const uint32_t vec = sbase + SM_VEC + qd * 16;
      uint4 ga[4];
      #pragma unroll
      for (int q = 0; q < 4; q++) ga[q] = lds128(vec + q * 64);
      wgmma_wait<0>();
      mbar_arrive_e(m_prev(sbase, r));
      fence_regs(a1);
      PROF(18, tid == 0);
      float rs_[4] = {0.f, 0.f, 0.f, 0.f}, gl[4] = {0.f, 0.f, 0.f, 0.f}, gh[4] = {0.f, 0.f, 0.f, 0.f};
      #pragma unroll
      for (int jj = 0; jj < 8; jj++) {
        uint32_t* v = &x2[4 * jj];
        const uint32_t wl = (jj & 1) ? ga[jj >> 1].z : ga[jj >> 1].x, wh = (jj & 1) ? ga[jj >> 1].w : ga[jj >> 1].y;
        #pragma unroll
        for (int e = 0; e < 4; e++) v[e] = fma_bf2(e & 2 ? wh : wl, pack_bf16(a1[8 * jj + 2 * e], a1[8 * jj + 2 * e + 1]), v[e]);
        mma16(rs_, v[0], v[1], v[2], v[3], 0x3F803F80u, 0x3F803F80u);
        mma16(gl, v[0], v[1], v[2], v[3], v[0], v[2]);
        mma16(gh, v[0], v[1], v[2], v[3], v[1], v[3]);
      }
      uint4* const sm = g_st2 + (mb * 8 + wid) * 64 + g;
      st_rlx_v4(sm + j * 8, __float_as_uint(rs_[0]), __float_as_uint(g & 1 ? gl[1] : gl[0]), __float_as_uint(rs_[2]), __float_as_uint(g & 1 ? gh[3] : gh[2]),
                qd == (g >> 1));
      float s[2], q2[2];
      PROF(19, tid == 0);
      uint4 sb[4], cb[4];
      #pragma unroll
      for (int q = 0; q < 4; q++) { sb[q] = lds128(vec + 256 + q * 64); cb[q] = lds128(vec + 512 + q * 64); }
      uint4 p0, p1;
      while (true) {
        p0 = ld_rlx_v4(sm + qd * 16); p1 = ld_rlx_v4(sm + qd * 16 + 8);
        if (poll_done(max(max(max(p0.x, p0.y), max(p0.z, p0.w)), max(max(p1.x, p1.y), max(p1.z, p1.w))) != ~0u, dl)) break;
      }
      PROF(20, tid == 0);
      s[0] = __uint_as_float(p0.x) + __uint_as_float(p1.x); q2[0] = __uint_as_float(p0.y) + __uint_as_float(p1.y);
      s[1] = __uint_as_float(p0.z) + __uint_as_float(p1.z); q2[1] = __uint_as_float(p0.w) + __uint_as_float(p1.w);
      #pragma unroll
      for (int o2 = 1; o2 <= 2; o2 <<= 1)
        #pragma unroll
        for (int h = 0; h < 2; h++) { s[h] += __shfl_xor_sync(0xffffffffu, s[h], o2); q2[h] += __shfl_xor_sync(0xffffffffu, q2[h], o2); }
      #pragma unroll
      for (int h = 0; h < 2; h++) {
        const float m = s[h] * (1.f / D_);
        ln_row(ln, h, m, rsqrtf(fmaxf(q2[h] * (1.f / D_) - m * m, 0.f) + 1e-5f));
      }
      #pragma unroll
      for (int jj = 0; jj < 8; jj++) {
        const uint32_t cl = (jj & 1) ? cb[jj >> 1].z : cb[jj >> 1].x, ch = (jj & 1) ? cb[jj >> 1].w : cb[jj >> 1].y;
        const uint32_t sl = (jj & 1) ? sb[jj >> 1].z : sb[jj >> 1].x, sh = (jj & 1) ? sb[jj >> 1].w : sb[jj >> 1].y;
        stmatrix_x4(sbase + SM_STG + (jj >> 2) * 16384 + frag.o[jj & 3], ln_mod(x2[4 * jj], ln, 0, cl, sl), ln_mod(x2[4 * jj + 1], ln, 1, cl, sl),
                    ln_mod(x2[4 * jj + 2], ln, 0, ch, sh), ln_mod(x2[4 * jj + 3], ln, 1, ch, sh));
        if (jj == 3) mbar_arrive_e(sbase + B_STH);
      }
      mbar_arrive_e(sbase + B_STREQ);
      fence_proxy_async_smem();
      bar_sync(NB_WG + wg, 128);
      PROF(21, tid == 0);
    }

    undef_regs(a0);
    #pragma unroll
    for (int t = 0; t < 2; t++) {
      const uint32_t slot = m_wait(sbase, r);
      mma_step(a0, sbase + SM_STG + t * 16384 + wgoff, slot, t == 0, t == 0 ? 0 : m_prev(sbase, r));
      mma_step(a1, sbase + SM_STG + t * 16384 + wgoff, slot + 16384, t == 0, 0);
      m_next(r);
    }
    PROF(22, tid == 0);
    #pragma unroll 1
    for (int t = 0; t < 7; t += 2) {
      g_switch(a1, a0, t == 0 ? 14 : 11, t > 0, 5 + t, sbase, wgoff, frag, r);
      if (t == 6) break;
      g_switch(a0, a1, t == 0 ? 9 : 11, true, 6 + t, sbase, wgoff, frag, r);
    }
    #pragma unroll 1
    for (int i = 5; i < 56; i++) m_step(a1, sbase, wgoff, r);
    {
      mbar_wait(sbase + B_STFREE, 1, dl);
      mbar_wait(sbase + B_VEC + 8, 0, dl);
      uint4 gb[4];
      #pragma unroll
      for (int q = 0; q < 4; q++) gb[q] = lds128(sbase + SM_VEC + 768 + qd * 16 + q * 64);
      wgmma_wait<0>();
      fence_regs(a1);
      PROF(50, tid == 0);
      #pragma unroll
      for (int t = 0; t < 2; t++) {
        #pragma unroll
        for (int jj = 4 * t; jj < 4 * t + 4; jj++) {
          const uint32_t gl = (jj & 1) ? gb[jj >> 1].z : gb[jj >> 1].x, gh = (jj & 1) ? gb[jj >> 1].w : gb[jj >> 1].y;
          const int i = 8 * jj;
          stmatrix_x4(sbase + SM_STG + t * 16384 + frag.o[jj & 3],
                      fma_bf2(gl, pack_bf16(a1[i], a1[i + 1]), x2[4 * jj]), fma_bf2(gl, pack_bf16(a1[i + 2], a1[i + 3]), x2[4 * jj + 1]),
                      fma_bf2(gh, pack_bf16(a1[i + 4], a1[i + 5]), x2[4 * jj + 2]), fma_bf2(gh, pack_bf16(a1[i + 6], a1[i + 7]), x2[4 * jj + 3]));
        }
        fence_proxy_async_smem();
        tma_store_3d(&maps.out, slab + t * 16384, j * 128 + t * 64, mb * 64 + warp * 16, wg);
      }
      bulk_commit();
      st_rlx(tid == 0 ? flags + FO_EPOCH : &g_flags[FL_EPOCH], e1, j == 0 && (tid == 0 || (tid == 1 && mb == 0)));
      bulk_wait_read0();
      PROFN(51, tid == 0);
    }
  }
}

typedef CUresult (*PFN_encodeTiled)(CUtensorMap*, CUtensorMapDataType, cuuint32_t, void*, const cuuint64_t*, const cuuint64_t*,
                                    const cuuint32_t*, const cuuint32_t*, CUtensorMapInterleave, CUtensorMapSwizzle,
                                    CUtensorMapL2promotion, CUtensorMapFloatOOBfill);

void encode(PFN_encodeTiled fn, CUtensorMap* m, const void* ptr, int rank, const cuuint64_t* dims, const cuuint64_t* strides,
            const cuuint32_t* box) {
  const cuuint32_t es[5] = {1, 1, 1, 1, 1};
  fn(m, CU_TENSOR_MAP_DATA_TYPE_BFLOAT16, rank, const_cast<void*>(ptr), dims, strides, box, es, CU_TENSOR_MAP_INTERLEAVE_NONE,
     CU_TENSOR_MAP_SWIZZLE_128B, CU_TENSOR_MAP_L2_PROMOTION_L2_256B, CU_TENSOR_MAP_FLOAT_OOB_FILL_NONE);
}
void map2d(PFN_encodeTiled fn, CUtensorMap* m, const void* ptr, int cols, int rows, int boxrows) {
  const cuuint64_t dims[2] = {(cuuint64_t)cols, (cuuint64_t)rows}, strides[1] = {(cuuint64_t)cols * 2};
  const cuuint32_t box[2] = {64, (cuuint32_t)boxrows};
  encode(fn, m, ptr, 2, dims, strides, box);
}
void map_w2chunk(PFN_encodeTiled fn, CUtensorMap* m, const void* ptr, int cols, int rows) {
  const cuuint64_t dims[3] = {64, (cuuint64_t)rows, (cuuint64_t)cols / 64}, strides[2] = {(cuuint64_t)cols * 2, 128};
  const cuuint32_t box[3] = {64, 64, 2};
  encode(fn, m, ptr, 3, dims, strides, box);
}
void map_parity(PFN_encodeTiled fn, CUtensorMap* m, const void* ptr, int boxpairs, int boxpar) {
  const cuuint64_t dims[3] = {D_, S_ / 2, 2}, strides[2] = {D_ * 4, D_ * 2};
  const cuuint32_t box[3] = {64, (cuuint32_t)boxpairs, (cuuint32_t)boxpar};
  encode(fn, m, ptr, 3, dims, strides, box);
}

}

extern "C" void kernel_launch(void* const* d_in, const int* in_sizes, int n_in, void* d_out, int out_size) {
  (void)in_sizes; (void)n_in; (void)out_size;
  const bf16* x = (const bf16*)d_in[0];
  const bf16* wqkv = (const bf16*)d_in[1];
  const bf16* wo = (const bf16*)d_in[2];
  const bf16* w1 = (const bf16*)d_in[4];
  const bf16* w3 = (const bf16*)d_in[5];
  const bf16* w2 = (const bf16*)d_in[6];
  const bf16* cvec = (const bf16*)d_in[7];
  const bf16* w_mod = (const bf16*)d_in[8];

  static PFN_encodeTiled fn = nullptr;
  static Maps maps;
  static const void* cached[8] = {};
  static int sms = 0;
  if (!fn) {
    void* p = nullptr; cudaDriverEntryPointQueryResult st;
    cudaGetDriverEntryPoint("cuTensorMapEncodeTiled", &p, cudaEnableDefault, &st);
    fn = (PFN_encodeTiled)p;
    cudaFuncSetAttribute(fused_block_kernel, cudaFuncAttributeMaxDynamicSharedMemorySize, SM_TOTAL);
    int dev = 0;
    cudaGetDevice(&dev);
    cudaDeviceGetAttribute(&sms, cudaDevAttrMultiProcessorCount, dev);
  }
  const void* cur[8] = {x, wqkv, wo, w1, w3, w2, d_out, w_mod};
  bool same = true;
  for (int i = 0; i < 8; i++) same = same && cached[i] == cur[i];
  if (!same) {
    void *o, *h2, *hh;
    cudaGetSymbolAddress(&hh, g_hh); cudaGetSymbolAddress(&o, g_o);
    h2 = o;
    map_parity(fn, &maps.x, x, 64, 2); map_parity(fn, &maps.out, d_out, 16, 1);
    map2d(fn, &maps.o, o, D_, S_, 128); map2d(fn, &maps.h2, h2, D_, S_, 128);
    {
      const cuuint64_t dims[3] = {512, (cuuint64_t)S_, 7}, strides[2] = {1024, (cuuint64_t)S_ * 1024};
      const cuuint32_t box[3] = {64, 128, 1};
      encode(fn, &maps.hh, hh, 3, dims, strides, box);
    }
    {
      const cuuint64_t dims[4] = {64, 1024, 16, 2}, strides[3] = {3072 * 2, 128, 2048};
      const cuuint64_t dimv[4] = {64, 1024, 8, 2}, stridev[3] = {3072 * 2, 128, 1024};
      const cuuint32_t box[4] = {64, 64, 1, 2};
      encode(fn, &maps.wqk, wqkv, 4, dims, strides, box);
      encode(fn, &maps.wvv, wqkv + 2048, 4, dimv, stridev, box);
      const cuuint64_t dim1[4] = {1024, 128, 8, 2}, stride1[3] = {3072 * 2, 128 * 3072 * 2, 2048};
      const cuuint32_t box1[4] = {64, 16, 4, 2};
      encode(fn, &maps.wq1, wqkv, 4, dim1, stride1, box1);
    }
    map_w2chunk(fn, &maps.wo, wo, D_, D_); map_w2chunk(fn, &maps.w2, w2, D_, F_);
    map2d(fn, &maps.w1, w1, F_, D_, 64); map2d(fn, &maps.w3, w3, F_, D_, 64);
    map2d(fn, &maps.wmod, w_mod, 6 * D_, D_, 256);
    for (int i = 0; i < 8; i++) cached[i] = cur[i];
  }
  if (sms >= NCTA + NAUX) {
    fused_block_kernel<<<NCTA + NAUX, 384, SM_TOTAL>>>(maps, x, cvec, w_mod, 0);
  } else {
    fused_block_kernel<<<NAUX, 384, SM_TOTAL>>>(maps, x, cvec, w_mod, 1);
    fused_block_kernel<<<NCTA, 384, SM_TOTAL>>>(maps, x, cvec, w_mod, 2);
  }
}
```

```cpp
#include <cuda.h>
#include <cuda_runtime.h>
#include <cuda_bf16.h>
#include <stdint.h>

namespace {

typedef __nv_bfloat16 bf16;

constexpr int S_ = 2048, D_ = 1024, F_ = 3584;
constexpr int NCTA = 128, NAUX = 4;

__device__ __align__(1024) bf16 g_o[S_ * D_];
__device__ __align__(1024) bf16 g_hh[S_ * F_];
__device__ __align__(1024) float g_mod[8 * 6 * D_];
__device__ __align__(1024) uint2 g_ln1[16 * 8 * 16];
__device__ __align__(1024) uint4 g_halo[16 * 16 * 2 * 4 * 32];
__device__ __align__(1024) uint4 g_st2[16 * 8 * 8 * 8];
constexpr int FO_EPOCH = 0, FO_O = 1, FO_H2 = 3, FO_H1 = 11, FL_EPOCH = 16 * 32, FL_RESET = FL_EPOCH + 1, FL_LN1 = FL_EPOCH + 2, FL_H2 = FL_EPOCH + 3, FL_O = FL_EPOCH + 4;
__device__ __align__(1024) unsigned g_flags[17 * 32];

#define AUXPOS 16
#define SMMAP 1
__device__ __forceinline__ int cta_role(int mode) {
  const int b = blockIdx.x;
  if (mode) return mode == 1 ? NCTA + b : b;
  uint32_t sm, nsm;
  asm("mov.u32 %0, %%smid;" : "=r"(sm)); asm("mov.u32 %0, %%nsmid;" : "=r"(nsm));
  if (!SMMAP || nsm != NCTA + NAUX) return b % 33 == AUXPOS ? NCTA + b / 33 : b - (b + 32 - AUXPOS) / 33;
  const int t = sm >> 1;
  int r;
  if (t < 32) r = (t & 7) * 16 + (t >> 3) * 2 + (sm & 1);
  else if (t < 60) r = (1 + (t - 32) % 7) * 16 + 8 + ((t - 32) / 7) * 2 + (sm & 1);
  else if (t < 62) r = NCTA + sm - 120;
  else r = sm - 116;
  return r;
}
#define PROF(slot, on) do {} while (0)
#define PROFN(slot, on) do {} while (0)
#define PROFW_DECL do {} while (0)
#define PROFW(stmt) do {} while (0)
#define PROFW_OUT(slot, on) do {} while (0)

__device__ __forceinline__ uint32_t smem_u32(const void* p) { return (uint32_t)__cvta_generic_to_shared(p); }
__device__ __forceinline__ void mbar_init(uint32_t bar, uint32_t count) {
  asm volatile("mbarrier.init.shared::cta.b64 [%0], %1;" :: "r"(bar), "r"(count));
}
#define ELECT "{\n.reg .pred p;\nelect.sync _|p, 0xffffffff;\n@p "
__device__ __forceinline__ void mbar_expect_tx_e(uint32_t bar, uint32_t bytes) {
  asm volatile(ELECT "mbarrier.arrive.expect_tx.shared::cta.b64 _, [%0], %1;\n}" :: "r"(bar), "r"(bytes) : "memory");
}
__device__ __forceinline__ void mbar_arrive_if(uint32_t bar, bool on) {
  asm volatile("{\n.reg .pred p;\nsetp.ne.b32 p, %1, 0;\n@p mbarrier.arrive.shared::cta.b64 _, [%0];\n}" :: "r"(bar), "r"((int)on) : "memory");
}
__device__ __forceinline__ void mbar_arrive_e(uint32_t bar) {
  asm volatile(ELECT "mbarrier.arrive.shared::cta.b64 _, [%0];\n}" :: "r"(bar) : "memory");
}
__device__ __forceinline__ uint32_t clock32() { uint32_t t; asm volatile("mov.u32 %0, %%clock;" : "=r"(t)); return t; }
__device__ __forceinline__ void mbar_wait(uint32_t bar, uint32_t parity, uint32_t dl) {
  asm volatile("{\n.reg .pred p, q;\n.reg .b32 t;\n"
               "mbarrier.try_wait.parity.shared::cta.b64 p, [%0], %1;\n"
               "@p bra LAB_DONE;\n"
               "LAB_WAIT:\n"
               "mbarrier.try_wait.parity.shared::cta.b64 p, [%0], %1;\n"
               "mov.u32 t, %%clock;\n"
               "sub.s32 t, t, %2;\n"
               "setp.lt.and.s32 q, t, 0, !p;\n"
               "@q bra LAB_WAIT;\n"
               "LAB_DONE:\n}" :: "r"(bar), "r"(parity), "r"(dl) : "memory");
}
__device__ __forceinline__ void mbar_sleep(uint32_t bar, uint32_t parity, uint32_t dl) {
  asm volatile("{\n.reg .pred p;\n.reg .b32 t;\n"
               "LAB_WAIT:\n"
               "mbarrier.try_wait.parity.shared::cta.b64 p, [%0], %1, 20000;\n"
               "@p bra LAB_DONE;\n"
               "mov.u32 t, %%clock;\n"
               "sub.s32 t, t, %2;\n"
               "setp.lt.s32 p, t, 0;\n"
               "@p bra LAB_WAIT;\n"
               "LAB_DONE:\n}" :: "r"(bar), "r"(parity), "r"(dl) : "memory");
}
__device__ __forceinline__ bool poll_done(bool ok, uint32_t dl) {
  return __all_sync(0xffffffffu, ok || (int)(clock32() - dl) >= 0);
}
__device__ __forceinline__ unsigned ld_relaxed(const unsigned* p) {
  unsigned v; asm volatile("ld.relaxed.gpu.global.u32 %0, [%1];" : "=r"(v) : "l"(p) : "memory"); return v;
}
__device__ __forceinline__ void red_add_e(unsigned* p, unsigned v) {
  asm volatile(ELECT "red.relaxed.gpu.global.add.u32 [%0], %1;\n}" :: "l"(p), "r"(v) : "memory");
}
__device__ __forceinline__ void wait_flag(const unsigned* p, unsigned target, uint32_t dl) {
  asm volatile("{\n.reg .pred p;\n.reg .b32 t;\n"
               "LAB_WAIT:\n"
               "ld.relaxed.gpu.global.u32 t, [%0];\n"
               "sub.s32 t, t, %1;\n"
               "setp.ge.s32 p, t, 0;\n"
               "@p bra LAB_DONE;\n"
               "mov.u32 t, %%clock;\n"
               "sub.s32 t, t, %2;\n"
               "setp.lt.s32 p, t, 0;\n"
               "@p bra LAB_WAIT;\n"
               "LAB_DONE:\n}" :: "l"(p), "r"(target), "r"(dl) : "memory");
}
__device__ __forceinline__ void wait_until(uint32_t t) { while ((int)(clock32() - t) < 0) {} }
__device__ __forceinline__ void fence_proxy_async_smem() { asm volatile("fence.proxy.async.shared::cta;" ::: "memory"); }

constexpr uint64_t EVICT_FIRST = 0x12F0000000000000ull;
template <bool STREAM = false>
__device__ __forceinline__ void tma_load_2d(uint32_t dst, const CUtensorMap* m, uint32_t bar, int c0, int c1) {
  if (STREAM)
    asm volatile(ELECT "cp.async.bulk.tensor.2d.shared::cluster.global.mbarrier::complete_tx::bytes.L2::cache_hint [%0], [%1, {%3, %4}], [%2], %5;\n}"
                 :: "r"(dst), "l"(m), "r"(bar), "r"(c0), "r"(c1), "l"(EVICT_FIRST) : "memory");
  else
    asm volatile(ELECT "cp.async.bulk.tensor.2d.shared::cluster.global.mbarrier::complete_tx::bytes [%0], [%1, {%3, %4}], [%2];\n}"
                 :: "r"(dst), "l"(m), "r"(bar), "r"(c0), "r"(c1) : "memory");
}
template <bool STREAM = false>
__device__ __forceinline__ void tma_load_3d(uint32_t dst, const CUtensorMap* m, uint32_t bar, int c0, int c1, int c2) {
  if (STREAM)
    asm volatile(ELECT "cp.async.bulk.tensor.3d.shared::cluster.global.mbarrier::complete_tx::bytes.L2::cache_hint [%0], [%1, {%3, %4, %5}], [%2], %6;\n}"
                 :: "r"(dst), "l"(m), "r"(bar), "r"(c0), "r"(c1), "r"(c2), "l"(EVICT_FIRST) : "memory");
  else
    asm volatile(ELECT "cp.async.bulk.tensor.3d.shared::cluster.global.mbarrier::complete_tx::bytes [%0], [%1, {%3, %4, %5}], [%2];\n}"
                 :: "r"(dst), "l"(m), "r"(bar), "r"(c0), "r"(c1), "r"(c2) : "memory");
}
template <bool STREAM = false>
__device__ __forceinline__ void tma_load_4d(uint32_t dst, const CUtensorMap* m, uint32_t bar, int c0, int c1, int c2, int c3) {
  if (STREAM)
    asm volatile(ELECT "cp.async.bulk.tensor.4d.shared::cluster.global.mbarrier::complete_tx::bytes.L2::cache_hint [%0], [%1, {%3, %4, %5, %6}], [%2], %7;\n}"
                 :: "r"(dst), "l"(m), "r"(bar), "r"(c0), "r"(c1), "r"(c2), "r"(c3), "l"(EVICT_FIRST) : "memory");
  else
    asm volatile(ELECT "cp.async.bulk.tensor.4d.shared::cluster.global.mbarrier::complete_tx::bytes [%0], [%1, {%3, %4, %5, %6}], [%2];\n}"
                 :: "r"(dst), "l"(m), "r"(bar), "r"(c0), "r"(c1), "r"(c2), "r"(c3) : "memory");
}
__device__ __forceinline__ void tma_store_2d(const CUtensorMap* m, uint32_t src, int c0, int c1) {
  asm volatile(ELECT "cp.async.bulk.tensor.2d.global.shared::cta.bulk_group [%0, {%2, %3}], [%1];\n}"
               :: "l"(m), "r"(src), "r"(c0), "r"(c1) : "memory");
}
__device__ __forceinline__ void tma_store_3d(const CUtensorMap* m, uint32_t src, int c0, int c1, int c2) {
  asm volatile(ELECT "cp.async.bulk.tensor.3d.global.shared::cta.bulk_group [%0, {%2, %3, %4}], [%1];\n}"
               :: "l"(m), "r"(src), "r"(c0), "r"(c1), "r"(c2) : "memory");
}
__device__ __forceinline__ void bulk_load(uint32_t dst, const void* src, uint32_t bytes, uint32_t bar) {
  asm volatile(ELECT "cp.async.bulk.shared::cluster.global.mbarrier::complete_tx::bytes [%0], [%1], %2, [%3];\n}"
               :: "r"(dst), "l"(src), "r"(bytes), "r"(bar) : "memory");
}
__device__ __forceinline__ void bulk_prefetch(const void* src, uint32_t bytes) {
  asm volatile(ELECT "cp.async.bulk.prefetch.L2.global [%0], %1;\n}" :: "l"(src), "r"(bytes) : "memory");
}
__device__ __forceinline__ void bulk_commit() { asm volatile("cp.async.bulk.commit_group;" ::: "memory"); }
__device__ __forceinline__ void bulk_wait0() { asm volatile("cp.async.bulk.wait_group 0;" ::: "memory"); }
__device__ __forceinline__ void bulk_wait_read0() { asm volatile("cp.async.bulk.wait_group.read 0;" ::: "memory"); }
__device__ __forceinline__ void prefetch_tmap(const CUtensorMap* m) { asm volatile("prefetch.tensormap [%0];" :: "l"(m) : "memory"); }
__device__ __forceinline__ void wgmma_fence() { asm volatile("wgmma.fence.sync.aligned;" ::: "memory"); }
__device__ __forceinline__ void wgmma_commit() { asm volatile("wgmma.commit_group.sync.aligned;" ::: "memory"); }
template <int N> __device__ __forceinline__ void wgmma_wait() { asm volatile("wgmma.wait_group.sync.aligned %0;" :: "n"(N) : "memory"); }
template <int R> __device__ __forceinline__ void reg_alloc() { asm volatile("setmaxnreg.inc.sync.aligned.u32 %0;" :: "n"(R)); }
template <int R> __device__ __forceinline__ void reg_dealloc() { asm volatile("setmaxnreg.dec.sync.aligned.u32 %0;" :: "n"(R)); }
__device__ __forceinline__ void bar_sync(int id, int n) { asm volatile("bar.sync %0, %1;" :: "r"(id), "r"(n) : "memory"); }
__device__ __forceinline__ void bar_arrive(int id, int n) { asm volatile("bar.arrive %0, %1;" :: "r"(id), "r"(n) : "memory"); }
__device__ __forceinline__ void sched_fence() {
  asm volatile("{\n.reg .pred p;\n.reg .b32 t;\nLAB_F:\nmov.u32 t, %%clock;\nsetp.eq.u32 p, t, %0;\n@p bra LAB_F;\n}" :: "n"(0) : "memory");
}
template <int N> __device__ __forceinline__ void fence_regs(float (&a)[N]) {
  #pragma unroll
  for (int i = 0; i < N; i++) asm volatile("" : "+f"(a[i]) :: "memory");
}
template <int N> __device__ __forceinline__ void undef_regs(float (&a)[N]) {
  #pragma unroll
  for (int i = 0; i < N; i++) asm volatile("" : "=f"(a[i]));
}

__device__ __forceinline__ uint64_t desc_from_lo(uint32_t lo) { return (uint64_t)lo | ((uint64_t)0x40000040u << 32); }
__device__ __forceinline__ uint32_t pack_bf16(float lo, float hi) {
  uint32_t r; asm("cvt.rn.bf16x2.f32 %0, %1, %2;" : "=r"(r) : "f"(hi), "f"(lo)); return r;
}
__device__ __forceinline__ uint32_t fma_bf2(uint32_t a, uint32_t b, uint32_t c) {
  uint32_t d; asm("fma.rn.bf16x2 %0, %1, %2, %3;" : "=r"(d) : "r"(a), "r"(b), "r"(c)); return d;
}
__device__ __forceinline__ float bf_lo(uint32_t v) { return __uint_as_float(v << 16); }
__device__ __forceinline__ float bf_hi(uint32_t v) { return __uint_as_float(v & 0xFFFF0000u); }
__device__ __forceinline__ float bf16_round(float x) { return bf_lo(pack_bf16(x, 0.f)); }
__device__ __forceinline__ void stmatrix_x4(uint32_t addr, uint32_t r0, uint32_t r1, uint32_t r2, uint32_t r3) {
  asm volatile("stmatrix.sync.aligned.m8n8.x4.shared.b16 [%0], {%1, %2, %3, %4};" :: "r"(addr), "r"(r0), "r"(r1), "r"(r2), "r"(r3) : "memory");
}
__device__ __forceinline__ void stmatrix_x4_if(uint32_t addr, uint32_t r0, uint32_t r1, uint32_t r2, uint32_t r3, bool on) {
  asm volatile("{\n.reg .pred p;\nsetp.ne.b32 p, %5, 0;\n@p stmatrix.sync.aligned.m8n8.x4.shared.b16 [%0], {%1, %2, %3, %4};\n}"
               :: "r"(addr), "r"(r0), "r"(r1), "r"(r2), "r"(r3), "r"((int)on) : "memory");
}
__device__ __forceinline__ void ldmatrix_x4(uint32_t addr, uint32_t& r0, uint32_t& r1, uint32_t& r2, uint32_t& r3) {
  asm volatile("ldmatrix.sync.aligned.m8n8.x4.shared.b16 {%0, %1, %2, %3}, [%4];" : "=r"(r0), "=r"(r1), "=r"(r2), "=r"(r3) : "r"(addr) : "memory");
}
__device__ __forceinline__ void ldmatrix_x4_t(uint32_t addr, uint32_t (&r)[4]) {
  asm volatile("ldmatrix.sync.aligned.m8n8.x4.trans.shared.b16 {%0, %1, %2, %3}, [%4];" : "=r"(r[0]), "=r"(r[1]), "=r"(r[2]), "=r"(r[3]) : "r"(addr) : "memory");
}
__device__ __forceinline__ uint32_t tagf(float v, unsigned par) { return (__float_as_uint(v) & ~1u) | par; }
__device__ __forceinline__ void st_rlx(void* p, uint32_t a, bool on) {
  asm volatile("{\n.reg .pred p;\nsetp.ne.b32 p, %2, 0;\n@p st.relaxed.gpu.global.u32 [%0], %1;\n}" :: "l"(p), "r"(a), "r"((int)on) : "memory");
}
__device__ __forceinline__ void st_rlx_v2(void* p, uint32_t a, uint32_t b, bool on) {
  asm volatile("{\n.reg .pred p;\nsetp.ne.b32 p, %3, 0;\n@p st.relaxed.gpu.global.v2.u32 [%0], {%1, %2};\n}" :: "l"(p), "r"(a), "r"(b), "r"((int)on) : "memory");
}
__device__ __forceinline__ uint2 ld_rlx_v2(const void* p) {
  uint2 v; asm volatile("ld.relaxed.gpu.global.v2.u32 {%0,%1}, [%2];" : "=r"(v.x), "=r"(v.y) : "l"(p) : "memory"); return v;
}
__device__ __forceinline__ void st_rlx_v4(void* p, uint32_t a, uint32_t b, uint32_t c, uint32_t d, bool on) {
  asm volatile("{\n.reg .pred p;\nsetp.ne.b32 p, %5, 0;\n@p st.relaxed.gpu.global.v4.u32 [%0], {%1, %2, %3, %4};\n}"
               :: "l"(p), "r"(a), "r"(b), "r"(c), "r"(d), "r"((int)on) : "memory");
}
__device__ __forceinline__ uint4 ld_rlx_v4(const void* p) {
  uint4 v; asm volatile("ld.relaxed.gpu.global.v4.u32 {%0,%1,%2,%3}, [%4];" : "=r"(v.x), "=r"(v.y), "=r"(v.z), "=r"(v.w) : "l"(p) : "memory"); return v;
}
__device__ __forceinline__ uint32_t movmatrix_t(uint32_t a) {
  uint32_t d; asm volatile("movmatrix.sync.aligned.m8n8.trans.b16 %0, %1;" : "=r"(d) : "r"(a)); return d;
}
__device__ __forceinline__ void mma16(float (&c)[4], uint32_t a0, uint32_t a1, uint32_t a2, uint32_t a3, uint32_t b0, uint32_t b1) {
  asm volatile("mma.sync.aligned.m16n8k16.row.col.f32.bf16.bf16.f32 {%0,%1,%2,%3}, {%4,%5,%6,%7}, {%8,%9}, {%0,%1,%2,%3};"
               : "+f"(c[0]), "+f"(c[1]), "+f"(c[2]), "+f"(c[3]) : "r"(a0), "r"(a1), "r"(a2), "r"(a3), "r"(b0), "r"(b1));
}
__device__ __forceinline__ void mma8(float (&c)[4], uint32_t a0, uint32_t a1, uint32_t b0) {
  asm volatile("mma.sync.aligned.m16n8k8.row.col.f32.bf16.bf16.f32 {%0,%1,%2,%3}, {%4,%5}, {%6}, {%0,%1,%2,%3};"
               : "+f"(c[0]), "+f"(c[1]), "+f"(c[2]), "+f"(c[3]) : "r"(a0), "r"(a1), "r"(b0));
}
__device__ __forceinline__ void sts128(uint32_t addr, uint32_t a, uint32_t b, uint32_t c, uint32_t d) {
  asm volatile("st.shared.v4.b32 [%0], {%1,%2,%3,%4};" :: "r"(addr), "r"(a), "r"(b), "r"(c), "r"(d) : "memory");
}
__device__ __forceinline__ uint4 lds128(uint32_t addr) {
  uint4 v; asm volatile("ld.shared.v4.b32 {%0,%1,%2,%3}, [%4];" : "=r"(v.x), "=r"(v.y), "=r"(v.z), "=r"(v.w) : "r"(addr) : "memory"); return v;
}
__device__ __forceinline__ float2 lds64f(uint32_t addr) {
  float2 v; asm volatile("ld.shared.v2.f32 {%0,%1}, [%2];" : "=f"(v.x), "=f"(v.y) : "r"(addr) : "memory"); return v;
}
__device__ __forceinline__ void sts64(uint32_t addr, uint32_t a, uint32_t b) {
  asm volatile("st.shared.v2.b32 [%0], {%1, %2};" :: "r"(addr), "r"(a), "r"(b) : "memory");
}
__device__ __forceinline__ float fast_ex2(float x) { float y; asm("ex2.approx.ftz.f32 %0, %1;" : "=f"(y) : "f"(x)); return y; }
__device__ __forceinline__ float fast_rcp(float x) { float y; asm("rcp.approx.ftz.f32 %0, %1;" : "=f"(y) : "f"(x)); return y; }
__device__ __forceinline__ float fast_rsqrt(float x) { float y; asm("rsqrt.approx.ftz.f32 %0, %1;" : "=f"(y) : "f"(x)); return y; }
__device__ __forceinline__ float silu_f(float g) { return g * fast_rcp(1.f + fast_ex2(g * -1.4426950408889634f)); }
__device__ __forceinline__ float swiglu(float g, float u) {
  const float h = 0.5f * g;
  float t; asm("tanh.approx.f32 %0, %1;" : "=f"(t) : "f"(h));
  return fmaf(h, t, h) * u;
}

__device__ __forceinline__ void wgmma_m64n128k16_ss(float (&d)[64], uint64_t descA, uint64_t descB, int scaleD) {
  asm volatile("{\n.reg .pred p;\nsetp.ne.b32 p, %66, 0;\n"
    "wgmma.mma_async.sync.aligned.m64n128k16.f32.bf16.bf16 "
    "{%0, %1, %2, %3, %4, %5, %6, %7, %8, %9, %10, %11, %12, %13, %14, %15, "
    "%16, %17, %18, %19, %20, %21, %22, %23, %24, %25, %26, %27, %28, %29, %30, %31, "
    "%32, %33, %34, %35, %36, %37, %38, %39, %40, %41, %42, %43, %44, %45, %46, %47, "
    "%48, %49, %50, %51, %52, %53, %54, %55, %56, %57, %58, %59, %60, %61, %62, %63}, "
    "%64, %65, p, 1, 1, 0, 1;\n}\n"
    : "+f"(d[0]), "+f"(d[1]), "+f"(d[2]), "+f"(d[3]), "+f"(d[4]), "+f"(d[5]), "+f"(d[6]), "+f"(d[7]),
      "+f"(d[8]), "+f"(d[9]), "+f"(d[10]), "+f"(d[11]), "+f"(d[12]), "+f"(d[13]), "+f"(d[14]), "+f"(d[15]),
      "+f"(d[16]), "+f"(d[17]), "+f"(d[18]), "+f"(d[19]), "+f"(d[20]), "+f"(d[21]), "+f"(d[22]), "+f"(d[23]),
      "+f"(d[24]), "+f"(d[25]), "+f"(d[26]), "+f"(d[27]), "+f"(d[28]), "+f"(d[29]), "+f"(d[30]), "+f"(d[31]),
      "+f"(d[32]), "+f"(d[33]), "+f"(d[34]), "+f"(d[35]), "+f"(d[36]), "+f"(d[37]), "+f"(d[38]), "+f"(d[39]),
      "+f"(d[40]), "+f"(d[41]), "+f"(d[42]), "+f"(d[43]), "+f"(d[44]), "+f"(d[45]), "+f"(d[46]), "+f"(d[47]),
      "+f"(d[48]), "+f"(d[49]), "+f"(d[50]), "+f"(d[51]), "+f"(d[52]), "+f"(d[53]), "+f"(d[54]), "+f"(d[55]),
      "+f"(d[56]), "+f"(d[57]), "+f"(d[58]), "+f"(d[59]), "+f"(d[60]), "+f"(d[61]), "+f"(d[62]), "+f"(d[63])
    : "l"(descA), "l"(descB), "r"(scaleD));
}
__device__ __forceinline__ void wgmma_m64n256k16_rs(float (&d)[128], uint32_t a0, uint32_t a1, uint32_t a2, uint32_t a3, uint64_t descB, int scaleD) {
  asm volatile("{\n.reg .pred p;\nsetp.ne.b32 p, %133, 0;\n"
    "wgmma.mma_async.sync.aligned.m64n256k16.f32.bf16.bf16 "
    "{%0, %1, %2, %3, %4, %5, %6, %7, %8, %9, %10, %11, %12, %13, %14, %15, "
    "%16, %17, %18, %19, %20, %21, %22, %23, %24, %25, %26, %27, %28, %29, %30, %31, "
    "%32, %33, %34, %35, %36, %37, %38, %39, %40, %41, %42, %43, %44, %45, %46, %47, "
    "%48, %49, %50, %51, %52, %53, %54, %55, %56, %57, %58, %59, %60, %61, %62, %63, "
    "%64, %65, %66, %67, %68, %69, %70, %71, %72, %73, %74, %75, %76, %77, %78, %79, "
    "%80, %81, %82, %83, %84, %85, %86, %87, %88, %89, %90, %91, %92, %93, %94, %95, "
    "%96, %97, %98, %99, %100, %101, %102, %103, %104, %105, %106, %107, %108, %109, %110, %111, "
    "%112, %113, %114, %115, %116, %117, %118, %119, %120, %121, %122, %123, %124, %125, %126, %127}, "
    "{%128, %129, %130, %131}, %132, p, 1, 1, 1;\n}\n"
    : "+f"(d[0]), "+f"(d[1]), "+f"(d[2]), "+f"(d[3]), "+f"(d[4]), "+f"(d[5]), "+f"(d[6]), "+f"(d[7]),
      "+f"(d[8]), "+f"(d[9]), "+f"(d[10]), "+f"(d[11]), "+f"(d[12]), "+f"(d[13]), "+f"(d[14]), "+f"(d[15]),
      "+f"(d[16]), "+f"(d[17]), "+f"(d[18]), "+f"(d[19]), "+f"(d[20]), "+f"(d[21]), "+f"(d[22]), "+f"(d[23]),
      "+f"(d[24]), "+f"(d[25]), "+f"(d[26]), "+f"(d[27]), "+f"(d[28]), "+f"(d[29]), "+f"(d[30]), "+f"(d[31]),
      "+f"(d[32]), "+f"(d[33]), "+f"(d[34]), "+f"(d[35]), "+f"(d[36]), "+f"(d[37]), "+f"(d[38]), "+f"(d[39]),
      "+f"(d[40]), "+f"(d[41]), "+f"(d[42]), "+f"(d[43]), "+f"(d[44]), "+f"(d[45]), "+f"(d[46]), "+f"(d[47]),
      "+f"(d[48]), "+f"(d[49]), "+f"(d[50]), "+f"(d[51]), "+f"(d[52]), "+f"(d[53]), "+f"(d[54]), "+f"(d[55]),
      "+f"(d[56]), "+f"(d[57]), "+f"(d[58]), "+f"(d[59]), "+f"(d[60]), "+f"(d[61]), "+f"(d[62]), "+f"(d[63]),
      "+f"(d[64]), "+f"(d[65]), "+f"(d[66]), "+f"(d[67]), "+f"(d[68]), "+f"(d[69]), "+f"(d[70]), "+f"(d[71]),
      "+f"(d[72]), "+f"(d[73]), "+f"(d[74]), "+f"(d[75]), "+f"(d[76]), "+f"(d[77]), "+f"(d[78]), "+f"(d[79]),
      "+f"(d[80]), "+f"(d[81]), "+f"(d[82]), "+f"(d[83]), "+f"(d[84]), "+f"(d[85]), "+f"(d[86]), "+f"(d[87]),
      "+f"(d[88]), "+f"(d[89]), "+f"(d[90]), "+f"(d[91]), "+f"(d[92]), "+f"(d[93]), "+f"(d[94]), "+f"(d[95]),
      "+f"(d[96]), "+f"(d[97]), "+f"(d[98]), "+f"(d[99]), "+f"(d[100]), "+f"(d[101]), "+f"(d[102]), "+f"(d[103]),
      "+f"(d[104]), "+f"(d[105]), "+f"(d[106]), "+f"(d[107]), "+f"(d[108]), "+f"(d[109]), "+f"(d[110]), "+f"(d[111]),
      "+f"(d[112]), "+f"(d[113]), "+f"(d[114]), "+f"(d[115]), "+f"(d[116]), "+f"(d[117]), "+f"(d[118]), "+f"(d[119]),
      "+f"(d[120]), "+f"(d[121]), "+f"(d[122]), "+f"(d[123]), "+f"(d[124]), "+f"(d[125]), "+f"(d[126]), "+f"(d[127])
    : "r"(a0), "r"(a1), "r"(a2), "r"(a3), "l"(descB), "r"(scaleD));
}

constexpr uint32_t MSLOT = 32768, QSLOT = 49152;
constexpr int NM = 6, NQ = 4;
constexpr uint32_t SM_X0 = 3 * QSLOT;
constexpr uint32_t SM_XR = SM_X0 + 16384;
constexpr uint32_t SM_STG = 196608;
constexpr uint32_t SM_XCH = SM_STG + 16384;
constexpr uint32_t SM_BAR = SM_STG + 32768;
constexpr uint32_t SM_VEC = SM_BAR + 512;
constexpr uint32_t SM_MODT = SM_VEC;
constexpr uint32_t SM_TOTAL = SM_VEC + 2048;
constexpr uint32_t B_FQ = SM_BAR, B_EQ = SM_BAR + 32, B_FM = SM_BAR + 64, B_EM = SM_BAR + 112, B_MOD = SM_BAR + 160,
                   B_STREQ = SM_BAR + 224, B_STFREE = SM_BAR + 232, B_VEC = SM_BAR + 240  , B_X = SM_BAR + 256  , B_LN = SM_BAR + 320,
                   B_FLG = SM_BAR + 328  , B_STH = SM_BAR + 416, B_GATE = SM_BAR + 424;
constexpr int NB_WG = 1  , NB_CONS = 3, NB_ORD = 4  ;
#define PF_BYTES 512
#define PF2_BYTES 0
#define X_FIRST 6
#define X_S1 4
#define GATE_EARLY 0
#define X_POLL 5
#define SVC_WAIT mbar_sleep
#define PRD_WAIT mbar_wait
#define WPRE 2
#define HOLD1 1
#define HOLD2 0
#define ST0 0
#define QORD 2
#define QPOS 1
#define AUX_SLOW 68
#define AUX_GAP 500
#define DTAIL 4
#define EF 7
#define TRG_WAIT mbar_wait
#define ST_SPIN0 2
#define X_UP 2
#define X_GAP 200
#define X_PER 2
#define NEARLY 1

struct Maps {
  CUtensorMap x, out;
  CUtensorMap o, h2, hh;
  CUtensorMap wqk, wvv, wq1, wo, w1, w3, w2;
  CUtensorMap wmod;
};

struct Ring { int st; uint32_t ph; int prev; uint32_t dl; };
__device__ __forceinline__ void ring_next(Ring& r) { if (++r.st == NM) { r.st = 0; r.ph ^= 1; } }

__device__ __forceinline__ void retire_prev(uint32_t rel, bool on) {
  wgmma_commit();
  wgmma_wait<1>();
  if (on) mbar_arrive_e(rel);
}
struct Nop { __device__ __forceinline__ void operator()() const {} };
template <bool REL = true, class F = Nop>
__device__ __forceinline__ void mma_step(float (&acc)[64], uint32_t a, uint32_t b, bool first, uint32_t rel, F urgent = F()) {
  const uint32_t alo = (a >> 4) + (1u << 16), blo = (b >> 4) + (512u << 16);
  wgmma_fence();
  #pragma unroll
  for (int k = 0; k < 4; k++) {
    wgmma_m64n128k16_ss(acc, desc_from_lo(alo + k * 2), desc_from_lo(blo + k * 128), k > 0 || !first);
    if (k == 0) { retire_prev(rel, REL); urgent(); }
  }
  wgmma_commit();
}
__device__ __forceinline__ uint32_t m_wait(uint32_t sbase, const Ring& r) {
  mbar_wait(sbase + B_FM + 8 * r.st, r.ph, r.dl);
  return sbase + r.st * MSLOT;
}
__device__ __forceinline__ uint32_t m_prev(uint32_t sbase, const Ring& r) { return sbase + B_EM + 8 * r.prev; }
__device__ __forceinline__ void m_next(Ring& r) { r.prev = r.st; ring_next(r); }
__device__ __forceinline__ void m_step(float (&acc)[64], uint32_t sbase, uint32_t wgoff, Ring& r, bool first = false) {
  const uint32_t slot = m_wait(sbase, r);
  mma_step(acc, slot + wgoff, slot + 16384, first, m_prev(sbase, r));
  m_next(r);
}

struct LnRow { uint32_t rs[2], nb[2]; };
__device__ __forceinline__ void ln_row(LnRow& l, int h, float mean, float rstd) {
  l.rs[h] = pack_bf16(rstd, rstd);
  const float nb = -mean * bf_lo(l.rs[h]);
  l.nb[h] = pack_bf16(nb, nb);
}
__device__ __forceinline__ uint32_t ln_mod(uint32_t x, const LnRow& l, int h, uint32_t c1, uint32_t s) {
  return fma_bf2(fma_bf2(x, l.rs[h], l.nb[h]), c1, s);
}

__device__ __forceinline__ uint32_t q_wait(int u, uint32_t sbase, uint32_t dl) {
  mbar_wait(sbase + B_FQ + 8 * (u & 3), (u >> 2) & 1, dl);
  return sbase + (u & 3) * QSLOT;
}
__device__ __forceinline__ uint32_t q_empty(int u, uint32_t sbase) { return sbase + B_EQ + 8 * (u & 3); }
struct Frag4 { uint32_t o[4]; };
__device__ __forceinline__ void q_load(uint32_t (&A)[16], uint4 (&p)[4], int kk, uint32_t tile, const Frag4& f, uint32_t t) {
  ldmatrix_x4(tile + f.o[kk], A[4 * kk], A[4 * kk + 1], A[4 * kk + 2], A[4 * kk + 3]);
  p[kk] = lds128(t + kk * 64);
}
__device__ __forceinline__ void q_norm(uint32_t (&A)[16], const uint4 (&p)[4], int kk, const LnRow& l) {
  A[4 * kk + 0] = ln_mod(A[4 * kk + 0], l, 0, p[kk].x, p[kk].z); A[4 * kk + 1] = ln_mod(A[4 * kk + 1], l, 1, p[kk].x, p[kk].z);
  A[4 * kk + 2] = ln_mod(A[4 * kk + 2], l, 0, p[kk].y, p[kk].w); A[4 * kk + 3] = ln_mod(A[4 * kk + 3], l, 1, p[kk].y, p[kk].w);
}
template <bool NEXT>
__device__ __forceinline__ void q_step_rs(float (&acc)[128], uint32_t (&A)[16], uint32_t (&N)[16], uint4 (&p)[4], int u, uint32_t sbase,
                                          const Frag4& f, uint32_t tab, const LnRow& l, int hq, bool first, uint32_t dl, int wg) {
  const uint32_t slot = first ? sbase : q_wait(u, sbase, dl);
  const uint32_t blo = ((slot + 16384) >> 4) + (512u << 16), t = tab + ((u + 1) & 7) * 256;
  #pragma unroll
  for (int kk = 0; kk < 4; kk++) q_norm(A, p, kk, l);
  if (first) {
    #pragma unroll
    for (int i = 0; i < 16; i++) asm volatile("" : "+r"(A[i]));
    mbar_wait(sbase + B_GATE, 0, dl);
    PROF(6, threadIdx.x == 0);
  }
  if (QORD == 1 && first && wg == 1) bar_sync(NB_ORD, 256);
  if (QORD == 2 && !(first && wg == 0)) bar_sync(NB_ORD + wg, 256);
  wgmma_fence();
  #pragma unroll
  for (int kk = 0; kk < 4; kk++) {
    wgmma_m64n256k16_rs(acc, A[4 * kk], A[4 * kk + 1], A[4 * kk + 2], A[4 * kk + 3], desc_from_lo(blo + kk * 128), kk > 0 || !first);
    if (kk == 0) retire_prev(q_empty(u - 1, sbase), !first);
    if (NEXT && kk < 2) { q_load(N, p, 2 * kk, slot, f, t); q_load(N, p, 2 * kk + 1, slot, f, t); }
    if (QORD == 1 && first && kk == QPOS && wg == 0) bar_arrive(NB_ORD, 256);
    if (QORD == 2 && kk == QPOS && (NEXT || wg == 0)) bar_arrive(NB_ORD + (wg ^ 1), 256);
    if (kk == 1) {
      const uint32_t dst = sbase + SM_STG + (u >> 3) * 16384 + (f.o[0] ^ ((u & 6) << 4));
      #pragma unroll
      for (int q = 0; q < 4; q++) stmatrix_x4_if(dst, A[4 * q], A[4 * q + 1], A[4 * q + 2], A[4 * q + 3], hq == q);
    }
  }
  wgmma_commit();
}

typedef uint32_t Frag8[8];
template <int N> __device__ __forceinline__ void pack_half(Frag8& f, const float (&acc)[N], int off, int half) {
  #pragma unroll
  for (int e = 0; e < 8; e++) { f[e] = pack_bf16(acc[off + 4 * e + 2 * half], acc[off + 4 * e + 2 * half + 1]); asm volatile("" : "+r"(f[e])); }
}
__device__ __forceinline__ void transpose8(Frag8& f) {
  #pragma unroll
  for (int e = 0; e < 8; e++) f[e] = movmatrix_t(f[e]);
}
__device__ __forceinline__ void attn_send(const Frag8& f, int kv, uint32_t xch, int warp, uint4* halo_out, bool has_next) {
  if (warp == 3) {
    st_rlx_v4(halo_out + kv * 64, f[0], f[1], f[2], f[3], has_next); st_rlx_v4(halo_out + kv * 64 + 32, f[4], f[5], f[6], f[7], has_next);
  } else {
    sts128(xch + 2048 + kv * 1024, f[0], f[1], f[2], f[3]); sts128(xch + 2048 + kv * 1024 + 512, f[4], f[5], f[6], f[7]);
  }
}
template <int N>
__device__ __forceinline__ void attn_recv(uint4* p, int first, uint32_t xch, int wg, int warp, const uint4* halo_in, bool has_prev) {
  bar_sync(NB_WG + wg, 128);
  #pragma unroll
  for (int e = 0; e < N; e++)
    asm volatile("{\n.reg .pred p, q;\nsetp.ne.b32 p, %6, 0;\nsetp.ne.b32 q, %7, 0;\n"
                 "mov.b32 %0, 0;\nmov.b32 %1, 0;\nmov.b32 %2, 0;\nmov.b32 %3, 0;\n"
                 "@p ld.shared.v4.b32 {%0,%1,%2,%3}, [%4];\n@q ld.relaxed.gpu.global.v4.u32 {%0,%1,%2,%3}, [%5];\n}"
                 : "=&r"(p[e].x), "=&r"(p[e].y), "=&r"(p[e].z), "=&r"(p[e].w)
                 : "r"(xch + (first + e) * 512), "l"(halo_in + (first + e) * 32), "r"((int)(warp > 0)), "r"((int)(warp == 0 && has_prev)) : "memory");
}
template <int N>
__device__ __forceinline__ void attn_check(uint4* p, int first, int warp, const uint4* halo_in, uint32_t dl) {
  if (warp == 0) {
    while (true) {
      uint32_t m = 0;
      #pragma unroll
      for (int e = 0; e < N; e++) m = max(max(m, max(p[e].x, p[e].y)), max(p[e].z, p[e].w));
      if (poll_done(m != ~0u, dl)) break;
      #pragma unroll
      for (int e = 0; e < N; e++) p[e] = ld_rlx_v4(halo_in + (first + e) * 32);
    }
  }
}
__device__ __forceinline__ void attn_core(const Frag8& qA, const Frag8& qB, const Frag8& kA, const Frag8& kB, const Frag8& vA, const Frag8& vB,
                                          const uint4* kP, const uint4* vP, bool noprev, int lane, float (&o)[2][5][4]) {
  const int g = lane >> 2, qd = lane & 3;
  const bool s0 = 2 * qd > g, s1 = 2 * qd + 1 > g;
  const uint32_t msk = (s0 ? 0xFFFFu : 0u) | (s1 ? 0xFFFF0000u : 0u);
  constexpr float SC = 0.17677669529663687f * 1.4426950408889634f;
  float s[2][3][4];
  #pragma unroll
  for (int h = 0; h < 2; h++)
    #pragma unroll
    for (int nb = 0; nb < 3; nb++) s[h][nb][0] = s[h][nb][1] = s[h][nb][2] = s[h][nb][3] = 0.f;
  #pragma unroll
  for (int kk = 0; kk < 2; kk++)
    #pragma unroll
    for (int h = 0; h < 2; h++) {
      const int e = 4 * h + 2 * kk;
      mma16(s[h][1], qA[e], qB[e], qA[e + 1], qB[e + 1], kA[e], kA[e + 1]);
      mma16(s[h][2], qA[e], qB[e], qA[e + 1], qB[e + 1], kB[e], kB[e + 1]);
      mma16(s[h][0], qA[e], qB[e], qA[e + 1], qB[e + 1], kk ? kP[h].z : kP[h].x, kk ? kP[h].w : kP[h].y);
    }
  float l[2][4], m[2][2];
  #pragma unroll
  for (int h = 0; h < 2; h++) {
    l[h][0] = s0 ? (noprev ? -INFINITY : s[h][0][0]) : s[h][1][0];
    l[h][1] = s1 ? (noprev ? -INFINITY : s[h][0][1]) : s[h][1][1];
    l[h][2] = s0 ? s[h][1][2] : s[h][2][2];
    l[h][3] = s1 ? s[h][1][3] : s[h][2][3];
    m[h][0] = fmaxf(l[h][0], l[h][1]); m[h][1] = fmaxf(l[h][2], l[h][3]);
  }
  #pragma unroll
  for (int x = 1; x <= 2; x <<= 1)
    #pragma unroll
    for (int e = 0; e < 4; e++) m[e >> 1][e & 1] = fmaxf(m[e >> 1][e & 1], __shfl_xor_sync(0xffffffffu, m[e >> 1][e & 1], x));
  #pragma unroll
  for (int h = 0; h < 2; h++) {
    #pragma unroll
    for (int e = 0; e < 4; e++) l[h][e] = fast_ex2((l[h][e] - m[h][e >> 1]) * SC);
    const uint32_t plo = pack_bf16(l[h][0], l[h][1]), phi = pack_bf16(l[h][2], l[h][3]);
    const uint32_t vp[4] = {vP[h].x, vP[h].y, vP[h].z, vP[h].w};
    #pragma unroll
    for (int d = 0; d < 5; d++) o[h][d][0] = o[h][d][1] = o[h][d][2] = o[h][d][3] = 0.f;
    mma8(o[h][4], plo, phi, 0x3F803F80u);
    #pragma unroll
    for (int d = 0; d < 4; d++) mma16(o[h][d], plo & ~msk, phi & msk, 0u, phi & ~msk, vA[4 * h + d], vB[4 * h + d]);
    #pragma unroll
    for (int d = 0; d < 4; d++) mma8(o[h][d], plo & msk, 0u, vp[d]);
  }
}
__device__ __forceinline__ void attn_store(const float (&o)[2][5][4], int h, uint32_t sbase, const Frag4& f) {
  const float r0 = fast_rcp(o[h][4][0]), r1 = fast_rcp(o[h][4][2]);
  #pragma unroll
  for (int d = 0; d < 4; d += 2)
    stmatrix_x4(sbase + SM_STG + f.o[2 * h + (d >> 1)],
                pack_bf16(o[h][d][0] * r0, o[h][d][1] * r0), pack_bf16(o[h][d][2] * r1, o[h][d][3] * r1),
                pack_bf16(o[h][d + 1][0] * r0, o[h][d + 1][1] * r0), pack_bf16(o[h][d + 1][2] * r1, o[h][d + 1][3] * r1));
}

__device__ __forceinline__ void g_switch(float (&cur)[64], float (&prv)[64], int nrest, bool first, int n, uint32_t sbase, uint32_t wgoff,
                                         const Frag4& f, Ring& r) {
  #pragma unroll 1
  for (int i = 1; i < nrest; i++) m_step(prv, sbase, wgoff, r);
  m_step(prv, sbase, wgoff, r);
  m_step(cur, sbase, wgoff, r, first);
  mbar_wait(sbase + B_STFREE, (n - 1) & 1, r.dl);
  fence_regs(prv);
  PROF(28 + n, threadIdx.x == 0);
  #pragma unroll
  for (int jj = 0; jj < 4; jj++) {
    uint32_t p[4];
    #pragma unroll
    for (int e = 0; e < 4; e++) {
      const int i = jj * 8 + e * 2;
      p[e] = pack_bf16(swiglu(prv[i], prv[i + 32]), swiglu(prv[i + 1], prv[i + 33]));
    }
    stmatrix_x4(sbase + SM_STG + f.o[jj], p[0], p[1], p[2], p[3]);
    m_step(cur, sbase, wgoff, r);
  }
  mbar_arrive_e(sbase + B_STREQ);
}

__device__ __forceinline__ uint32_t bad2(uint32_t a, uint32_t b, unsigned par) {
  uint32_t d; asm("lop3.b32 %0, %1, %2, %3, 0x7E;" : "=r"(d) : "r"(a), "r"(b), "r"(par)); return d;
}
__device__ __forceinline__ uint32_t bad4(const uint4& v, unsigned par) { return bad2(v.x, v.y, par) | bad2(v.z, v.w, par); }
__device__ __forceinline__ uint32_t hi_halves(uint32_t lo, uint32_t hi) { return __byte_perm(lo, hi, 0x7632); }

__device__ __forceinline__ void gather_table(const float* src, uint32_t dst, uint32_t bar, unsigned par, uint32_t dl) {
  asm volatile("{\n.reg .pred p, e;\n.reg .b32 s<4>, c<4>, t<4>, w<4>;\n"
               "elect.sync _|e, 0xffffffff;\n"
               "LAB_POLL:\n"
               "ld.relaxed.gpu.global.v4.u32 {s0, s1, s2, s3}, [%0];\n"
               "ld.relaxed.gpu.global.v4.u32 {c0, c1, c2, c3}, [%0 + 4096];\n"
               "prmt.b32 w0, c0, c1, 0x7632;\nprmt.b32 w1, c2, c3, 0x7632;\nprmt.b32 w2, s0, s1, 0x7632;\nprmt.b32 w3, s2, s3, 0x7632;\n"
               "st.shared.v4.b32 [%1], {w0, w1, w2, w3};\n"
               "lop3.b32 t0, s0, s1, %3, 0x7E;\nlop3.b32 t1, s2, s3, %3, 0x7E;\nlop3.b32 t2, c0, c1, %3, 0x7E;\nlop3.b32 t3, c2, c3, %3, 0x7E;\n"
               "lop3.b32 t0, t0, t1, 1, 0xA8;\nlop3.b32 t2, t2, t3, 1, 0xA8;\n"
               "or.b32 t0, t0, t2;\n"
               "setp.eq.u32 p, t0, 0;\n"
               "vote.sync.all.pred p, p, 0xffffffff;\n"
               "@p bra.uni LAB_OK;\n"
               "mov.u32 t0, %%clock;\nsub.s32 t0, t0, %4;\nsetp.lt.s32 p, t0, 0;\n"
               "vote.sync.all.pred p, p, 0xffffffff;\n"
               "@p bra.uni LAB_POLL;\n"
               "LAB_OK:\n"
               "@e mbarrier.arrive.shared::cta.b64 _, [%2];\n}"
               :: "l"(src), "r"(dst), "r"(bar), "r"(par), "r"(dl) : "memory");
}

__device__ __forceinline__ int other_slot(int i, int j) { return i < 4 ? (~j & 4) + i : (j & 4) + i - 4 + (i - 4 >= (j & 3)); }

__device__ __forceinline__ int aux_col(int a, int u) { return u < 8 ? (a & 1) * 1024 + (2 * u + (a >> 1)) * 64 : 2048 + ((u - 8) * 4 + a) * 64; }
constexpr int NA = 7;
constexpr uint32_t A_FULL = SM_BAR, A_EMPTY = SM_BAR + 64, A_SUM = SM_BAR + 128, A_FREE = SM_BAR + 136, SM_RED = SM_VEC;
__device__ __forceinline__ void aux_role(const Maps& maps, const bf16* __restrict__ cvec, int a, uint32_t sbase, int wid) {
  const int tid = threadIdx.x, lane = tid & 31;
  const uint32_t dl = clock32() + 800000000u;
  int st = 0; uint32_t ph = 0;
  if (wid == 8) {
    if (lane == 0) {
      prefetch_tmap(&maps.wmod);
      for (int s = 0; s < NA; s++) { mbar_init(sbase + A_FULL + 8 * s, 1); mbar_init(sbase + A_EMPTY + 8 * s, 8); }
      mbar_init(sbase + A_SUM, 8); mbar_init(sbase + A_FREE, 2);
      asm volatile("fence.mbarrier_init.release.cluster;" ::: "memory");
      fence_proxy_async_smem();
    }
    __syncwarp();
    #pragma unroll 1
    for (int i = 0; i < 96; i++) {
      if (i == NA) bar_sync(0, 352);
      if (i >= AUX_SLOW) wait_until(clock32() + AUX_GAP);
      mbar_wait(sbase + A_EMPTY + 8 * st, ph ^ 1, dl);
      mbar_expect_tx_e(sbase + A_FULL + 8 * st, 32768);
      if (i < 8) tma_load_2d(sbase + st * MSLOT, &maps.wmod, sbase + A_FULL + 8 * st, aux_col(a, i >> 2), (i & 3) * 256);
      else tma_load_2d<(EF & 1) != 0>(sbase + st * MSLOT, &maps.wmod, sbase + A_FULL + 8 * st, aux_col(a, i >> 2), (i & 3) * 256);
      if (++st == NA) { st = 0; ph ^= 1; }
    }
  } else if (wid < 8) {
    const int g = lane >> 2, qd = lane & 3;
    uint32_t sc[16];
    #pragma unroll
    for (int i = 0; i < 16; i++) sc[i] = *reinterpret_cast<const uint32_t*>(cvec + (i >> 2) * 256 + wid * 32 + (i & 3) * 8 + qd * 2);
    #pragma unroll
    for (int i = 0; i < 16; i++) sc[i] = pack_bf16(silu_f(bf_lo(sc[i])), silu_f(bf_hi(sc[i])));
    bar_sync(0, 352);
    PROFN(0, tid == 0);
    const uint32_t aoff = (wid * 32 + (lane & 7) + (lane >> 4) * 8) * 128 + ((((lane >> 3) & 1) ^ (lane & 7)) << 4);
    uint32_t w[2][8][4];
    auto fetch = [&](uint32_t (&f)[8][4]) {
      mbar_wait(sbase + A_FULL + 8 * st, ph, dl);
      #pragma unroll
      for (int e = 0; e < 8; e++) ldmatrix_x4_t((sbase + st * MSLOT + aoff + (e >> 2) * 2048) ^ ((e & 3) << 5), f[e]);
      mbar_arrive_e(sbase + A_EMPTY + 8 * st);
      if (++st == NA) { st = 0; ph ^= 1; }
    };
    #pragma unroll 1
    for (int u = 0; u < 24; u++) {
      float acc[4][4];
      #pragma unroll
      for (int m = 0; m < 4; m++) acc[m][0] = acc[m][1] = acc[m][2] = acc[m][3] = 0.f;
      fetch(w[0]);
      #pragma unroll
      for (int q = 0; q < 4; q++) {
        PROF(30 + (u & 1) * 4 + q, u < 2 && tid == 0);
        if (q < 3) fetch(w[(q + 1) & 1]);
        if (q == 1) mbar_wait(sbase + A_FREE, (u & 1) ^ 1, dl);
        #pragma unroll
        for (int e = 0; e < 8; e++) {
          const uint32_t (&f)[4] = w[q & 1][e];
          mma16(acc[e & 3], f[0], f[1], f[2], f[3], sc[4 * q + 2 * (e >> 2)], sc[4 * q + 2 * (e >> 2) + 1]);
        }
      }
      const float v0 = qd & 2 ? (qd & 1 ? acc[3][0] : acc[2][0]) : (qd & 1 ? acc[1][0] : acc[0][0]);
      const float v1 = qd & 2 ? (qd & 1 ? acc[3][2] : acc[2][2]) : (qd & 1 ? acc[1][2] : acc[0][2]);
      sts64(sbase + SM_RED + wid * 256 + (qd * 8 + g) * 8, __float_as_uint(v0), __float_as_uint(v1));
      mbar_arrive_e(sbase + A_SUM);
    }
  } else if (wid < 11) {
    const unsigned par = (1 + ld_relaxed(&g_flags[FL_EPOCH])) & 1;
    float* const mail = &g_mod[(wid - 9) * 4 * 6 * D_ + 2 * lane];
    bar_sync(0, 352);
    #pragma unroll 1
    for (int u = -2; u < 24; u++) {
      if (u >= 0) {
        const int col = aux_col(a, u);
        const float add = (col >> 10) == 1 || (col >> 10) == 4 ? 1.f : 0.f;
        mbar_wait(sbase + A_SUM, u & 1, dl);
        float2 v[8];
        #pragma unroll
        for (int w = 0; w < 8; w++) v[w] = lds64f(sbase + SM_RED + w * 256 + lane * 8);
        const float t0 = ((v[0].x + v[1].x) + (v[2].x + v[3].x)) + ((v[4].x + v[5].x) + (v[6].x + v[7].x));
        const float t1 = ((v[0].y + v[1].y) + (v[2].y + v[3].y)) + ((v[4].y + v[5].y) + (v[6].y + v[7].y));
        const uint32_t w = pack_bf16(add + bf16_round(t0), add + bf16_round(t1)), o = __shfl_xor_sync(0xffffffffu, w, 1);
        const uint32_t m0 = (lane & 1) ? (o & 0xFFFF0000u) : (w << 16), m1 = (lane & 1) ? (w & 0xFFFF0000u) : (o << 16);
        #pragma unroll
        for (int c = 0; c < 4; c++) st_rlx_v2(mail + c * 6 * D_ + col, m0 | par, m1 | par, true);
        mbar_arrive_e(sbase + A_FREE);
        PROF(1 + u, tid == 288);
      }
      #pragma unroll 1
      for (int v = 2 * (u + 2); v < 2 * (u + 3) && v < 24; v++)
        #pragma unroll
        for (int c = 0; c < 4; c++) st_rlx_v2(mail + c * 6 * D_ + aux_col(a, v), par ^ 1, par ^ 1, true);
    }
  }
}

__global__ void __launch_bounds__(384, 1)
fused_block_kernel(const __grid_constant__ Maps maps, const bf16* __restrict__ x, const bf16* __restrict__ cvec, const bf16* __restrict__ wmod,
                   int mode) {
  extern __shared__ __align__(1024) uint8_t smem_raw[];
  const uint32_t sbase = smem_u32(smem_raw);
  const int tid = threadIdx.x, lane = tid & 31;
  const int wid = __shfl_sync(0xffffffffu, tid >> 5, 0);
  const int b = cta_role(mode);
  if (b >= NCTA) { aux_role(maps, cvec, b - NCTA, sbase, wid); return; }
  const int jg = b >> 6, mb = jg ? 31 - (b >> 2) : (b >> 2), j = 4 * jg + (b & 3);
  const uint32_t dl = clock32() + 800000000u;
  unsigned* const flags = &g_flags[mb * 32];
  const unsigned e1 = 1 + ld_relaxed(wid >= 10 ? &g_flags[FL_EPOCH] : flags + FO_EPOCH);
  const unsigned par = e1 & 1;
  const int row0 = mb * 128;

  if (wid >= 8) {
    if (wid == 8) {
      if (lane == 0) {
        for (int s = 0; s < 8; s++) mbar_init(sbase + B_X + 8 * s, 1);
        asm volatile("fence.mbarrier_init.release.cluster;" ::: "memory");
        fence_proxy_async_smem();
      }
      #pragma unroll 1
      for (int q = 0; q < X_UP; q++) {
        mbar_expect_tx_e(sbase + B_X + 8 * q, 4096);
        bulk_load(sbase + SM_XR + q * 4096, x + (size_t)(row0 + j * 16 + 2 * q) * D_, 4096, sbase + B_X + 8 * q);
      }
    } else if (tid == 288) {
      for (int s = 0; s < NQ; s++) { mbar_init(sbase + B_FQ + 8 * s, 1 + (s & 1)); mbar_init(sbase + B_EQ + 8 * s, 8); }
      for (int s = 0; s < NM; s++) { mbar_init(sbase + B_FM + 8 * s, 1); mbar_init(sbase + B_EM + 8 * s, 8); }
      mbar_init(sbase + B_MOD, 1); mbar_init(sbase + B_GATE, 1);
      mbar_init(sbase + B_STREQ, 8); mbar_init(sbase + B_STFREE, 1); mbar_init(sbase + B_VEC, 1); mbar_init(sbase + B_VEC + 8, 1); mbar_init(sbase + B_LN, 8);
      for (int s = 0; s < 11; s++) mbar_init(sbase + B_FLG + 8 * s, 1);
      mbar_init(sbase + B_STH, 8);
      asm volatile("fence.mbarrier_init.release.cluster;" ::: "memory");
      fence_proxy_async_smem();
    } else if (tid >= 320 && tid < 332) {
      prefetch_tmap(&maps.x + (tid - 320));
    }
    bar_sync(0, 384);
    reg_dealloc<40>();
    if (wid == 8) {
      uint32_t tnext = clock32();
      int xq = X_UP;
      #pragma unroll 1
      for (int u = 0; u < 16; u++) {
        const int st = u & 3;
        if (u <= NEARLY) {
          #pragma unroll 1
          for (; xq < 8 && (xq < X_UP + X_FIRST + u * X_PER || u == NEARLY); xq++) {
            tnext += X_GAP; wait_until(tnext);
            mbar_expect_tx_e(sbase + B_X + 8 * xq, 4096);
            bulk_load(sbase + SM_XR + xq * 4096, x + (size_t)(row0 + j * 16 + 2 * xq) * D_, 4096, sbase + B_X + 8 * xq);
          }
          if (u == NEARLY) PRD_WAIT(sbase + B_X + 8 * X_S1, 0, dl);
        }
        if (u == 2) { PRD_WAIT(sbase + B_GATE, 0, dl); PROFN(60, lane == 0); }
        if (u == 3) PRD_WAIT(sbase + B_EQ, 0, dl);
        PRD_WAIT(sbase + B_EQ + 8 * st, ((u >> 2) & 1) ^ 1, dl);
        const uint32_t slot = sbase + st * QSLOT, fb = sbase + B_FQ + 8 * st;
        mbar_expect_tx_e(fb, u == 0 ? 65536 : u == 15 ? 32768 : 49152);
        if (u == 0) tma_load_3d(sbase + SM_X0, &maps.x, fb, 0, mb * 64, 0);
        tma_load_4d<(EF & 2) != 0>(slot + 16384, &maps.wqk, fb, 0, u * 64, j, 0);
        tma_load_4d<(EF & 2) != 0>(slot + 32768, &maps.wvv, fb, 0, u * 64, j, 0);
        if (u < 15) tma_load_3d(slot, &maps.x, fb, u * 64 + 64, mb * 64, 0);
      }
      Ring r{0, 1, 0, dl};
      uint32_t slot, fb;
      auto acquire = [&](uint32_t bytes) {
        PRD_WAIT(sbase + B_EM + 8 * r.st, r.ph, dl);
        slot = sbase + r.st * MSLOT; fb = sbase + B_FM + 8 * r.st;
        mbar_expect_tx_e(fb, bytes);
        ring_next(r);
      };
      auto hold = [&](int n) { Ring h = r; for (int i = 0; i < n; i++) ring_next(h); PRD_WAIT(sbase + B_EM + 8 * h.st, h.ph, dl); };
      #pragma unroll 1
      for (int kt = 0; kt < 16; kt++) {
        if (kt < 5) PRD_WAIT(sbase + B_EQ + 8 * (kt - (kt >= 2)), 1, dl);
        if (kt == 8) hold(HOLD1);
        if ((kt & 7) == 0) { PROF(46, lane == 0 && kt == 8); PRD_WAIT(sbase + B_FLG + kt, 0, dl); PROF(47, lane == 0 && kt == 8); }
        acquire(32768);
        tma_load_4d<(EF & 2) != 0>(slot + 16384, &maps.wq1, fb, (j + 8) * 64, (kt & 1) * 64 + (kt & 6) * 8, (kt >> 3) * 4, 0);
        tma_load_3d(slot, &maps.hh, fb, (kt & 7) * 64, row0, kt >> 3);
      }
      hold(HOLD2);
      PROF(82, lane == 0);
      PRD_WAIT(sbase + B_FLG + 16, 0, dl);
      PROF(83, lane == 0);
      #pragma unroll 1
      for (int kt = 0; kt < 8; kt++) {
        acquire(32768);
        tma_load_3d<(EF & 2) != 0>(slot + 16384, &maps.wo, fb, 0, kt * 64, 2 * j);
        tma_load_2d(slot, &maps.o, fb, kt * 64, row0);
      }
      acquire(16384);
      tma_load_3d<(EF & 2) != 0>(slot + 16384, &maps.wo, fb, 0, (8 + j) * 64, 2 * j);
      {
        constexpr int NPRE = WPRE;
        Ring ra = r;
        #pragma unroll 1
        for (int i = 0; i < 7; i++) {
          const int kt = 8 + other_slot(i, j);
          if (i == 4) {
            acquire(32768);
            tma_load_3d(slot, &maps.x, fb, j * 128, mb * 64, 0);
            tma_load_3d(slot + 16384, &maps.x, fb, j * 128 + 64, mb * 64, 0);
          }
          acquire(32768);
          tma_load_3d<(EF & 2) != 0>(slot + 16384, &maps.wo, fb, 0, kt * 64, 2 * j);
          if (i == NPRE - 1) {
            wait_flag(&g_flags[FL_O], e1 * NCTA, dl);
            PROF(61, lane == 0);
            #pragma unroll 1
            for (int q = 0; q < NPRE - 1; q++) { tma_load_2d(sbase + ra.st * MSLOT, &maps.o, sbase + B_FM + 8 * ra.st, (8 + other_slot(q, j)) * 64, row0); ring_next(ra); }
          }
          if (i >= NPRE - 1) tma_load_2d(slot, &maps.o, fb, kt * 64, row0);
        }
      }
      #pragma unroll 1
      for (int t = 0; t < 2; t++) {
        acquire(32768);
        tma_load_2d<(EF & 4) != 0>(slot, &maps.w1, fb, j * 64, (2 * j + t) * 64);
        tma_load_2d<(EF & 4) != 0>(slot + 8192, &maps.w3, fb, j * 64, (2 * j + t) * 64);
        tma_load_2d<(EF & 4) != 0>(slot + 16384, &maps.w1, fb, (8 + j) * 64, (2 * j + t) * 64);
        tma_load_2d<(EF & 4) != 0>(slot + 24576, &maps.w3, fb, (8 + j) * 64, (2 * j + t) * 64);
      }
      {
        Ring ra = r;
        #pragma unroll 1
        for (int i = 0; i < 4; i++) {
          const int kt = 2 * ((~j & 4) + i);
          acquire(32768);
          tma_load_2d<(EF & 4) != 0>(slot + 16384, &maps.w1, fb, j * 64, kt * 64);
          tma_load_2d<(EF & 4) != 0>(slot + 24576, &maps.w3, fb, j * 64, kt * 64);
        }
        wait_flag(&g_flags[FL_H2], e1 * NCTA, dl);
        PROFN(62, lane == 0);
        #pragma unroll 1
        for (int i = 0; i < 4; i++) { tma_load_2d(sbase + ra.st * MSLOT, &maps.h2, sbase + B_FM + 8 * ra.st, ((~j & 4) + i) * 128, row0); ring_next(ra); }
      }
      #pragma unroll 1
      for (int gt = 0; gt < 7; gt++) {
        const int ncol = (8 * gt + j) * 64;
        #pragma unroll 1
        for (int i = (gt == 0 ? 4 : 0); i < (gt < 2 ? 14 : 16); i++) {
          const int kt = gt >= 2 ? i : i < 7 ? 2 * other_slot(i, j) : 2 * other_slot(i - 7, j) + 1;
          if (gt == 0 && i == 7) PRD_WAIT(sbase + B_FLG + 24, 0, dl);
          acquire(32768);
          tma_load_2d<(EF & 4) != 0>(slot + 16384, &maps.w1, fb, ncol, kt * 64);
          tma_load_2d<(EF & 4) != 0>(slot + 24576, &maps.w3, fb, ncol, kt * 64);
          tma_load_2d(slot, &maps.h2, fb, kt * 64, row0);
        }
      }
      #pragma unroll 1
      for (int kt = 0; kt < 56; kt++) {
        if ((kt & 7) == 0) PRD_WAIT(sbase + B_FLG + 32 + kt, 0, dl);
        acquire(32768);
        tma_load_3d<(EF & 8) != 0>(slot + 16384, &maps.w2, fb, 0, kt * 64, 2 * j);
        tma_load_3d<(EF & 16) != 0>(slot, &maps.hh, fb, (kt & 7) * 64, row0, kt >> 3);
      }
    } else {
      if (wid == 9) {
        mbar_wait(sbase + B_LN, 0, dl);
        red_add_e(&g_flags[FL_LN1], 1);
        SVC_WAIT(sbase + B_GATE, 0, dl);
        #pragma unroll 1
        for (int e = 0; e < 16; e++) st_rlx_v4(g_halo + (mb * 16 + j + (e & 8)) * 256 + (e & 7) * 32 + lane, ~0u, ~0u, ~0u, ~0u, true);
        #pragma unroll 1
        for (int e = 0; e < 2; e++) st_rlx_v4(g_st2 + ((mb * 8 + e * 4 + (lane >> 3)) * 8 + j) * 8 + (lane & 7), ~0u, ~0u, ~0u, ~0u, true);
        __threadfence();
        red_add_e(&g_flags[FL_RESET], 1);
        #pragma unroll 1
        for (int n = 0; n < 12; n++) {
          if (n == 4) {
            mbar_wait(sbase + B_STH, 0, dl);
            fence_proxy_async_smem();
            tma_store_2d(&maps.h2, sbase + SM_STG, j * 128, row0);
            bulk_commit();
            bulk_wait0();
            red_add_e(&g_flags[FL_H2], 1);
            PROF(84, lane == 0);
          }
          if (n >= ST_SPIN0 && n <= 4) mbar_wait(sbase + B_STREQ, n & 1, dl); else SVC_WAIT(sbase + B_STREQ, n & 1, dl);
          fence_proxy_async_smem();
          if (n == 2 || n == 3) tma_store_2d(&maps.o, sbase + SM_STG, (j + 8 * (n - 2)) * 64, row0);
          else if (n == 4) tma_store_2d(&maps.h2, sbase + SM_STG + 16384, j * 128 + 64, row0);
          else tma_store_3d(&maps.hh, sbase + SM_STG + (n == 1 ? 16384 : 0), j * 64, row0, n < 2 ? n : n - 5);
          bulk_commit();
          bulk_wait0();
          red_add_e(n == 3 ? &g_flags[FL_O] : flags + (n < 2 ? FO_H1 + n : n - 1), 1);
          mbar_arrive_e(sbase + B_STFREE);
          PROFN(70 + n, lane == 0 && n > 0);
        }
      } else {
        mbar_wait(sbase + B_X + 8 * X_POLL, 0, dl);
        const float* const mail = &g_mod[(b & 7) * 6 * D_ + lane * 4];
        if (wid == 10) {
          #pragma unroll 1
          for (int p = 0; p < 8; p++) {
            if (p >= 2) TRG_WAIT(p == 2 ? sbase + B_GATE : q_empty(2 * p - 5, sbase), p == 2 ? 0 : ((2 * p - 5) >> 2) & 1, dl);
            gather_table(mail + p * 128, sbase + SM_MODT + (p & 3) * 512 + lane * 16, p == 0 ? sbase + B_MOD : sbase + B_FQ + 8 * ((2 * p - 1) & 3), par, dl);
            PROF(63 + p, lane == 0 && p < 7);
          }
          const uint32_t vdst = sbase + SM_VEC + (lane >> 3) * 64 + (lane & 3) * 16 + ((lane >> 2) & 1) * 8;
          #pragma unroll 1
          for (int v = 0; v < 2; v++) {
            SVC_WAIT(sbase + B_FLG + 16 + 16 * v, 0, dl);
            uint4 m[3];
            while (true) {
              #pragma unroll
              for (int e = 0; e < 3; e++) m[e] = ld_rlx_v4(mail + (2 + v + e) * 1024 + j * 128);
              if (poll_done(((bad4(m[0], par) | bad4(m[1], par) | bad4(m[2], par)) & 1) == 0, dl)) break;
              __nanosleep(200);
            }
            #pragma unroll
            for (int e = 0; e < 3; e++) sts64(vdst + (v + e) * 256, hi_halves(m[e].x, m[e].y), hi_halves(m[e].z, m[e].w));
            mbar_arrive_e(sbase + B_VEC + 8 * v);
            PROF(70, lane == 0 && v == 0);
          }
        } else {
          mbar_wait(sbase + B_LN, 0, dl);
          wait_flag(&g_flags[FL_LN1], e1 * NCTA, dl);
          mbar_arrive_e(sbase + B_GATE);
          PROF(41, lane == 0);
          SVC_WAIT(q_empty(3, sbase), 0, dl);
          wait_flag(&g_flags[FL_RESET], e1 * NCTA, dl);
          SVC_WAIT(q_empty(7, sbase), 1, dl);
          SVC_WAIT(q_empty(11, sbase), 0, dl);
          mbar_arrive_e(sbase + B_FQ + 24);
          #pragma unroll 1
          for (int i = 0; i < 11; i++) {
            const unsigned* f = flags + (i < 2 ? FO_H1 + i : i == 2 ? FO_O : FO_H2 + i - 3);
            if (i == 3) SVC_WAIT(sbase + B_STH, 0, dl);
            while (!poll_done((int)(ld_relaxed(f) - e1 * 8) >= 0, dl)) { if (i > 3) __nanosleep(200); }
            mbar_arrive_e(sbase + B_FLG + 8 * i);
          }
        }
      }
    }
  } else {
    PROFN(0, tid == 0);
    const int wg = wid >> 2, warp = wid & 3;
    const int g = lane >> 2, qd = lane & 3;
    bulk_prefetch(wmod + (size_t)(b * 8 + wid) * (6 * D_), PF_BYTES);
    bulk_prefetch(wmod + (size_t)(b * 8 + wid) * (6 * D_) + D_, PF_BYTES);
    bar_sync(0, 384);
    reg_alloc<232>();
    const uint32_t wgoff = wg * 8192;
    Frag4 frag;
    #pragma unroll
    for (int q = 0; q < 4; q++) frag.o[q] = wid * 2048 + (lane & 15) * 128 + (((2 * q + (lane >> 4)) ^ (lane & 7)) << 4);
    const uint32_t slab = sbase + SM_STG + wid * 2048;

    LnRow ln;
    {
      uint2* const lmail = &g_ln1[(mb * 8 + (lane & 1) * 4 + (j >> 1)) * 16 + (j & 1) * 8 + wid];
      st_rlx_v2(lmail, par ^ 1, par ^ 1, lane < 2);
      mbar_wait(sbase + B_X + 8 * wid, 0, dl);
      PROF(3, tid == 224);
      if (PF2_BYTES) {
        bulk_prefetch(wmod + (size_t)(b * 8 + wid) * (6 * D_) + PF_BYTES / 2, PF2_BYTES);
        bulk_prefetch(wmod + (size_t)(b * 8 + wid) * (6 * D_) + PF_BYTES / 2 + D_, PF2_BYTES);
      }
      float s[2][2] = {{0.f, 0.f}, {0.f, 0.f}}, q2[2][2] = {{0.f, 0.f}, {0.f, 0.f}};
      #pragma unroll
      for (int c = 0; c < 8; c++) {
        const uint4 v = lds128(sbase + SM_XR + wid * 4096 + c * 512 + lane * 16);
        const uint32_t vv[4] = {v.x, v.y, v.z, v.w};
        #pragma unroll
        for (int e = 0; e < 4; e++) {
          const float lo = bf_lo(vv[e]), hi = bf_hi(vv[e]);
          s[c >> 2][0] += lo; s[c >> 2][1] += hi; q2[c >> 2][0] = fmaf(lo, lo, q2[c >> 2][0]); q2[c >> 2][1] = fmaf(hi, hi, q2[c >> 2][1]);
        }
      }
      if (GATE_EARLY) mbar_arrive_if(sbase + B_LN, lane == 0 && s[0][0] != 12345.678f);
      const bool odd = lane & 1;
      float sm = (s[0][0] + s[0][1]), so = (s[1][0] + s[1][1]), qm = (q2[0][0] + q2[0][1]), qo = (q2[1][0] + q2[1][1]);
      { const float a = odd ? so : sm, c = odd ? qo : qm;
        sm = a + __shfl_xor_sync(0xffffffffu, odd ? sm : so, 1); qm = c + __shfl_xor_sync(0xffffffffu, odd ? qm : qo, 1); }
      #pragma unroll
      for (int o = 2; o < 32; o <<= 1) { sm += __shfl_xor_sync(0xffffffffu, sm, o); qm += __shfl_xor_sync(0xffffffffu, qm, o); }
      sm *= (1.f / D_);
      st_rlx_v2(lmail, tagf(fast_rsqrt(fmaxf(qm * (1.f / D_) - sm * sm, 0.f) + 1e-5f), par), tagf(sm, par), lane < 2);
      if (!GATE_EARLY) mbar_arrive_e(sbase + B_LN);
      PROF(4, tid == 224);
    }

    uint4* const halo_out = g_halo + ((mb * 16 + j) * 2 + wg) * 128 + lane;
    const uint4* const halo_in = halo_out - 16 * 256;
    const uint32_t xch = sbase + SM_XCH + wid * 2048 + lane * 16;
    const bool noprev = mb == 0 && warp == 0;
    float a0[64], a1[64];
    uint32_t x2[32];
    Ring r{mode >> 8, 0, 0, dl};
    Frag8 qA, qB, kA, kB, vA, vB, wA, wB;
    {
      float acc[128];
      uint32_t A0[16], A1[16];
      undef_regs(acc);
      const uint32_t tab = sbase + SM_MODT + qd * 16;
      uint4 p[4];
      q_wait(0, sbase, dl);
      mbar_wait(sbase + B_LN, 0, dl);
      const uint2* const lin = &g_ln1[(mb * 8 + wid) * 16 + g];
      uint2 v0 = ld_rlx_v2(lin), v1 = ld_rlx_v2(lin + 8);
      mbar_wait(sbase + B_MOD, 0, dl);
      #pragma unroll
      for (int kk = 0; kk < 4; kk++) q_load(A0, p, kk, sbase + SM_X0, frag, tab);
      while (!poll_done(((bad2(v0.x, v0.y, par) | bad2(v1.x, v1.y, par)) & 1) == 0, dl)) { v0 = ld_rlx_v2(lin); v1 = ld_rlx_v2(lin + 8); }
      ln_row(ln, 0, __uint_as_float(v0.y), __uint_as_float(v0.x));
      ln_row(ln, 1, __uint_as_float(v1.y), __uint_as_float(v1.x));
      PROF(5, tid == 0);
      const int hq0 = (j & 1) ? 4 : j >> 1, hq1 = (j & 1) ? j >> 1 : 4;
      q_step_rs<true>(acc, A0, A1, p, 0, sbase, frag, tab, ln, hq0, true, dl, wg);
      #pragma unroll 1
      for (int u = 1; u < 15; u += 2) {
        q_step_rs<true>(acc, A1, A0, p, u, sbase, frag, tab, ln, hq1, false, dl, wg);
        mbar_arrive_if(sbase + B_STREQ, u == 7 && lane == 0);
        q_step_rs<true>(acc, A0, A1, p, u + 1, sbase, frag, tab, ln, hq0, false, dl, wg);
      }
      q_step_rs<false>(acc, A1, A0, p, 15, sbase, frag, tab, ln, hq1, false, dl, wg);
      mbar_wait(sbase + B_STFREE, 0, dl);
      mbar_arrive_e(sbase + B_STREQ);
      wgmma_wait<0>();
      undef_regs(a0);
      { const uint32_t slot = m_wait(sbase, r); mma_step(a0, slot + wgoff, slot + 16384, true, q_empty(15, sbase)); m_next(r); }
      fence_regs(acc);
      PROF(8, tid == 0);
      sched_fence();
      pack_half(kB, acc, 32, 1); pack_half(vB, acc, 64, 1); transpose8(vB);
      m_step(a0, sbase, wgoff, r);
      sched_fence();
      attn_send(kB, 0, xch - 16384, warp, halo_out, mb < 15); attn_send(vB, 1, xch - 16384, warp, halo_out, mb < 15);
      pack_half(qA, acc, 0, 0); pack_half(qB, acc, 0, 1); pack_half(kA, acc, 32, 0);
      m_step(a0, sbase, wgoff, r);
      sched_fence();
      pack_half(vA, acc, 64, 0); pack_half(wB, acc, 96, 1); pack_half(wA, acc, 96, 0); transpose8(vA);
    }
    uint4 wP[2];
    {
      m_step(a0, sbase, wgoff, r);
      uint4 pv[4];
      attn_recv<4>(pv, 0, xch - 16384, wg, warp, halo_in, mb > 0);
      m_step(a0, sbase, wgoff, r);
      mbar_wait(sbase + B_STFREE, 1, dl);
      transpose8(wB);
      m_step(a0, sbase, wgoff, r);
      attn_check<4>(pv, 0, warp, halo_in, dl);
      wgmma_wait<0>();
      PROF(9, tid == 0);
      float o[2][5][4];
      sched_fence();
      attn_core(qA, qB, kA, kB, vA, vB, pv, pv + 2, noprev, lane, o);
      if (ST0 == 0) { attn_store(o, 0, sbase, frag); attn_store(o, 1, sbase, frag); mbar_arrive_e(sbase + B_STREQ); }
      if (ST0 == 1) attn_store(o, 0, sbase, frag);
      sched_fence();
      bar_sync(NB_CONS, 256);
      PROF(10, tid == 0);
      m_step(a0, sbase, wgoff, r);
      sched_fence();
      if (ST0 == 2) attn_store(o, 0, sbase, frag);
      if (ST0 >= 1) { attn_store(o, 1, sbase, frag); mbar_arrive_e(sbase + B_STREQ); }
      m_step(a0, sbase, wgoff, r);
      sched_fence();
      attn_send(wB, 1, xch, warp, halo_out + 8 * 256, mb < 15);
      transpose8(wA);
      #pragma unroll 1
      for (int i = 8; i < 15; i++) m_step(a0, sbase, wgoff, r);
      attn_recv<2>(wP, 2, xch, wg, warp, halo_in + 8 * 256, mb > 0);
      m_step(a0, sbase, wgoff, r);
    }
    {
      undef_regs(a1);
      {
        const uint32_t slot = m_wait(sbase, r);
        mma_step(a1, slot + wgoff, slot + 16384, true, m_prev(sbase, r), [&] {
          fence_regs(a0);
          pack_half(kB, a0, 32, 1);
          attn_send(kB, 0, xch, warp, halo_out + 8 * 256, mb < 15);
        });
        m_next(r);
      }
      PROF(14, tid == 0);
      sched_fence();
      pack_half(kA, a0, 32, 0); pack_half(qA, a0, 0, 0); pack_half(qB, a0, 0, 1);
      m_step(a1, sbase, wgoff, r);
      attn_check<2>(wP, 2, warp, halo_in + 8 * 256, dl);
      uint4 kP[2];
      attn_recv<2>(kP, 0, xch, wg, warp, halo_in + 8 * 256, mb > 0);
      m_step(a1, sbase, wgoff, r);
      attn_check<2>(kP, 0, warp, halo_in + 8 * 256, dl);
      wgmma_wait<0>();
      PROF(15, tid == 0);
      float o[2][5][4];
      mbar_wait(sbase + B_STFREE, 0, dl);
      attn_core(qA, qB, kA, kB, wA, wB, kP, wP, noprev, lane, o);
      attn_store(o, 0, sbase, frag);
      attn_store(o, 1, sbase, frag);
      mbar_arrive_e(sbase + B_STREQ);
      fence_proxy_async_smem();
      bar_sync(NB_CONS, 256);
      PROF(16, tid == 0);
      #pragma unroll 1
      for (int i = 3; i < 8; i++) m_step(a1, sbase, wgoff, r);
      mma_step(a1, sbase + SM_STG + wgoff, m_wait(sbase, r) + 16384, false, m_prev(sbase, r));
      m_next(r);
      PROF(17, tid == 0);
      #pragma unroll 1
      for (int i = 0; i < 4; i++) { m_step(a1, sbase, wgoff, r); PROF(42, tid == 0 && i == 0); }
      PROF(43, tid == 0);
      const uint32_t xs = m_wait(sbase, r), xe = sbase + B_EM + 8 * r.st;
      PROF(44, tid == 0);
      ring_next(r);
      #pragma unroll
      for (int t = 0; t < 2; t++) {
        #pragma unroll
        for (int jj = 4 * t; jj < 4 * t + 4; jj++) ldmatrix_x4(xs + t * 16384 + frag.o[jj & 3], x2[4 * jj], x2[4 * jj + 1], x2[4 * jj + 2], x2[4 * jj + 3]);
        if (t == 1) mbar_arrive_e(xe);
        m_step(a1, sbase, wgoff, r);
      }
      m_step(a1, sbase, wgoff, r);
      PROF(45, tid == 0);
      mbar_wait(sbase + B_VEC, 0, dl);
      mbar_wait(sbase + B_STFREE, 1, dl);
      const uint32_t vec = sbase + SM_VEC + qd * 16;
      uint4 ga[4];
      #pragma unroll
      for (int q = 0; q < 4; q++) ga[q] = lds128(vec + q * 64);
      wgmma_wait<0>();
      mbar_arrive_e(m_prev(sbase, r));
      fence_regs(a1);
      PROF(18, tid == 0);
      float rs_[4] = {0.f, 0.f, 0.f, 0.f}, gl[4] = {0.f, 0.f, 0.f, 0.f}, gh[4] = {0.f, 0.f, 0.f, 0.f};
      #pragma unroll
      for (int jj = 0; jj < 8; jj++) {
        uint32_t* v = &x2[4 * jj];
        const uint32_t wl = (jj & 1) ? ga[jj >> 1].z : ga[jj >> 1].x, wh = (jj & 1) ? ga[jj >> 1].w : ga[jj >> 1].y;
        #pragma unroll
        for (int e = 0; e < 4; e++) v[e] = fma_bf2(e & 2 ? wh : wl, pack_bf16(a1[8 * jj + 2 * e], a1[8 * jj + 2 * e + 1]), v[e]);
        mma16(rs_, v[0], v[1], v[2], v[3], 0x3F803F80u, 0x3F803F80u);
        mma16(gl, v[0], v[1], v[2], v[3], v[0], v[2]);
        mma16(gh, v[0], v[1], v[2], v[3], v[1], v[3]);
      }
      uint4* const sm = g_st2 + (mb * 8 + wid) * 64 + g;
      st_rlx_v4(sm + j * 8, __float_as_uint(rs_[0]), __float_as_uint(g & 1 ? gl[1] : gl[0]), __float_as_uint(rs_[2]), __float_as_uint(g & 1 ? gh[3] : gh[2]),
                qd == (g >> 1));
      float s[2], q2[2];
      PROF(19, tid == 0);
      uint4 sb[4], cb[4];
      #pragma unroll
      for (int q = 0; q < 4; q++) { sb[q] = lds128(vec + 256 + q * 64); cb[q] = lds128(vec + 512 + q * 64); }
      uint4 p0, p1;
      while (true) {
        p0 = ld_rlx_v4(sm + qd * 16); p1 = ld_rlx_v4(sm + qd * 16 + 8);
        if (poll_done(max(max(max(p0.x, p0.y), max(p0.z, p0.w)), max(max(p1.x, p1.y), max(p1.z, p1.w))) != ~0u, dl)) break;
      }
      PROF(20, tid == 0);
      s[0] = __uint_as_float(p0.x) + __uint_as_float(p1.x); q2[0] = __uint_as_float(p0.y) + __uint_as_float(p1.y);
      s[1] = __uint_as_float(p0.z) + __uint_as_float(p1.z); q2[1] = __uint_as_float(p0.w) + __uint_as_float(p1.w);
      #pragma unroll
      for (int o2 = 1; o2 <= 2; o2 <<= 1)
        #pragma unroll
        for (int h = 0; h < 2; h++) { s[h] += __shfl_xor_sync(0xffffffffu, s[h], o2); q2[h] += __shfl_xor_sync(0xffffffffu, q2[h], o2); }
      #pragma unroll
      for (int h = 0; h < 2; h++) {
        const float m = s[h] * (1.f / D_);
        ln_row(ln, h, m, fast_rsqrt(fmaxf(q2[h] * (1.f / D_) - m * m, 0.f) + 1e-5f));
      }
      #pragma unroll
      for (int jj = 0; jj < 8; jj++) {
        const uint32_t cl = (jj & 1) ? cb[jj >> 1].z : cb[jj >> 1].x, ch = (jj & 1) ? cb[jj >> 1].w : cb[jj >> 1].y;
        const uint32_t sl = (jj & 1) ? sb[jj >> 1].z : sb[jj >> 1].x, sh = (jj & 1) ? sb[jj >> 1].w : sb[jj >> 1].y;
        stmatrix_x4(sbase + SM_STG + (jj >> 2) * 16384 + frag.o[jj & 3], ln_mod(x2[4 * jj], ln, 0, cl, sl), ln_mod(x2[4 * jj + 1], ln, 1, cl, sl),
                    ln_mod(x2[4 * jj + 2], ln, 0, ch, sh), ln_mod(x2[4 * jj + 3], ln, 1, ch, sh));
        if (jj == 3) mbar_arrive_e(sbase + B_STH);
      }
      mbar_arrive_e(sbase + B_STREQ);
      fence_proxy_async_smem();
      bar_sync(NB_WG + wg, 128);
      PROF(21, tid == 0);
    }

    undef_regs(a0);
    #pragma unroll
    for (int t = 0; t < 2; t++) {
      const uint32_t slot = m_wait(sbase, r);
      if (t == 0) mma_step<false>(a0, sbase + SM_STG + wgoff, slot, true, 0);
      else mma_step(a0, sbase + SM_STG + 16384 + wgoff, slot, false, m_prev(sbase, r));
      mma_step<false>(a1, sbase + SM_STG + t * 16384 + wgoff, slot + 16384, t == 0, 0);
      m_next(r);
    }
    PROF(22, tid == 0);
    #pragma unroll 1
    for (int t = 0; t < 7; t += 2) {
      g_switch(a1, a0, t == 0 ? 14 : 11, t > 0, 5 + t, sbase, wgoff, frag, r);
      if (t == 6) break;
      g_switch(a0, a1, t == 0 ? 9 : 11, true, 6 + t, sbase, wgoff, frag, r);
    }
    #pragma unroll 1
    for (int i = 5; i < 56 - DTAIL; i++) m_step(a1, sbase, wgoff, r);
    if (DTAIL) {
      if (wg == 1) { wgmma_wait<0>(); mbar_arrive_e(m_prev(sbase, r)); bar_sync(NB_ORD, 256); }
      #pragma unroll
      for (int i = 0; i < DTAIL; i++) {
        const uint32_t slot = m_wait(sbase, r);
        const uint32_t alo = ((slot + wgoff) >> 4) + (1u << 16), blo = ((slot + 16384) >> 4) + (512u << 16);
        wgmma_fence();
        #pragma unroll
        for (int k = 0; k < 4; k++) wgmma_m64n128k16_ss(a1, desc_from_lo(alo + k * 2), desc_from_lo(blo + k * 128), true);
        wgmma_commit();
        ring_next(r);
      }
      if (wg == 0) bar_arrive(NB_ORD, 256);
    }
    {
      mbar_wait(sbase + B_STFREE, 1, dl);
      mbar_wait(sbase + B_VEC + 8, 0, dl);
      uint4 gb[4];
      #pragma unroll
      for (int q = 0; q < 4; q++) gb[q] = lds128(sbase + SM_VEC + 768 + qd * 16 + q * 64);
      wgmma_wait<0>();
      fence_regs(a1);
      PROF(50, tid == 128);
      #pragma unroll
      for (int t = 0; t < 2; t++) {
        #pragma unroll
        for (int jj = 4 * t; jj < 4 * t + 4; jj++) {
          const uint32_t gl = (jj & 1) ? gb[jj >> 1].z : gb[jj >> 1].x, gh = (jj & 1) ? gb[jj >> 1].w : gb[jj >> 1].y;
          const int i = 8 * jj;
          stmatrix_x4(sbase + SM_STG + t * 16384 + frag.o[jj & 3],
                      fma_bf2(gl, pack_bf16(a1[i], a1[i + 1]), x2[4 * jj]), fma_bf2(gl, pack_bf16(a1[i + 2], a1[i + 3]), x2[4 * jj + 1]),
                      fma_bf2(gh, pack_bf16(a1[i + 4], a1[i + 5]), x2[4 * jj + 2]), fma_bf2(gh, pack_bf16(a1[i + 6], a1[i + 7]), x2[4 * jj + 3]));
        }
        fence_proxy_async_smem();
        tma_store_3d(&maps.out, slab + t * 16384, j * 128 + t * 64, mb * 64 + warp * 16, wg);
      }
      bulk_commit();
      st_rlx(tid == 0 ? flags + FO_EPOCH : &g_flags[FL_EPOCH], e1, j == 0 && (tid == 0 || (tid == 1 && mb == 0)));
      bulk_wait_read0();
      PROFN(51, tid == 128);
    }
  }
}

typedef CUresult (*PFN_encodeTiled)(CUtensorMap*, CUtensorMapDataType, cuuint32_t, void*, const cuuint64_t*, const cuuint64_t*,
                                    const cuuint32_t*, const cuuint32_t*, CUtensorMapInterleave, CUtensorMapSwizzle,
                                    CUtensorMapL2promotion, CUtensorMapFloatOOBfill);

void encode(PFN_encodeTiled fn, CUtensorMap* m, const void* ptr, int rank, const cuuint64_t* dims, const cuuint64_t* strides,
            const cuuint32_t* box) {
  const cuuint32_t es[5] = {1, 1, 1, 1, 1};
  fn(m, CU_TENSOR_MAP_DATA_TYPE_BFLOAT16, rank, const_cast<void*>(ptr), dims, strides, box, es, CU_TENSOR_MAP_INTERLEAVE_NONE,
     CU_TENSOR_MAP_SWIZZLE_128B, CU_TENSOR_MAP_L2_PROMOTION_L2_256B, CU_TENSOR_MAP_FLOAT_OOB_FILL_NONE);
}
void map2d(PFN_encodeTiled fn, CUtensorMap* m, const void* ptr, int cols, int rows, int boxrows) {
  const cuuint64_t dims[2] = {(cuuint64_t)cols, (cuuint64_t)rows}, strides[1] = {(cuuint64_t)cols * 2};
  const cuuint32_t box[2] = {64, (cuuint32_t)boxrows};
  encode(fn, m, ptr, 2, dims, strides, box);
}
void map_w2chunk(PFN_encodeTiled fn, CUtensorMap* m, const void* ptr, int cols, int rows) {
  const cuuint64_t dims[3] = {64, (cuuint64_t)rows, (cuuint64_t)cols / 64}, strides[2] = {(cuuint64_t)cols * 2, 128};
  const cuuint32_t box[3] = {64, 64, 2};
  encode(fn, m, ptr, 3, dims, strides, box);
}
void map_parity(PFN_encodeTiled fn, CUtensorMap* m, const void* ptr, int boxpairs, int boxpar) {
  const cuuint64_t dims[3] = {D_, S_ / 2, 2}, strides[2] = {D_ * 4, D_ * 2};
  const cuuint32_t box[3] = {64, (cuuint32_t)boxpairs, (cuuint32_t)boxpar};
  encode(fn, m, ptr, 3, dims, strides, box);
}

}

extern "C" void kernel_launch(void* const* d_in, const int* in_sizes, int n_in, void* d_out, int out_size) {
  (void)in_sizes; (void)n_in; (void)out_size;
  const bf16* x = (const bf16*)d_in[0];
  const bf16* wqkv = (const bf16*)d_in[1];
  const bf16* wo = (const bf16*)d_in[2];
  const bf16* w1 = (const bf16*)d_in[4];
  const bf16* w3 = (const bf16*)d_in[5];
  const bf16* w2 = (const bf16*)d_in[6];
  const bf16* cvec = (const bf16*)d_in[7];
  const bf16* w_mod = (const bf16*)d_in[8];

  static PFN_encodeTiled fn = nullptr;
  static Maps maps;
  static const void* cached[8] = {};
  static int sms = 0;
  if (!fn) {
    void* p = nullptr; cudaDriverEntryPointQueryResult st;
    cudaGetDriverEntryPoint("cuTensorMapEncodeTiled", &p, cudaEnableDefault, &st);
    fn = (PFN_encodeTiled)p;
    cudaFuncSetAttribute(fused_block_kernel, cudaFuncAttributeMaxDynamicSharedMemorySize, SM_TOTAL);
    int dev = 0;
    cudaGetDevice(&dev);
    cudaDeviceGetAttribute(&sms, cudaDevAttrMultiProcessorCount, dev);
  }
  const void* cur[8] = {x, wqkv, wo, w1, w3, w2, d_out, w_mod};
  bool same = true;
  for (int i = 0; i < 8; i++) same = same && cached[i] == cur[i];
  if (!same) {
    void *o, *h2, *hh;
    cudaGetSymbolAddress(&hh, g_hh); cudaGetSymbolAddress(&o, g_o);
    h2 = o;
    map_parity(fn, &maps.x, x, 64, 2); map_parity(fn, &maps.out, d_out, 16, 1);
    map2d(fn, &maps.o, o, D_, S_, 128); map2d(fn, &maps.h2, h2, D_, S_, 128);
    {
      const cuuint64_t dims[3] = {512, (cuuint64_t)S_, 7}, strides[2] = {1024, (cuuint64_t)S_ * 1024};
      const cuuint32_t box[3] = {64, 128, 1};
      encode(fn, &maps.hh, hh, 3, dims, strides, box);
    }
    {
      const cuuint64_t dims[4] = {64, 1024, 16, 2}, strides[3] = {3072 * 2, 128, 2048};
      const cuuint64_t dimv[4] = {64, 1024, 8, 2}, stridev[3] = {3072 * 2, 128, 1024};
      const cuuint32_t box[4] = {64, 64, 1, 2};
      encode(fn, &maps.wqk, wqkv, 4, dims, strides, box);
      encode(fn, &maps.wvv, wqkv + 2048, 4, dimv, stridev, box);
      const cuuint64_t dim1[4] = {1024, 128, 8, 2}, stride1[3] = {3072 * 2, 128 * 3072 * 2, 2048};
      const cuuint32_t box1[4] = {64, 16, 4, 2};
      encode(fn, &maps.wq1, wqkv, 4, dim1, stride1, box1);
    }
    map_w2chunk(fn, &maps.wo, wo, D_, D_); map_w2chunk(fn, &maps.w2, w2, D_, F_);
    map2d(fn, &maps.w1, w1, F_, D_, 64); map2d(fn, &maps.w3, w3, F_, D_, 64);
    map2d(fn, &maps.wmod, w_mod, 6 * D_, D_, 256);
    for (int i = 0; i < 8; i++) cached[i] = cur[i];
  }
  if (sms >= NCTA + NAUX) {
    fused_block_kernel<<<NCTA + NAUX, 384, SM_TOTAL>>>(maps, x, cvec, w_mod, 0);
  } else {
    fused_block_kernel<<<NAUX, 384, SM_TOTAL>>>(maps, x, cvec, w_mod, 1);
    fused_block_kernel<<<NCTA, 384, SM_TOTAL>>>(maps, x, cvec, w_mod, 2);
  }
}
```

```cpp
#include <cuda.h>
#include <cuda_runtime.h>
#include <cuda_bf16.h>
#include <stdint.h>

namespace {

typedef __nv_bfloat16 bf16;

constexpr int S_ = 2048, D_ = 1024, F_ = 3584;
constexpr int NCTA = 128, NAUX = 4;

__device__ __align__(1024) bf16 g_o[S_ * D_];
__device__ __align__(1024) bf16 g_hh[S_ * F_];
constexpr int FO_EPOCH = 0, FO_O = 1, FO_H2 = 3, FO_H1 = 11;
constexpr int FL_EPOCH = 16 * 32, FL_RESET = FL_EPOCH + 1, FL_LN1 = FL_EPOCH + 2, FL_H2 = FL_EPOCH + 3, FL_O = FL_EPOCH + 4;
struct Mail {
  unsigned flags[32 * 32];
  float mod[8 * 6 * D_];
  uint2 ln1[16 * 8 * 16];
  uint4 halo[16 * 16 * 2 * 4 * 32];
  uint4 st2[16 * 8 * 8 * 8];
};
__device__ __align__(1024) Mail g_mail;

template <int mode>
__device__ __forceinline__ int cta_role() {
  if (mode) return mode == 1 ? NCTA + (blockIdx.x & 3) : blockIdx.x & 127;
  uint32_t sm;
  asm("mov.u32 %0, %%smid;" : "=r"(sm));
  sm = (sm & ~3u) == 12 ? sm + 108 : (sm & ~3u) == 120 ? sm - 108 : sm;
  const int t = sm >> 1;
  int r;
  if (t < 32) r = (t & 7) * 16 + (t >> 3) * 2 + (sm & 1);
  else if (t < 60) r = (1 + (t - 32) % 7) * 16 + 8 + ((t - 32) / 7) * 2 + (sm & 1);
  else if (t < 62) r = NCTA + sm - 120;
  else r = sm - 116;
  return r;
}
#define PROF(slot, on) do {} while (0)
#define PROFN(slot, on) do {} while (0)
#define PROF_OUT(role, t) do {} while (0)
constexpr uint32_t SM_PROF = 0;

__device__ __forceinline__ uint32_t smem_u32(const void* p) { return (uint32_t)__cvta_generic_to_shared(p); }
#define ELECT "{\n.reg .pred p;\nelect.sync _|p, 0xffffffff;\n@p "
__device__ __forceinline__ void mbar_init_e(uint32_t bar, uint32_t count) {
  asm volatile(ELECT "mbarrier.init.shared::cta.b64 [%0], %1;\n}" :: "r"(bar), "r"(count) : "memory");
}
__device__ __forceinline__ void mbar_expect_tx_e(uint32_t bar, uint32_t bytes) {
  asm volatile(ELECT "mbarrier.arrive.expect_tx.shared::cta.b64 _, [%0], %1;\n}" :: "r"(bar), "r"(bytes) : "memory");
}
__device__ __forceinline__ void mbar_arrive_if(uint32_t bar, bool on) {
  asm volatile("{\n.reg .pred p;\nsetp.ne.b32 p, %1, 0;\n@p mbarrier.arrive.shared::cta.b64 _, [%0];\n}" :: "r"(bar), "r"((int)on) : "memory");
}
__device__ __forceinline__ void mbar_arrive_e(uint32_t bar) {
  asm volatile(ELECT "mbarrier.arrive.shared::cta.b64 _, [%0];\n}" :: "r"(bar) : "memory");
}
__device__ __forceinline__ uint32_t clock32() { uint32_t t; asm volatile("mov.u32 %0, %%clock;" : "=r"(t)); return t; }
__device__ __forceinline__ void mbar_wait(uint32_t bar, uint32_t parity, uint32_t dl) {
  asm volatile("{\n.reg .pred p, q;\n.reg .b32 t;\n"
               "mbarrier.try_wait.parity.shared::cta.b64 p, [%0], %1;\n"
               "@p bra LAB_DONE;\n"
               "LAB_WAIT:\n"
               "mbarrier.try_wait.parity.shared::cta.b64 p, [%0], %1;\n"
               "mov.u32 t, %%clock;\n"
               "sub.s32 t, t, %2;\n"
               "setp.lt.and.s32 q, t, 0, !p;\n"
               "@q bra LAB_WAIT;\n"
               "LAB_DONE:\n}" :: "r"(bar), "r"(parity), "r"(dl) : "memory");
}
__device__ __forceinline__ void mbar_sleep(uint32_t bar, uint32_t parity, uint32_t dl) {
  asm volatile("{\n.reg .pred p;\n.reg .b32 t;\n"
               "LAB_WAIT:\n"
               "mbarrier.try_wait.parity.shared::cta.b64 p, [%0], %1, 20000;\n"
               "@p bra LAB_DONE;\n"
               "mov.u32 t, %%clock;\n"
               "sub.s32 t, t, %2;\n"
               "setp.lt.s32 p, t, 0;\n"
               "@p bra LAB_WAIT;\n"
               "LAB_DONE:\n}" :: "r"(bar), "r"(parity), "r"(dl) : "memory");
}
__device__ __forceinline__ bool poll_done(bool ok, uint32_t dl) {
  return __all_sync(0xffffffffu, ok || (int)(clock32() - dl) >= 0);
}
__device__ __forceinline__ unsigned ld_relaxed(const unsigned* p) {
  unsigned v; asm volatile("ld.relaxed.gpu.global.u32 %0, [%1];" : "=r"(v) : "l"(p) : "memory"); return v;
}
__device__ __forceinline__ void red_add_e(unsigned* p, unsigned v) {
  asm volatile(ELECT "red.relaxed.gpu.global.add.u32 [%0], %1;\n}" :: "l"(p), "r"(v) : "memory");
}
__device__ __forceinline__ void wait_flag(const unsigned* p, unsigned target, uint32_t dl) {
  asm volatile("{\n.reg .pred p;\n.reg .b32 t;\n"
               "LAB_WAIT:\n"
               "ld.relaxed.gpu.global.u32 t, [%0];\n"
               "sub.s32 t, t, %1;\n"
               "setp.ge.s32 p, t, 0;\n"
               "@p bra LAB_DONE;\n"
               "mov.u32 t, %%clock;\n"
               "sub.s32 t, t, %2;\n"
               "setp.lt.s32 p, t, 0;\n"
               "@p bra LAB_WAIT;\n"
               "LAB_DONE:\n}" :: "l"(p), "r"(target), "r"(dl) : "memory");
}
__device__ __forceinline__ void wait_until(uint32_t t) { while ((int)(clock32() - t) < 0) {} }
__device__ __forceinline__ void fence_proxy_async_smem() { asm volatile("fence.proxy.async.shared::cta;" ::: "memory"); }

constexpr uint64_t EVICT_FIRST = 0x12F0000000000000ull;
template <bool STREAM = false>
__device__ __forceinline__ void tma_load_2d(uint32_t dst, const CUtensorMap* m, uint32_t bar, int c0, int c1) {
  if (STREAM)
    asm volatile(ELECT "cp.async.bulk.tensor.2d.shared::cluster.global.mbarrier::complete_tx::bytes.L2::cache_hint [%0], [%1, {%3, %4}], [%2], %5;\n}"
                 :: "r"(dst), "l"(m), "r"(bar), "r"(c0), "r"(c1), "l"(EVICT_FIRST) : "memory");
  else
    asm volatile(ELECT "cp.async.bulk.tensor.2d.shared::cluster.global.mbarrier::complete_tx::bytes [%0], [%1, {%3, %4}], [%2];\n}"
                 :: "r"(dst), "l"(m), "r"(bar), "r"(c0), "r"(c1) : "memory");
}
template <bool STREAM = false>
__device__ __forceinline__ void tma_load_3d(uint32_t dst, const CUtensorMap* m, uint32_t bar, int c0, int c1, int c2) {
  if (STREAM)
    asm volatile(ELECT "cp.async.bulk.tensor.3d.shared::cluster.global.mbarrier::complete_tx::bytes.L2::cache_hint [%0], [%1, {%3, %4, %5}], [%2], %6;\n}"
                 :: "r"(dst), "l"(m), "r"(bar), "r"(c0), "r"(c1), "r"(c2), "l"(EVICT_FIRST) : "memory");
  else
    asm volatile(ELECT "cp.async.bulk.tensor.3d.shared::cluster.global.mbarrier::complete_tx::bytes [%0], [%1, {%3, %4, %5}], [%2];\n}"
                 :: "r"(dst), "l"(m), "r"(bar), "r"(c0), "r"(c1), "r"(c2) : "memory");
}
template <bool STREAM = false>
__device__ __forceinline__ void tma_load_4d(uint32_t dst, const CUtensorMap* m, uint32_t bar, int c0, int c1, int c2, int c3) {
  if (STREAM)
    asm volatile(ELECT "cp.async.bulk.tensor.4d.shared::cluster.global.mbarrier::complete_tx::bytes.L2::cache_hint [%0], [%1, {%3, %4, %5, %6}], [%2], %7;\n}"
                 :: "r"(dst), "l"(m), "r"(bar), "r"(c0), "r"(c1), "r"(c2), "r"(c3), "l"(EVICT_FIRST) : "memory");
  else
    asm volatile(ELECT "cp.async.bulk.tensor.4d.shared::cluster.global.mbarrier::complete_tx::bytes [%0], [%1, {%3, %4, %5, %6}], [%2];\n}"
                 :: "r"(dst), "l"(m), "r"(bar), "r"(c0), "r"(c1), "r"(c2), "r"(c3) : "memory");
}
__device__ __forceinline__ void tma_store_2d(const CUtensorMap* m, uint32_t src, int c0, int c1) {
  asm volatile(ELECT "cp.async.bulk.tensor.2d.global.shared::cta.bulk_group [%0, {%2, %3}], [%1];\n}"
               :: "l"(m), "r"(src), "r"(c0), "r"(c1) : "memory");
}
__device__ __forceinline__ void tma_store_3d(const CUtensorMap* m, uint32_t src, int c0, int c1, int c2) {
  asm volatile(ELECT "cp.async.bulk.tensor.3d.global.shared::cta.bulk_group [%0, {%2, %3, %4}], [%1];\n}"
               :: "l"(m), "r"(src), "r"(c0), "r"(c1), "r"(c2) : "memory");
}
__device__ __forceinline__ void bulk_load(uint32_t dst, const void* src, uint32_t bytes, uint32_t bar) {
  asm volatile(ELECT "cp.async.bulk.shared::cluster.global.mbarrier::complete_tx::bytes [%0], [%1], %2, [%3];\n}"
               :: "r"(dst), "l"(src), "r"(bytes), "r"(bar) : "memory");
}
__device__ __forceinline__ void bulk_prefetch(const void* src, uint32_t bytes) {
  asm volatile(ELECT "cp.async.bulk.prefetch.L2.global [%0], %1;\n}" :: "l"(src), "r"(bytes) : "memory");
}
__device__ __forceinline__ void bulk_commit() { asm volatile("cp.async.bulk.commit_group;" ::: "memory"); }
__device__ __forceinline__ void bulk_wait0() { asm volatile("cp.async.bulk.wait_group 0;" ::: "memory"); }
__device__ __forceinline__ void bulk_wait_read0() { asm volatile("cp.async.bulk.wait_group.read 0;" ::: "memory"); }
__device__ __forceinline__ void prefetch_tmap(const CUtensorMap* m) { asm volatile(ELECT "prefetch.tensormap [%0];\n}" :: "l"(m) : "memory"); }
__device__ __forceinline__ void wgmma_fence() { asm volatile("wgmma.fence.sync.aligned;" ::: "memory"); }
__device__ __forceinline__ void wgmma_commit() { asm volatile("wgmma.commit_group.sync.aligned;" ::: "memory"); }
template <int N> __device__ __forceinline__ void wgmma_wait() { asm volatile("wgmma.wait_group.sync.aligned %0;" :: "n"(N) : "memory"); }
template <int R> __device__ __forceinline__ void reg_alloc() { asm volatile("setmaxnreg.inc.sync.aligned.u32 %0;" :: "n"(R)); }
template <int R> __device__ __forceinline__ void reg_dealloc() { asm volatile("setmaxnreg.dec.sync.aligned.u32 %0;" :: "n"(R)); }
__device__ __forceinline__ void bar_sync(int id, int n) { asm volatile("bar.sync %0, %1;" :: "r"(id), "r"(n) : "memory"); }
__device__ __forceinline__ void bar_arrive(int id, int n) { asm volatile("bar.arrive %0, %1;" :: "r"(id), "r"(n) : "memory"); }
__device__ __forceinline__ void sched_fence() {
  asm volatile("{\n.reg .pred p;\n.reg .b32 t;\nLAB_F:\nmov.u32 t, %%clock;\nsetp.eq.u32 p, t, %0;\n@p bra LAB_F;\n}" :: "n"(0) : "memory");
}
template <int N> __device__ __forceinline__ void fence_regs(float (&a)[N]) {
  #pragma unroll
  for (int i = 0; i < N; i++) asm volatile("" : "+f"(a[i]) :: "memory");
}
template <int N> __device__ __forceinline__ void undef_regs(float (&a)[N]) {
  #pragma unroll
  for (int i = 0; i < N; i++) asm volatile("" : "=f"(a[i]));
}

__device__ __forceinline__ uint64_t desc_from_lo(uint32_t lo) { return (uint64_t)lo | ((uint64_t)0x40000040u << 32); }
__device__ __forceinline__ uint32_t pack_bf16(float lo, float hi) {
  uint32_t r; asm("cvt.rn.bf16x2.f32 %0, %1, %2;" : "=r"(r) : "f"(hi), "f"(lo)); return r;
}
__device__ __forceinline__ uint32_t fma_bf2(uint32_t a, uint32_t b, uint32_t c) {
  uint32_t d; asm("fma.rn.bf16x2 %0, %1, %2, %3;" : "=r"(d) : "r"(a), "r"(b), "r"(c)); return d;
}
__device__ __forceinline__ float bf_lo(uint32_t v) { return __uint_as_float(v << 16); }
__device__ __forceinline__ float bf_hi(uint32_t v) { return __uint_as_float(v & 0xFFFF0000u); }
__device__ __forceinline__ float bf16_round(float x) { return bf_lo(pack_bf16(x, 0.f)); }
__device__ __forceinline__ void stmatrix_x4(uint32_t addr, uint32_t r0, uint32_t r1, uint32_t r2, uint32_t r3) {
  asm volatile("stmatrix.sync.aligned.m8n8.x4.shared.b16 [%0], {%1, %2, %3, %4};" :: "r"(addr), "r"(r0), "r"(r1), "r"(r2), "r"(r3) : "memory");
}
__device__ __forceinline__ void stmatrix_x4_if(uint32_t addr, uint32_t r0, uint32_t r1, uint32_t r2, uint32_t r3, bool on) {
  asm volatile("{\n.reg .pred p;\nsetp.ne.b32 p, %5, 0;\n@p stmatrix.sync.aligned.m8n8.x4.shared.b16 [%0], {%1, %2, %3, %4};\n}"
               :: "r"(addr), "r"(r0), "r"(r1), "r"(r2), "r"(r3), "r"((int)on) : "memory");
}
__device__ __forceinline__ void ldmatrix_x4(uint32_t addr, uint32_t& r0, uint32_t& r1, uint32_t& r2, uint32_t& r3) {
  asm volatile("ldmatrix.sync.aligned.m8n8.x4.shared.b16 {%0, %1, %2, %3}, [%4];" : "=r"(r0), "=r"(r1), "=r"(r2), "=r"(r3) : "r"(addr) : "memory");
}
__device__ __forceinline__ void ldmatrix_x4_t(uint32_t addr, uint32_t (&r)[4]) {
  asm volatile("ldmatrix.sync.aligned.m8n8.x4.trans.shared.b16 {%0, %1, %2, %3}, [%4];" : "=r"(r[0]), "=r"(r[1]), "=r"(r[2]), "=r"(r[3]) : "r"(addr) : "memory");
}
__device__ __forceinline__ uint32_t tagf(float v, unsigned par) { return (__float_as_uint(v) & ~1u) | par; }
__device__ __forceinline__ void st_rlx(void* p, uint32_t a, bool on) {
  asm volatile("{\n.reg .pred p;\nsetp.ne.b32 p, %2, 0;\n@p st.relaxed.gpu.global.u32 [%0], %1;\n}" :: "l"(p), "r"(a), "r"((int)on) : "memory");
}
__device__ __forceinline__ void st_rlx_v2(void* p, uint32_t a, uint32_t b, bool on) {
  asm volatile("{\n.reg .pred p;\nsetp.ne.b32 p, %3, 0;\n@p st.relaxed.gpu.global.v2.u32 [%0], {%1, %2};\n}" :: "l"(p), "r"(a), "r"(b), "r"((int)on) : "memory");
}
__device__ __forceinline__ uint2 ld_rlx_v2(const void* p) {
  uint2 v; asm volatile("ld.relaxed.gpu.global.v2.u32 {%0,%1}, [%2];" : "=r"(v.x), "=r"(v.y) : "l"(p) : "memory"); return v;
}
__device__ __forceinline__ void st_rlx_v4(void* p, uint32_t a, uint32_t b, uint32_t c, uint32_t d, bool on) {
  asm volatile("{\n.reg .pred p;\nsetp.ne.b32 p, %5, 0;\n@p st.relaxed.gpu.global.v4.u32 [%0], {%1, %2, %3, %4};\n}"
               :: "l"(p), "r"(a), "r"(b), "r"(c), "r"(d), "r"((int)on) : "memory");
}
__device__ __forceinline__ uint4 ld_rlx_v4(const void* p) {
  uint4 v; asm volatile("ld.relaxed.gpu.global.v4.u32 {%0,%1,%2,%3}, [%4];" : "=r"(v.x), "=r"(v.y), "=r"(v.z), "=r"(v.w) : "l"(p) : "memory"); return v;
}
__device__ __forceinline__ uint32_t movmatrix_t(uint32_t a) {
  uint32_t d; asm volatile("movmatrix.sync.aligned.m8n8.trans.b16 %0, %1;" : "=r"(d) : "r"(a)); return d;
}
__device__ __forceinline__ void mma16(float (&c)[4], uint32_t a0, uint32_t a1, uint32_t a2, uint32_t a3, uint32_t b0, uint32_t b1) {
  asm volatile("mma.sync.aligned.m16n8k16.row.col.f32.bf16.bf16.f32 {%0,%1,%2,%3}, {%4,%5,%6,%7}, {%8,%9}, {%0,%1,%2,%3};"
               : "+f"(c[0]), "+f"(c[1]), "+f"(c[2]), "+f"(c[3]) : "r"(a0), "r"(a1), "r"(a2), "r"(a3), "r"(b0), "r"(b1));
}
__device__ __forceinline__ void mma8(float (&c)[4], uint32_t a0, uint32_t a1, uint32_t b0) {
  asm volatile("mma.sync.aligned.m16n8k8.row.col.f32.bf16.bf16.f32 {%0,%1,%2,%3}, {%4,%5}, {%6}, {%0,%1,%2,%3};"
               : "+f"(c[0]), "+f"(c[1]), "+f"(c[2]), "+f"(c[3]) : "r"(a0), "r"(a1), "r"(b0));
}
__device__ __forceinline__ void sts128(uint32_t addr, uint32_t a, uint32_t b, uint32_t c, uint32_t d) {
  asm volatile("st.shared.v4.b32 [%0], {%1,%2,%3,%4};" :: "r"(addr), "r"(a), "r"(b), "r"(c), "r"(d) : "memory");
}
__device__ __forceinline__ uint4 lds128(uint32_t addr) {
  uint4 v; asm volatile("ld.shared.v4.b32 {%0,%1,%2,%3}, [%4];" : "=r"(v.x), "=r"(v.y), "=r"(v.z), "=r"(v.w) : "r"(addr) : "memory"); return v;
}
__device__ __forceinline__ uint32_t lds32(uint32_t addr) {
  uint32_t v; asm volatile("ld.shared.b32 %0, [%1];" : "=r"(v) : "r"(addr) : "memory"); return v;
}
__device__ __forceinline__ float2 lds64f(uint32_t addr) {
  float2 v; asm volatile("ld.shared.v2.f32 {%0,%1}, [%2];" : "=f"(v.x), "=f"(v.y) : "r"(addr) : "memory"); return v;
}
__device__ __forceinline__ void sts64(uint32_t addr, uint32_t a, uint32_t b) {
  asm volatile("st.shared.v2.b32 [%0], {%1, %2};" :: "r"(addr), "r"(a), "r"(b) : "memory");
}
__device__ __forceinline__ float fast_ex2(float x) { float y; asm("ex2.approx.ftz.f32 %0, %1;" : "=f"(y) : "f"(x)); return y; }
__device__ __forceinline__ float fast_rcp(float x) { float y; asm("rcp.approx.ftz.f32 %0, %1;" : "=f"(y) : "f"(x)); return y; }
__device__ __forceinline__ float fast_rsqrt(float x) { float y; asm("rsqrt.approx.ftz.f32 %0, %1;" : "=f"(y) : "f"(x)); return y; }
__device__ __forceinline__ float silu_f(float g) { return g * fast_rcp(1.f + fast_ex2(g * -1.4426950408889634f)); }
__device__ __forceinline__ float swiglu(float g, float u) {
  const float h = 0.5f * g;
  float t; asm("tanh.approx.f32 %0, %1;" : "=f"(t) : "f"(h));
  return fmaf(h, t, h) * u;
}

__device__ __forceinline__ void wgmma_m64n128k16_ss(float (&d)[64], uint64_t descA, uint64_t descB, int scaleD) {
  asm volatile("{\n.reg .pred p;\nsetp.ne.b32 p, %66, 0;\n"
    "wgmma.mma_async.sync.aligned.m64n128k16.f32.bf16.bf16 "
    "{%0, %1, %2, %3, %4, %5, %6, %7, %8, %9, %10, %11, %12, %13, %14, %15, "
    "%16, %17, %18, %19, %20, %21, %22, %23, %24, %25, %26, %27, %28, %29, %30, %31, "
    "%32, %33, %34, %35, %36, %37, %38, %39, %40, %41, %42, %43, %44, %45, %46, %47, "
    "%48, %49, %50, %51, %52, %53, %54, %55, %56, %57, %58, %59, %60, %61, %62, %63}, "
    "%64, %65, p, 1, 1, 0, 1;\n}\n"
    : "+f"(d[0]), "+f"(d[1]), "+f"(d[2]), "+f"(d[3]), "+f"(d[4]), "+f"(d[5]), "+f"(d[6]), "+f"(d[7]),
      "+f"(d[8]), "+f"(d[9]), "+f"(d[10]), "+f"(d[11]), "+f"(d[12]), "+f"(d[13]), "+f"(d[14]), "+f"(d[15]),
      "+f"(d[16]), "+f"(d[17]), "+f"(d[18]), "+f"(d[19]), "+f"(d[20]), "+f"(d[21]), "+f"(d[22]), "+f"(d[23]),
      "+f"(d[24]), "+f"(d[25]), "+f"(d[26]), "+f"(d[27]), "+f"(d[28]), "+f"(d[29]), "+f"(d[30]), "+f"(d[31]),
      "+f"(d[32]), "+f"(d[33]), "+f"(d[34]), "+f"(d[35]), "+f"(d[36]), "+f"(d[37]), "+f"(d[38]), "+f"(d[39]),
      "+f"(d[40]), "+f"(d[41]), "+f"(d[42]), "+f"(d[43]), "+f"(d[44]), "+f"(d[45]), "+f"(d[46]), "+f"(d[47]),
      "+f"(d[48]), "+f"(d[49]), "+f"(d[50]), "+f"(d[51]), "+f"(d[52]), "+f"(d[53]), "+f"(d[54]), "+f"(d[55]),
      "+f"(d[56]), "+f"(d[57]), "+f"(d[58]), "+f"(d[59]), "+f"(d[60]), "+f"(d[61]), "+f"(d[62]), "+f"(d[63])
    : "l"(descA), "l"(descB), "r"(scaleD));
}
__device__ __forceinline__ void wgmma_m64n256k16_rs(float (&d)[128], uint32_t a0, uint32_t a1, uint32_t a2, uint32_t a3, uint64_t descB, int scaleD) {
  asm volatile("{\n.reg .pred p;\nsetp.ne.b32 p, %133, 0;\n"
    "wgmma.mma_async.sync.aligned.m64n256k16.f32.bf16.bf16 "
    "{%0, %1, %2, %3, %4, %5, %6, %7, %8, %9, %10, %11, %12, %13, %14, %15, "
    "%16, %17, %18, %19, %20, %21, %22, %23, %24, %25, %26, %27, %28, %29, %30, %31, "
    "%32, %33, %34, %35, %36, %37, %38, %39, %40, %41, %42, %43, %44, %45, %46, %47, "
    "%48, %49, %50, %51, %52, %53, %54, %55, %56, %57, %58, %59, %60, %61, %62, %63, "
    "%64, %65, %66, %67, %68, %69, %70, %71, %72, %73, %74, %75, %76, %77, %78, %79, "
    "%80, %81, %82, %83, %84, %85, %86, %87, %88, %89, %90, %91, %92, %93, %94, %95, "
    "%96, %97, %98, %99, %100, %101, %102, %103, %104, %105, %106, %107, %108, %109, %110, %111, "
    "%112, %113, %114, %115, %116, %117, %118, %119, %120, %121, %122, %123, %124, %125, %126, %127}, "
    "{%128, %129, %130, %131}, %132, p, 1, 1, 1;\n}\n"
    : "+f"(d[0]), "+f"(d[1]), "+f"(d[2]), "+f"(d[3]), "+f"(d[4]), "+f"(d[5]), "+f"(d[6]), "+f"(d[7]),
      "+f"(d[8]), "+f"(d[9]), "+f"(d[10]), "+f"(d[11]), "+f"(d[12]), "+f"(d[13]), "+f"(d[14]), "+f"(d[15]),
      "+f"(d[16]), "+f"(d[17]), "+f"(d[18]), "+f"(d[19]), "+f"(d[20]), "+f"(d[21]), "+f"(d[22]), "+f"(d[23]),
      "+f"(d[24]), "+f"(d[25]), "+f"(d[26]), "+f"(d[27]), "+f"(d[28]), "+f"(d[29]), "+f"(d[30]), "+f"(d[31]),
      "+f"(d[32]), "+f"(d[33]), "+f"(d[34]), "+f"(d[35]), "+f"(d[36]), "+f"(d[37]), "+f"(d[38]), "+f"(d[39]),
      "+f"(d[40]), "+f"(d[41]), "+f"(d[42]), "+f"(d[43]), "+f"(d[44]), "+f"(d[45]), "+f"(d[46]), "+f"(d[47]),
      "+f"(d[48]), "+f"(d[49]), "+f"(d[50]), "+f"(d[51]), "+f"(d[52]), "+f"(d[53]), "+f"(d[54]), "+f"(d[55]),
      "+f"(d[56]), "+f"(d[57]), "+f"(d[58]), "+f"(d[59]), "+f"(d[60]), "+f"(d[61]), "+f"(d[62]), "+f"(d[63]),
      "+f"(d[64]), "+f"(d[65]), "+f"(d[66]), "+f"(d[67]), "+f"(d[68]), "+f"(d[69]), "+f"(d[70]), "+f"(d[71]),
      "+f"(d[72]), "+f"(d[73]), "+f"(d[74]), "+f"(d[75]), "+f"(d[76]), "+f"(d[77]), "+f"(d[78]), "+f"(d[79]),
      "+f"(d[80]), "+f"(d[81]), "+f"(d[82]), "+f"(d[83]), "+f"(d[84]), "+f"(d[85]), "+f"(d[86]), "+f"(d[87]),
      "+f"(d[88]), "+f"(d[89]), "+f"(d[90]), "+f"(d[91]), "+f"(d[92]), "+f"(d[93]), "+f"(d[94]), "+f"(d[95]),
      "+f"(d[96]), "+f"(d[97]), "+f"(d[98]), "+f"(d[99]), "+f"(d[100]), "+f"(d[101]), "+f"(d[102]), "+f"(d[103]),
      "+f"(d[104]), "+f"(d[105]), "+f"(d[106]), "+f"(d[107]), "+f"(d[108]), "+f"(d[109]), "+f"(d[110]), "+f"(d[111]),
      "+f"(d[112]), "+f"(d[113]), "+f"(d[114]), "+f"(d[115]), "+f"(d[116]), "+f"(d[117]), "+f"(d[118]), "+f"(d[119]),
      "+f"(d[120]), "+f"(d[121]), "+f"(d[122]), "+f"(d[123]), "+f"(d[124]), "+f"(d[125]), "+f"(d[126]), "+f"(d[127])
    : "r"(a0), "r"(a1), "r"(a2), "r"(a3), "l"(descB), "r"(scaleD));
}

constexpr uint32_t MSLOT = 32768, QSLOT = 49152;
constexpr int NM = 6;
constexpr uint32_t SM_X0 = 3 * QSLOT;
constexpr uint32_t SM_XR = SM_X0 + 16384;
constexpr uint32_t SM_STG = 196608;
constexpr uint32_t SM_XCH = SM_STG + 16384;
constexpr uint32_t SM_BAR = SM_STG + 32768;
constexpr uint32_t SM_VEC = SM_BAR + 512;
constexpr uint32_t SM_MODT = SM_VEC;
constexpr uint32_t SM_TOTAL = SM_VEC + 2048;
constexpr uint32_t B_X = SM_BAR  , B_EQ = B_X + 64, B_EM = B_EQ + 32, B_STREQ = B_EM + 48, B_STH = B_STREQ + 8, B_LN = B_STH + 8,
                   B_FQ = B_LN + 8, B_FM = B_FQ + 32, B_MOD = B_FM + 48, B_GATE = B_MOD + 8, B_STFREE = B_GATE + 8, B_VEC = B_STFREE + 8  ,
                   B_FLG = B_VEC + 16  , B_END = B_FLG + 88;
constexpr int NB_WG = 1  , NB_CONS = 3, NB_ORD = 4  ;
#define PF_BYTES 512
#define X_S1 8
#define X_POLL 5
#define SVC_WAIT mbar_sleep
#define PRD_WAIT mbar_wait
#define WPRE 2
#define HOLD1 1
#define HOLD2 0
#define ST0 0
#define QORD 2
#define QPOS 1
#define AUX_SLOW 68
#define AUX_GAP 500
#define DTAIL 4
#define EF 7
#define TRG_WAIT mbar_wait
#define ST_SPIN0 2
#define AUX_HOLD 3200
#define X_UP 1
#define X_GAP 250

struct Maps {
  CUtensorMap x, out;
  CUtensorMap o, h2, hh;
  CUtensorMap wqk, wvv, wq1, wo, w1, w3, w2;
  CUtensorMap wmod;
};

struct Ring { int st; uint32_t ph; int prev; uint32_t dl; };
__device__ __forceinline__ void ring_next(Ring& r) { if (++r.st == NM) { r.st = 0; r.ph ^= 1; } }

__device__ __forceinline__ void retire_prev(uint32_t rel, bool on) {
  wgmma_commit();
  wgmma_wait<1>();
  if (on) mbar_arrive_e(rel);
}
struct Nop { __device__ __forceinline__ void operator()() const {} };
template <bool REL = true, class F = Nop>
__device__ __forceinline__ void mma_step(float (&acc)[64], uint32_t a, uint32_t b, bool first, uint32_t rel, F urgent = F()) {
  const uint32_t alo = (a >> 4) + (1u << 16), blo = (b >> 4) + (512u << 16);
  wgmma_fence();
  #pragma unroll
  for (int k = 0; k < 4; k++) {
    wgmma_m64n128k16_ss(acc, desc_from_lo(alo + k * 2), desc_from_lo(blo + k * 128), k > 0 || !first);
    if (k == 0) { retire_prev(rel, REL); urgent(); }
  }
  wgmma_commit();
}
__device__ __forceinline__ uint32_t m_wait(uint32_t sbase, const Ring& r) {
  mbar_wait(sbase + B_FM + 8 * r.st, r.ph, r.dl);
  return sbase + r.st * MSLOT;
}
__device__ __forceinline__ uint32_t m_prev(uint32_t sbase, const Ring& r) { return sbase + B_EM + 8 * r.prev; }
__device__ __forceinline__ void m_next(Ring& r) { r.prev = r.st; ring_next(r); }
__device__ __forceinline__ void m_step(float (&acc)[64], uint32_t sbase, uint32_t wgoff, Ring& r, bool first = false) {
  const uint32_t slot = m_wait(sbase, r);
  mma_step(acc, slot + wgoff, slot + 16384, first, m_prev(sbase, r));
  m_next(r);
}

struct LnRow { uint32_t rs[2], nb[2]; };
__device__ __forceinline__ void ln_row(LnRow& l, int h, float mean, float rstd) {
  l.rs[h] = pack_bf16(rstd, rstd);
  const float nb = -mean * bf_lo(l.rs[h]);
  l.nb[h] = pack_bf16(nb, nb);
}
__device__ __forceinline__ uint32_t ln_mod(uint32_t x, const LnRow& l, int h, uint32_t c1, uint32_t s) {
  return fma_bf2(fma_bf2(x, l.rs[h], l.nb[h]), c1, s);
}

__device__ __forceinline__ uint32_t q_wait(int u, uint32_t sbase, uint32_t dl) {
  mbar_wait(sbase + B_FQ + 8 * (u & 3), (u >> 2) & 1, dl);
  return sbase + (u & 3) * QSLOT;
}
__device__ __forceinline__ uint32_t q_empty(int u, uint32_t sbase) { return sbase + B_EQ + 8 * (u & 3); }
struct Frag4 { uint32_t o[4]; };
__device__ __forceinline__ void q_load(uint32_t (&A)[16], uint4 (&p)[4], int kk, uint32_t tile, const Frag4& f, uint32_t t) {
  ldmatrix_x4(tile + f.o[kk], A[4 * kk], A[4 * kk + 1], A[4 * kk + 2], A[4 * kk + 3]);
  p[kk] = lds128(t + kk * 64);
}
__device__ __forceinline__ void q_norm(uint32_t (&A)[16], const uint4 (&p)[4], int kk, const LnRow& l) {
  A[4 * kk + 0] = ln_mod(A[4 * kk + 0], l, 0, p[kk].x, p[kk].z); A[4 * kk + 1] = ln_mod(A[4 * kk + 1], l, 1, p[kk].x, p[kk].z);
  A[4 * kk + 2] = ln_mod(A[4 * kk + 2], l, 0, p[kk].y, p[kk].w); A[4 * kk + 3] = ln_mod(A[4 * kk + 3], l, 1, p[kk].y, p[kk].w);
}
template <bool NEXT>
__device__ __forceinline__ void q_step_rs(float (&acc)[128], uint32_t (&A)[16], uint32_t (&N)[16], uint4 (&p)[4], int u, uint32_t sbase,
                                          const Frag4& f, uint32_t tab, const LnRow& l, int hq, bool first, uint32_t dl, int wg) {
  const uint32_t slot = first ? sbase : q_wait(u, sbase, dl);
  const uint32_t blo = ((slot + 16384) >> 4) + (512u << 16), t = tab + ((u + 1) & 7) * 256;
  #pragma unroll
  for (int kk = 0; kk < 4; kk++) q_norm(A, p, kk, l);
  if (first) {
    #pragma unroll
    for (int i = 0; i < 16; i++) asm volatile("" : "+r"(A[i]));
    mbar_wait(sbase + B_GATE, 0, dl);
    PROF(6, threadIdx.x == 0);
  }
  if (QORD == 1 && first && wg == 1) bar_sync(NB_ORD, 256);
  if (QORD == 2 && !(first && wg == 0)) bar_sync(NB_ORD + wg, 256);
  wgmma_fence();
  #pragma unroll
  for (int kk = 0; kk < 4; kk++) {
    wgmma_m64n256k16_rs(acc, A[4 * kk], A[4 * kk + 1], A[4 * kk + 2], A[4 * kk + 3], desc_from_lo(blo + kk * 128), kk > 0 || !first);
    if (kk == 0) retire_prev(q_empty(u - 1, sbase), !first);
    if (NEXT && kk < 2) { q_load(N, p, 2 * kk, slot, f, t); q_load(N, p, 2 * kk + 1, slot, f, t); }
    if (QORD == 1 && first && kk == QPOS && wg == 0) bar_arrive(NB_ORD, 256);
    if (QORD == 2 && kk == QPOS && (NEXT || wg == 0)) bar_arrive(NB_ORD + (wg ^ 1), 256);
    if (kk == 1) {
      const uint32_t dst = sbase + SM_STG + (u >> 3) * 16384 + (f.o[0] ^ ((u & 6) << 4));
      #pragma unroll
      for (int q = 0; q < 4; q++) stmatrix_x4_if(dst, A[4 * q], A[4 * q + 1], A[4 * q + 2], A[4 * q + 3], hq == q);
    }
  }
  wgmma_commit();
}

typedef uint32_t Frag8[8];
template <int N> __device__ __forceinline__ void pack_half(Frag8& f, const float (&acc)[N], int off, int half) {
  #pragma unroll
  for (int e = 0; e < 8; e++) { f[e] = pack_bf16(acc[off + 4 * e + 2 * half], acc[off + 4 * e + 2 * half + 1]); asm volatile("" : "+r"(f[e])); }
}
__device__ __forceinline__ void transpose8(Frag8& f) {
  #pragma unroll
  for (int e = 0; e < 8; e++) f[e] = movmatrix_t(f[e]);
}
__device__ __forceinline__ void attn_send(const Frag8& f, int kv, uint32_t xch, int warp, uint4* halo_out, bool has_next) {
  if (warp == 3) {
    st_rlx_v4(halo_out + kv * 64, f[0], f[1], f[2], f[3], has_next); st_rlx_v4(halo_out + kv * 64 + 32, f[4], f[5], f[6], f[7], has_next);
  } else {
    sts128(xch + 2048 + kv * 1024, f[0], f[1], f[2], f[3]); sts128(xch + 2048 + kv * 1024 + 512, f[4], f[5], f[6], f[7]);
  }
}
template <int N>
__device__ __forceinline__ void attn_recv(uint4* p, int first, uint32_t xch, int wg, int warp, const uint4* halo_in, bool has_prev) {
  bar_sync(NB_WG + wg, 128);
  #pragma unroll
  for (int e = 0; e < N; e++)
    asm volatile("{\n.reg .pred p, q;\nsetp.ne.b32 p, %6, 0;\nsetp.ne.b32 q, %7, 0;\n"
                 "mov.b32 %0, 0;\nmov.b32 %1, 0;\nmov.b32 %2, 0;\nmov.b32 %3, 0;\n"
                 "@p ld.shared.v4.b32 {%0,%1,%2,%3}, [%4];\n@q ld.relaxed.gpu.global.v4.u32 {%0,%1,%2,%3}, [%5];\n}"
                 : "=&r"(p[e].x), "=&r"(p[e].y), "=&r"(p[e].z), "=&r"(p[e].w)
                 : "r"(xch + (first + e) * 512), "l"(halo_in + (first + e) * 32), "r"((int)(warp > 0)), "r"((int)(warp == 0 && has_prev)) : "memory");
}
template <int N>
__device__ __forceinline__ void attn_check(uint4* p, int first, int warp, const uint4* halo_in, uint32_t dl) {
  if (warp == 0) {
    while (true) {
      uint32_t m = 0;
      #pragma unroll
      for (int e = 0; e < N; e++) m = max(max(m, max(p[e].x, p[e].y)), max(p[e].z, p[e].w));
      if (poll_done(m != ~0u, dl)) break;
      #pragma unroll
      for (int e = 0; e < N; e++) p[e] = ld_rlx_v4(halo_in + (first + e) * 32);
    }
  }
}
__device__ __forceinline__ void attn_core(const Frag8& qA, const Frag8& qB, const Frag8& kA, const Frag8& kB, const Frag8& vA, const Frag8& vB,
                                          const uint4* kP, const uint4* vP, bool noprev, int lane, float (&o)[2][5][4]) {
  const int g = lane >> 2, qd = lane & 3;
  const bool s0 = 2 * qd > g, s1 = 2 * qd + 1 > g;
  const uint32_t msk = (s0 ? 0xFFFFu : 0u) | (s1 ? 0xFFFF0000u : 0u);
  constexpr float SC = 0.17677669529663687f * 1.4426950408889634f;
  float s[2][3][4];
  #pragma unroll
  for (int h = 0; h < 2; h++)
    #pragma unroll
    for (int nb = 0; nb < 3; nb++) s[h][nb][0] = s[h][nb][1] = s[h][nb][2] = s[h][nb][3] = 0.f;
  #pragma unroll
  for (int kk = 0; kk < 2; kk++)
    #pragma unroll
    for (int h = 0; h < 2; h++) {
      const int e = 4 * h + 2 * kk;
      mma16(s[h][1], qA[e], qB[e], qA[e + 1], qB[e + 1], kA[e], kA[e + 1]);
      mma16(s[h][2], qA[e], qB[e], qA[e + 1], qB[e + 1], kB[e], kB[e + 1]);
      mma16(s[h][0], qA[e], qB[e], qA[e + 1], qB[e + 1], kk ? kP[h].z : kP[h].x, kk ? kP[h].w : kP[h].y);
    }
  float l[2][4], m[2][2];
  #pragma unroll
  for (int h = 0; h < 2; h++) {
    l[h][0] = s0 ? (noprev ? -INFINITY : s[h][0][0]) : s[h][1][0];
    l[h][1] = s1 ? (noprev ? -INFINITY : s[h][0][1]) : s[h][1][1];
    l[h][2] = s0 ? s[h][1][2] : s[h][2][2];
    l[h][3] = s1 ? s[h][1][3] : s[h][2][3];
    m[h][0] = fmaxf(l[h][0], l[h][1]); m[h][1] = fmaxf(l[h][2], l[h][3]);
  }
  #pragma unroll
  for (int x = 1; x <= 2; x <<= 1)
    #pragma unroll
    for (int e = 0; e < 4; e++) m[e >> 1][e & 1] = fmaxf(m[e >> 1][e & 1], __shfl_xor_sync(0xffffffffu, m[e >> 1][e & 1], x));
  #pragma unroll
  for (int h = 0; h < 2; h++) {
    #pragma unroll
    for (int e = 0; e < 4; e++) l[h][e] = fast_ex2((l[h][e] - m[h][e >> 1]) * SC);
    const uint32_t plo = pack_bf16(l[h][0], l[h][1]), phi = pack_bf16(l[h][2], l[h][3]);
    const uint32_t vp[4] = {vP[h].x, vP[h].y, vP[h].z, vP[h].w};
    #pragma unroll
    for (int d = 0; d < 5; d++) o[h][d][0] = o[h][d][1] = o[h][d][2] = o[h][d][3] = 0.f;
    mma8(o[h][4], plo, phi, 0x3F803F80u);
    #pragma unroll
    for (int d = 0; d < 4; d++) mma16(o[h][d], plo & ~msk, phi & msk, 0u, phi & ~msk, vA[4 * h + d], vB[4 * h + d]);
    #pragma unroll
    for (int d = 0; d < 4; d++) mma8(o[h][d], plo & msk, 0u, vp[d]);
  }
}
__device__ __forceinline__ void attn_store(const float (&o)[2][5][4], int h, uint32_t sbase, const Frag4& f) {
  const float r0 = fast_rcp(o[h][4][0]), r1 = fast_rcp(o[h][4][2]);
  #pragma unroll
  for (int d = 0; d < 4; d += 2)
    stmatrix_x4(sbase + SM_STG + f.o[2 * h + (d >> 1)],
                pack_bf16(o[h][d][0] * r0, o[h][d][1] * r0), pack_bf16(o[h][d][2] * r1, o[h][d][3] * r1),
                pack_bf16(o[h][d + 1][0] * r0, o[h][d + 1][1] * r0), pack_bf16(o[h][d + 1][2] * r1, o[h][d + 1][3] * r1));
}

__device__ __forceinline__ void g_switch(float (&cur)[64], float (&prv)[64], int nrest, bool first, int n, uint32_t sbase, uint32_t wgoff,
                                         const Frag4& f, Ring& r) {
  #pragma unroll 1
  for (int i = 1; i < nrest; i++) m_step(prv, sbase, wgoff, r);
  m_step(prv, sbase, wgoff, r);
  m_step(cur, sbase, wgoff, r, first);
  mbar_wait(sbase + B_STFREE, (n - 1) & 1, r.dl);
  fence_regs(prv);
  PROF(28 + n, threadIdx.x == 0);
  #pragma unroll
  for (int jj = 0; jj < 4; jj++) {
    uint32_t p[4];
    #pragma unroll
    for (int e = 0; e < 4; e++) {
      const int i = jj * 8 + e * 2;
      p[e] = pack_bf16(swiglu(prv[i], prv[i + 32]), swiglu(prv[i + 1], prv[i + 33]));
    }
    stmatrix_x4(sbase + SM_STG + f.o[jj], p[0], p[1], p[2], p[3]);
    m_step(cur, sbase, wgoff, r);
  }
  mbar_arrive_e(sbase + B_STREQ);
}

__device__ __forceinline__ uint32_t bad2(uint32_t a, uint32_t b, unsigned par) {
  uint32_t d; asm("lop3.b32 %0, %1, %2, %3, 0x7E;" : "=r"(d) : "r"(a), "r"(b), "r"(par)); return d;
}
__device__ __forceinline__ uint32_t bad4(const uint4& v, unsigned par) { return bad2(v.x, v.y, par) | bad2(v.z, v.w, par); }
__device__ __forceinline__ uint32_t hi_halves(uint32_t lo, uint32_t hi) { return __byte_perm(lo, hi, 0x7632); }

__device__ __forceinline__ void gather_table(const float* src, uint32_t dst, uint32_t bar, unsigned par, uint32_t dl) {
  asm volatile("{\n.reg .pred p, e;\n.reg .b32 s<4>, c<4>, t<4>, w<4>;\n"
               "elect.sync _|e, 0xffffffff;\n"
               "LAB_POLL:\n"
               "ld.relaxed.gpu.global.v4.u32 {s0, s1, s2, s3}, [%0];\n"
               "ld.relaxed.gpu.global.v4.u32 {c0, c1, c2, c3}, [%0 + 4096];\n"
               "prmt.b32 w0, c0, c1, 0x7632;\nprmt.b32 w1, c2, c3, 0x7632;\nprmt.b32 w2, s0, s1, 0x7632;\nprmt.b32 w3, s2, s3, 0x7632;\n"
               "st.shared.v4.b32 [%1], {w0, w1, w2, w3};\n"
               "lop3.b32 t0, s0, s1, %3, 0x7E;\nlop3.b32 t1, s2, s3, %3, 0x7E;\nlop3.b32 t2, c0, c1, %3, 0x7E;\nlop3.b32 t3, c2, c3, %3, 0x7E;\n"
               "lop3.b32 t0, t0, t1, 1, 0xA8;\nlop3.b32 t2, t2, t3, 1, 0xA8;\n"
               "or.b32 t0, t0, t2;\n"
               "setp.eq.u32 p, t0, 0;\n"
               "vote.sync.all.pred p, p, 0xffffffff;\n"
               "@p bra.uni LAB_OK;\n"
               "mov.u32 t0, %%clock;\nsub.s32 t0, t0, %4;\nsetp.lt.s32 p, t0, 0;\n"
               "vote.sync.all.pred p, p, 0xffffffff;\n"
               "@p bra.uni LAB_POLL;\n"
               "LAB_OK:\n"
               "@e mbarrier.arrive.shared::cta.b64 _, [%2];\n}"
               :: "l"(src), "r"(dst), "r"(bar), "r"(par), "r"(dl) : "memory");
}

__device__ __forceinline__ int other_slot(int i, int j) { return i < 4 ? (~j & 4) + i : (j & 4) + i - 4 + (i - 4 >= (j & 3)); }

__device__ __forceinline__ int aux_col(int a, int u) { return u < 8 ? (a & 1) * 1024 + (2 * u + (a >> 1)) * 64 : 2048 + ((u - 8) * 4 + a) * 64; }
constexpr int NA = 7;
constexpr uint32_t A_FULL = SM_BAR, A_EMPTY = SM_BAR + 64, A_SUM = SM_BAR + 128, A_FREE = SM_BAR + 136, SM_RED = SM_VEC;
__device__ __forceinline__ void aux_role(const Maps& maps, const bf16* __restrict__ cvec, Mail* mail0, int a, uint32_t sbase, int wid) {
  const int tid = threadIdx.x, lane = tid & 31;
  const uint32_t dl = clock32() + 800000000u;
  int st = 0; uint32_t ph = 0;
  if (wid == 8) {
    prefetch_tmap(&maps.wmod);
    #pragma unroll
    for (int i = 0; i < 18; i++) mbar_init_e(sbase + A_FULL + 8 * i, i < 8 ? 1 : i < 17 ? 8 : 2);
    fence_proxy_async_smem();
    bar_arrive(0, 352);
    PROF(39, lane == 0);
    #pragma unroll
    for (int i = 0; i < NA; i++) {
      mbar_expect_tx_e(sbase + A_FULL + 8 * i, 32768);
      tma_load_2d(sbase + i * MSLOT, &maps.wmod, sbase + A_FULL + 8 * i, aux_col(a, i >> 2), (i & 3) * 256);
    }
    PROF(40, lane == 0);
    #pragma unroll 1
    for (int i = NA; i < 96; i++) {
      if (i >= AUX_SLOW) wait_until(clock32() + AUX_GAP);
      if (i == 8) wait_until(dl - 800000000u + AUX_HOLD);
      mbar_wait(sbase + A_EMPTY + 8 * st, ph, dl);
      mbar_expect_tx_e(sbase + A_FULL + 8 * st, 32768);
      tma_load_2d<(EF & 1) != 0>(sbase + st * MSLOT, &maps.wmod, sbase + A_FULL + 8 * st, aux_col(a, i >> 2), (i & 3) * 256);
      if (++st == NA) { st = 0; ph ^= 1; }
    }
  } else if (wid < 8) {
    const int g = lane >> 2, qd = lane & 3;
    uint32_t sc[16];
    const uint2 c = *reinterpret_cast<const uint2*>(cvec + tid * 4);
    sts64(sbase + SM_RED + tid * 8, pack_bf16(silu_f(bf_lo(c.x)), silu_f(bf_hi(c.x))), pack_bf16(silu_f(bf_lo(c.y)), silu_f(bf_hi(c.y))));
    bar_sync(0, 352);
    #pragma unroll
    for (int i = 0; i < 16; i++) sc[i] = lds32(sbase + SM_RED + ((i >> 2) * 256 + wid * 32 + (i & 3) * 8 + qd * 2) * 2);
    bar_sync(NB_CONS, 256);
    PROF(38, tid == 0);
    const uint32_t aoff = (wid * 32 + (lane & 7) + (lane >> 4) * 8) * 128 + ((((lane >> 3) & 1) ^ (lane & 7)) << 4);
    uint32_t w[2][8][4];
    auto fetch = [&](uint32_t (&f)[8][4]) {
      mbar_wait(sbase + A_FULL + 8 * st, ph, dl);
      #pragma unroll
      for (int e = 0; e < 8; e++) ldmatrix_x4_t((sbase + st * MSLOT + aoff + (e >> 2) * 2048) ^ ((e & 3) << 5), f[e]);
      mbar_arrive_e(sbase + A_EMPTY + 8 * st);
      if (++st == NA) { st = 0; ph ^= 1; }
    };
    #pragma unroll 1
    for (int u = 0; u < 24; u++) {
      float acc[4][4];
      #pragma unroll
      for (int m = 0; m < 4; m++) acc[m][0] = acc[m][1] = acc[m][2] = acc[m][3] = 0.f;
      fetch(w[0]);
      #pragma unroll
      for (int q = 0; q < 4; q++) {
        PROF(30 + (u & 1) * 4 + q, u < 2 && tid == 0);
        if (q < 3) fetch(w[(q + 1) & 1]);
        if (q == 1) mbar_wait(sbase + A_FREE, (u & 1) ^ 1, dl);
        #pragma unroll
        for (int e = 0; e < 8; e++) {
          const uint32_t (&f)[4] = w[q & 1][e];
          mma16(acc[e & 3], f[0], f[1], f[2], f[3], sc[4 * q + 2 * (e >> 2)], sc[4 * q + 2 * (e >> 2) + 1]);
        }
      }
      const float v0 = qd & 2 ? (qd & 1 ? acc[3][0] : acc[2][0]) : (qd & 1 ? acc[1][0] : acc[0][0]);
      const float v1 = qd & 2 ? (qd & 1 ? acc[3][2] : acc[2][2]) : (qd & 1 ? acc[1][2] : acc[0][2]);
      sts64(sbase + SM_RED + wid * 256 + (qd * 8 + g) * 8, __float_as_uint(v0), __float_as_uint(v1));
      mbar_arrive_e(sbase + A_SUM);
    }
  } else if (wid < 11) {
    float* const mail = &mail0->mod[(wid - 9) * 4 * 6 * D_ + 2 * lane];
    unsigned par = ld_relaxed(&mail0->flags[FL_EPOCH + (lane >> 5)]);
    bar_sync(0, 352);
    par = (par + 1) & 1;
    #pragma unroll 1
    for (int u = -2; u < 24; u++) {
      if (u >= 0) {
        const int col = aux_col(a, u);
        const float add = (col >> 10) == 1 || (col >> 10) == 4 ? 1.f : 0.f;
        mbar_wait(sbase + A_SUM, u & 1, dl);
        float2 v[8];
        #pragma unroll
        for (int w = 0; w < 8; w++) v[w] = lds64f(sbase + SM_RED + w * 256 + lane * 8);
        const float t0 = ((v[0].x + v[1].x) + (v[2].x + v[3].x)) + ((v[4].x + v[5].x) + (v[6].x + v[7].x));
        const float t1 = ((v[0].y + v[1].y) + (v[2].y + v[3].y)) + ((v[4].y + v[5].y) + (v[6].y + v[7].y));
        const uint32_t w = pack_bf16(add + bf16_round(t0), add + bf16_round(t1)), o = __shfl_xor_sync(0xffffffffu, w, 1);
        const uint32_t m0 = (lane & 1) ? (o & 0xFFFF0000u) : (w << 16), m1 = (lane & 1) ? (w & 0xFFFF0000u) : (o << 16);
        #pragma unroll
        for (int c = 0; c < 4; c++) st_rlx_v2(mail + c * 6 * D_ + col, m0 | par, m1 | par, true);
        mbar_arrive_e(sbase + A_FREE);
        PROF(1 + u, tid == 288);
      }
      #pragma unroll 1
      for (int v = 2 * (u + 2); v < 2 * (u + 3) && v < 24; v++)
        #pragma unroll
        for (int c = 0; c < 4; c++) st_rlx_v2(mail + c * 6 * D_ + aux_col(a, v), par ^ 1, par ^ 1, true);
    }
  }
}

template <int MODE>
__global__ void __launch_bounds__(384, 1)
fused_block_kernel(const bf16* __restrict__ x, const bf16* __restrict__ cvec, const bf16* __restrict__ wmod, Mail* mail0, int zero,
                   const __grid_constant__ Maps maps) {
  extern __shared__ __align__(1024) uint8_t smem_raw[];
  const uint32_t sbase = smem_u32(smem_raw);
  const int tid = threadIdx.x, lane = tid & 31;
  PROFN(0, tid == 0);
  const int wid = __shfl_sync(0xffffffffu, tid >> 5, 0);
  const int b = cta_role<MODE>();
  if (b >= NCTA) { aux_role(maps, cvec, mail0, b - NCTA, sbase, wid); return; }
  const int jg = b >> 6, mb = jg ? 31 - (b >> 2) : (b >> 2), j = 4 * jg + (b & 3);
  const uint32_t dl = clock32() + 800000000u;
  unsigned* const flags = &mail0->flags[mb * 32];
  const int row0 = mb * 128;

  if (wid >= 8) {
    if (wid == 8) {
      #pragma unroll
      for (int i = 0; i < 8; i++) mbar_init_e(sbase + B_X + 8 * i, 1);
      fence_proxy_async_smem();
      #pragma unroll
      for (int q = 0; q < X_UP; q++) {
        mbar_expect_tx_e(sbase + B_X + 8 * q, 4096);
        bulk_load(sbase + SM_XR + q * 4096, x + (size_t)(row0 + j * 16 + 2 * q) * D_, 4096, sbase + B_X + 8 * q);
      }
    } else if (wid == 11) {
      #pragma unroll
      for (int i = 0; i < 12; i++) prefetch_tmap(&maps.x + i);
    } else if (wid == 9) {
      #pragma unroll
      for (uint32_t bar = B_EQ; bar < B_FM; bar += 8) mbar_init_e(sbase + bar, bar < B_FQ ? 8 : bar == B_FQ + 8 || bar == B_FQ + 24 ? 2 : 1);
      fence_proxy_async_smem();
    } else {
      #pragma unroll
      for (uint32_t bar = B_FM; bar < B_END; bar += 8) mbar_init_e(sbase + bar, 1);
      fence_proxy_async_smem();
    }
    bar_sync(0, 384);
    reg_dealloc<40>();
    PROF(92, tid == 256);
    if (wid == 8) {
      uint32_t tnext = clock32();
      #pragma unroll 1
      for (int q = X_UP; q < 8; q++) {
        wait_until(tnext);
        mbar_expect_tx_e(sbase + B_X + 8 * q, 4096);
        bulk_load(sbase + SM_XR + q * 4096, x + (size_t)(row0 + j * 16 + 2 * q) * D_, 4096, sbase + B_X + 8 * q);
        tnext += X_GAP;
      }
      #pragma unroll 1
      for (int u = 0; u < 16; u++) {
        const int st = u & 3;
        if (u == 1) PRD_WAIT(X_S1 < 8 ? sbase + B_X + 8 * X_S1 : sbase + B_MOD, 0, dl);
        if (u == 2) { PRD_WAIT(sbase + B_GATE, 0, dl); PROFN(60, lane == 0); }
        if (u == 3) PRD_WAIT(sbase + B_EQ, 0, dl);
        PRD_WAIT(sbase + B_EQ + 8 * st, ((u >> 2) & 1) ^ 1, dl);
        const uint32_t slot = sbase + st * QSLOT, fb = sbase + B_FQ + 8 * st;
        mbar_expect_tx_e(fb, u == 0 ? 65536 : u == 15 ? 32768 : 49152);
        if (u == 0) tma_load_3d(sbase + SM_X0, &maps.x, fb, 0, mb * 64, 0);
        tma_load_4d<(EF & 2) != 0>(slot + 16384, &maps.wqk, fb, 0, u * 64, j, 0);
        tma_load_4d<(EF & 2) != 0>(slot + 32768, &maps.wvv, fb, 0, u * 64, j, 0);
        if (u < 15) tma_load_3d(slot, &maps.x, fb, u * 64 + 64, mb * 64, 0);
      }
      const unsigned e1 = 1 + ld_relaxed(flags + FO_EPOCH);
      Ring r{0, 1, 0, dl};
      uint32_t slot, fb;
      auto acquire = [&](uint32_t bytes) {
        PRD_WAIT(sbase + B_EM + 8 * r.st, r.ph, dl);
        slot = sbase + r.st * MSLOT; fb = sbase + B_FM + 8 * r.st;
        mbar_expect_tx_e(fb, bytes);
        ring_next(r);
      };
      auto hold = [&](int n) { Ring h = r; for (int i = 0; i < n; i++) ring_next(h); PRD_WAIT(sbase + B_EM + 8 * h.st, h.ph, dl); };
      #pragma unroll 1
      for (int kt = 0; kt < 16; kt++) {
        if (kt < 5) PRD_WAIT(sbase + B_EQ + 8 * (kt - (kt >= 2)), 1, dl);
        if (kt == 8) hold(HOLD1);
        if ((kt & 7) == 0) { PROF(46, lane == 0 && kt == 8); PRD_WAIT(sbase + B_FLG + kt, 0, dl); PROF(47, lane == 0 && kt == 8); }
        acquire(32768);
        tma_load_4d<(EF & 2) != 0>(slot + 16384, &maps.wq1, fb, (j + 8) * 64, (kt & 1) * 64 + (kt & 6) * 8, (kt >> 3) * 4, 0);
        tma_load_3d(slot, &maps.hh, fb, (kt & 7) * 64, row0, kt >> 3);
      }
      hold(HOLD2);
      PROF(82, lane == 0);
      PRD_WAIT(sbase + B_FLG + 16, 0, dl);
      PROF(83, lane == 0);
      #pragma unroll 1
      for (int kt = 0; kt < 8; kt++) {
        acquire(32768);
        tma_load_3d<(EF & 2) != 0>(slot + 16384, &maps.wo, fb, 0, kt * 64, 2 * j);
        tma_load_2d(slot, &maps.o, fb, kt * 64, row0);
      }
      acquire(16384);
      tma_load_3d<(EF & 2) != 0>(slot + 16384, &maps.wo, fb, 0, (8 + j) * 64, 2 * j);
      {
        constexpr int NPRE = WPRE;
        Ring ra = r;
        #pragma unroll 1
        for (int i = 0; i < 7; i++) {
          const int kt = 8 + other_slot(i, j);
          if (i == 4) {
            acquire(32768);
            tma_load_3d(slot, &maps.x, fb, j * 128, mb * 64, 0);
            tma_load_3d(slot + 16384, &maps.x, fb, j * 128 + 64, mb * 64, 0);
          }
          acquire(32768);
          tma_load_3d<(EF & 2) != 0>(slot + 16384, &maps.wo, fb, 0, kt * 64, 2 * j);
          if (i == NPRE - 1) {
            wait_flag(&mail0->flags[FL_O], e1 * NCTA, dl);
            PROF(61, lane == 0);
            #pragma unroll 1
            for (int q = 0; q < NPRE - 1; q++) { tma_load_2d(sbase + ra.st * MSLOT, &maps.o, sbase + B_FM + 8 * ra.st, (8 + other_slot(q, j)) * 64, row0); ring_next(ra); }
          }
          if (i >= NPRE - 1) tma_load_2d(slot, &maps.o, fb, kt * 64, row0);
        }
      }
      #pragma unroll 1
      for (int t = 0; t < 2; t++) {
        acquire(32768);
        tma_load_2d<(EF & 4) != 0>(slot, &maps.w1, fb, j * 64, (2 * j + t) * 64);
        tma_load_2d<(EF & 4) != 0>(slot + 8192, &maps.w3, fb, j * 64, (2 * j + t) * 64);
        tma_load_2d<(EF & 4) != 0>(slot + 16384, &maps.w1, fb, (8 + j) * 64, (2 * j + t) * 64);
        tma_load_2d<(EF & 4) != 0>(slot + 24576, &maps.w3, fb, (8 + j) * 64, (2 * j + t) * 64);
      }
      {
        Ring ra = r;
        #pragma unroll 1
        for (int i = 0; i < 4; i++) {
          const int kt = 2 * ((~j & 4) + i);
          acquire(32768);
          tma_load_2d<(EF & 4) != 0>(slot + 16384, &maps.w1, fb, j * 64, kt * 64);
          tma_load_2d<(EF & 4) != 0>(slot + 24576, &maps.w3, fb, j * 64, kt * 64);
        }
        wait_flag(&mail0->flags[FL_H2], e1 * NCTA, dl);
        PROFN(62, lane == 0);
        #pragma unroll 1
        for (int i = 0; i < 4; i++) { tma_load_2d(sbase + ra.st * MSLOT, &maps.h2, sbase + B_FM + 8 * ra.st, ((~j & 4) + i) * 128, row0); ring_next(ra); }
      }
      #pragma unroll 1
      for (int gt = 0; gt < 7; gt++) {
        const int ncol = (8 * gt + j) * 64;
        #pragma unroll 1
        for (int i = (gt == 0 ? 4 : 0); i < (gt < 2 ? 14 : 16); i++) {
          const int kt = gt >= 2 ? i : i < 7 ? 2 * other_slot(i, j) : 2 * other_slot(i - 7, j) + 1;
          if (gt == 0 && i == 7) PRD_WAIT(sbase + B_FLG + 24, 0, dl);
          acquire(32768);
          tma_load_2d<(EF & 4) != 0>(slot + 16384, &maps.w1, fb, ncol, kt * 64);
          tma_load_2d<(EF & 4) != 0>(slot + 24576, &maps.w3, fb, ncol, kt * 64);
          tma_load_2d(slot, &maps.h2, fb, kt * 64, row0);
        }
      }
      #pragma unroll 1
      for (int kt = 0; kt < 56; kt++) {
        if ((kt & 7) == 0) PRD_WAIT(sbase + B_FLG + 32 + kt, 0, dl);
        acquire(32768);
        tma_load_3d<(EF & 8) != 0>(slot + 16384, &maps.w2, fb, 0, kt * 64, 2 * j);
        tma_load_3d<(EF & 16) != 0>(slot, &maps.hh, fb, (kt & 7) * 64, row0, kt >> 3);
      }
    } else {
      const unsigned e1 = 1 + ld_relaxed(wid == 9 ? flags + FO_EPOCH : &mail0->flags[FL_EPOCH]), par = e1 & 1;
      if (wid == 9) {
        mbar_wait(sbase + B_LN, 0, dl);
        red_add_e(&mail0->flags[FL_LN1], 1);
        SVC_WAIT(sbase + B_GATE, 0, dl);
        #pragma unroll 1
        for (int e = 0; e < 16; e++) st_rlx_v4(mail0->halo + (mb * 16 + j + (e & 8)) * 256 + (e & 7) * 32 + lane, ~0u, ~0u, ~0u, ~0u, true);
        #pragma unroll 1
        for (int e = 0; e < 2; e++) st_rlx_v4(mail0->st2 + ((mb * 8 + e * 4 + (lane >> 3)) * 8 + j) * 8 + (lane & 7), ~0u, ~0u, ~0u, ~0u, true);
        __threadfence();
        red_add_e(&mail0->flags[FL_RESET], 1);
        #pragma unroll 1
        for (int n = 0; n < 12; n++) {
          if (n == 4) {
            mbar_wait(sbase + B_STH, 0, dl);
            fence_proxy_async_smem();
            tma_store_2d(&maps.h2, sbase + SM_STG, j * 128, row0);
            bulk_commit();
            bulk_wait0();
            red_add_e(&mail0->flags[FL_H2], 1);
            PROF(84, lane == 0);
          }
          if (n >= ST_SPIN0 && n <= 4) mbar_wait(sbase + B_STREQ, n & 1, dl); else SVC_WAIT(sbase + B_STREQ, n & 1, dl);
          fence_proxy_async_smem();
          if (n == 2 || n == 3) tma_store_2d(&maps.o, sbase + SM_STG, (j + 8 * (n - 2)) * 64, row0);
          else if (n == 4) tma_store_2d(&maps.h2, sbase + SM_STG + 16384, j * 128 + 64, row0);
          else tma_store_3d(&maps.hh, sbase + SM_STG + (n == 1 ? 16384 : 0), j * 64, row0, n < 2 ? n : n - 5);
          bulk_commit();
          bulk_wait0();
          red_add_e(n == 3 ? &mail0->flags[FL_O] : flags + (n < 2 ? FO_H1 + n : n - 1), 1);
          mbar_arrive_e(sbase + B_STFREE);
          PROFN(70 + n, lane == 0 && n > 0);
        }
      } else {
        mbar_wait(sbase + B_X + 8 * X_POLL, 0, dl);
        const float* const mail = &mail0->mod[(b & 7) * 6 * D_ + lane * 4];
        if (wid == 10) {
          #pragma unroll 1
          for (int p = 0; p < 8; p++) {
            if (p >= 2) TRG_WAIT(p == 2 ? sbase + B_GATE : q_empty(2 * p - 5, sbase), p == 2 ? 0 : ((2 * p - 5) >> 2) & 1, dl);
            gather_table(mail + p * 128, sbase + SM_MODT + (p & 3) * 512 + lane * 16, p == 0 ? sbase + B_MOD : sbase + B_FQ + 8 * ((2 * p - 1) & 3), par, dl);
            PROF(63 + p, lane == 0 && p < 7);
          }
          const uint32_t vdst = sbase + SM_VEC + (lane >> 3) * 64 + (lane & 3) * 16 + ((lane >> 2) & 1) * 8;
          #pragma unroll 1
          for (int v = 0; v < 2; v++) {
            SVC_WAIT(sbase + B_FLG + 16 + 16 * v, 0, dl);
            uint4 m[3];
            while (true) {
              #pragma unroll
              for (int e = 0; e < 3; e++) m[e] = ld_rlx_v4(mail + (2 + v + e) * 1024 + j * 128);
              if (poll_done(((bad4(m[0], par) | bad4(m[1], par) | bad4(m[2], par)) & 1) == 0, dl)) break;
              __nanosleep(200);
            }
            #pragma unroll
            for (int e = 0; e < 3; e++) sts64(vdst + (v + e) * 256, hi_halves(m[e].x, m[e].y), hi_halves(m[e].z, m[e].w));
            mbar_arrive_e(sbase + B_VEC + 8 * v);
            PROF(70, lane == 0 && v == 0);
          }
        } else {
          mbar_wait(sbase + B_LN, 0, dl);
          wait_flag(&mail0->flags[FL_LN1], e1 * NCTA, dl);
          mbar_arrive_e(sbase + B_GATE);
          PROF(41, lane == 0);
          SVC_WAIT(q_empty(3, sbase), 0, dl);
          wait_flag(&mail0->flags[FL_RESET], e1 * NCTA, dl);
          SVC_WAIT(q_empty(7, sbase), 1, dl);
          SVC_WAIT(q_empty(11, sbase), 0, dl);
          mbar_arrive_e(sbase + B_FQ + 24);
          #pragma unroll 1
          for (int i = 0; i < 11; i++) {
            const unsigned* f = flags + (i < 2 ? FO_H1 + i : i == 2 ? FO_O : FO_H2 + i - 3);
            if (i == 3) SVC_WAIT(sbase + B_STH, 0, dl);
            while (!poll_done((int)(ld_relaxed(f) - e1 * 8) >= 0, dl)) { if (i > 3) __nanosleep(200); }
            mbar_arrive_e(sbase + B_FLG + 8 * i);
          }
        }
      }
    }
  } else {
    const int wg = wid >> 2, warp = wid & 3;
    const int g = lane >> 2, qd = lane & 3;
    bulk_prefetch(wmod + (size_t)(b * 8 + wid) * (6 * D_), PF_BYTES);
    bulk_prefetch(wmod + (size_t)(b * 8 + wid) * (6 * D_) + D_, PF_BYTES);
    bar_sync(0, 384);
    const unsigned e1 = 1 + ld_relaxed(flags + FO_EPOCH), par = e1 & 1;
    reg_alloc<232>();
    PROF(1, tid == 0);
    const uint32_t wgoff = wg * 8192;
    Frag4 frag;
    #pragma unroll
    for (int q = 0; q < 4; q++) frag.o[q] = wid * 2048 + (lane & 15) * 128 + (((2 * q + (lane >> 4)) ^ (lane & 7)) << 4);
    const uint32_t slab = sbase + SM_STG + wid * 2048;

    LnRow ln;
    {
      uint2* const lmail = &mail0->ln1[(mb * 8 + (lane & 1) * 4 + (j >> 1)) * 16 + (j & 1) * 8 + wid];
      st_rlx_v2(lmail, par ^ 1, par ^ 1, lane < 2);
      mbar_wait(sbase + B_X + 8 * wid, 0, dl);
      PROF(3, tid == 224); PROF(93, tid == 0);
      float s[2][2] = {{0.f, 0.f}, {0.f, 0.f}}, q2[2][2] = {{0.f, 0.f}, {0.f, 0.f}};
      #pragma unroll
      for (int c = 0; c < 8; c++) {
        const uint4 v = lds128(sbase + SM_XR + wid * 4096 + c * 512 + lane * 16);
        const uint32_t vv[4] = {v.x, v.y, v.z, v.w};
        #pragma unroll
        for (int e = 0; e < 4; e++) {
          const float lo = bf_lo(vv[e]), hi = bf_hi(vv[e]);
          s[c >> 2][0] += lo; s[c >> 2][1] += hi; q2[c >> 2][0] = fmaf(lo, lo, q2[c >> 2][0]); q2[c >> 2][1] = fmaf(hi, hi, q2[c >> 2][1]);
        }
      }
      const bool odd = lane & 1;
      float sm = (s[0][0] + s[0][1]), so = (s[1][0] + s[1][1]), qm = (q2[0][0] + q2[0][1]), qo = (q2[1][0] + q2[1][1]);
      { const float a = odd ? so : sm, c = odd ? qo : qm;
        sm = a + __shfl_xor_sync(0xffffffffu, odd ? sm : so, 1); qm = c + __shfl_xor_sync(0xffffffffu, odd ? qm : qo, 1); }
      #pragma unroll
      for (int o = 2; o < 32; o <<= 1) { sm += __shfl_xor_sync(0xffffffffu, sm, o); qm += __shfl_xor_sync(0xffffffffu, qm, o); }
      sm *= (1.f / D_);
      st_rlx_v2(lmail, tagf(fast_rsqrt(fmaxf(qm * (1.f / D_) - sm * sm, 0.f) + 1e-5f), par), tagf(sm, par), lane < 2);
      mbar_arrive_e(sbase + B_LN);
      PROF(4, tid == 224);
    }

    uint4* const halo_out = mail0->halo + ((mb * 16 + j) * 2 + wg) * 128 + lane;
    const uint4* const halo_in = halo_out - 16 * 256;
    const uint32_t xch = sbase + SM_XCH + wid * 2048 + lane * 16;
    const bool noprev = mb == 0 && warp == 0;
    float a0[64], a1[64];
    uint32_t x2[32];
    Ring r{zero, 0, 0, dl};
    Frag8 qA, qB, kA, kB, vA, vB, wA, wB;
    {
      float acc[128];
      uint32_t A0[16], A1[16];
      undef_regs(acc);
      const uint32_t tab = sbase + SM_MODT + qd * 16;
      uint4 p[4];
      q_wait(0, sbase, dl);
      mbar_wait(sbase + B_LN, 0, dl);
      const uint2* const lin = &mail0->ln1[(mb * 8 + wid) * 16 + g];
      uint2 v0 = ld_rlx_v2(lin), v1 = ld_rlx_v2(lin + 8);
      mbar_wait(sbase + B_MOD, 0, dl);
      #pragma unroll
      for (int kk = 0; kk < 4; kk++) q_load(A0, p, kk, sbase + SM_X0, frag, tab);
      while (!poll_done(((bad2(v0.x, v0.y, par) | bad2(v1.x, v1.y, par)) & 1) == 0, dl)) { v0 = ld_rlx_v2(lin); v1 = ld_rlx_v2(lin + 8); }
      ln_row(ln, 0, __uint_as_float(v0.y), __uint_as_float(v0.x));
      ln_row(ln, 1, __uint_as_float(v1.y), __uint_as_float(v1.x));
      PROF(5, tid == 0);
      const int hq0 = (j & 1) ? 4 : j >> 1, hq1 = (j & 1) ? j >> 1 : 4;
      q_step_rs<true>(acc, A0, A1, p, 0, sbase, frag, tab, ln, hq0, true, dl, wg);
      #pragma unroll 1
      for (int u = 1; u < 15; u += 2) {
        q_step_rs<true>(acc, A1, A0, p, u, sbase, frag, tab, ln, hq1, false, dl, wg);
        mbar_arrive_if(sbase + B_STREQ, u == 7 && lane == 0);
        q_step_rs<true>(acc, A0, A1, p, u + 1, sbase, frag, tab, ln, hq0, false, dl, wg);
      }
      q_step_rs<false>(acc, A1, A0, p, 15, sbase, frag, tab, ln, hq1, false, dl, wg);
      mbar_wait(sbase + B_STFREE, 0, dl);
      mbar_arrive_e(sbase + B_STREQ);
      wgmma_wait<0>();
      undef_regs(a0);
      { const uint32_t slot = m_wait(sbase, r); mma_step(a0, slot + wgoff, slot + 16384, true, q_empty(15, sbase)); m_next(r); }
      fence_regs(acc);
      PROF(8, tid == 0);
      sched_fence();
      pack_half(kB, acc, 32, 1); pack_half(vB, acc, 64, 1); transpose8(vB);
      m_step(a0, sbase, wgoff, r);
      sched_fence();
      attn_send(kB, 0, xch - 16384, warp, halo_out, mb < 15); attn_send(vB, 1, xch - 16384, warp, halo_out, mb < 15);
      pack_half(qA, acc, 0, 0); pack_half(qB, acc, 0, 1); pack_half(kA, acc, 32, 0);
      m_step(a0, sbase, wgoff, r);
      sched_fence();
      pack_half(vA, acc, 64, 0); pack_half(wB, acc, 96, 1); pack_half(wA, acc, 96, 0); transpose8(vA);
    }
    uint4 wP[2];
    {
      m_step(a0, sbase, wgoff, r);
      uint4 pv[4];
      attn_recv<4>(pv, 0, xch - 16384, wg, warp, halo_in, mb > 0);
      m_step(a0, sbase, wgoff, r);
      mbar_wait(sbase + B_STFREE, 1, dl);
      transpose8(wB);
      m_step(a0, sbase, wgoff, r);
      attn_check<4>(pv, 0, warp, halo_in, dl);
      wgmma_wait<0>();
      PROF(9, tid == 0);
      float o[2][5][4];
      sched_fence();
      attn_core(qA, qB, kA, kB, vA, vB, pv, pv + 2, noprev, lane, o);
      if (ST0 == 0) { attn_store(o, 0, sbase, frag); attn_store(o, 1, sbase, frag); mbar_arrive_e(sbase + B_STREQ); }
      if (ST0 == 1) attn_store(o, 0, sbase, frag);
      sched_fence();
      bar_sync(NB_CONS, 256);
      PROF(10, tid == 0);
      m_step(a0, sbase, wgoff, r);
      sched_fence();
      if (ST0 == 2) attn_store(o, 0, sbase, frag);
      if (ST0 >= 1) { attn_store(o, 1, sbase, frag); mbar_arrive_e(sbase + B_STREQ); }
      m_step(a0, sbase, wgoff, r);
      sched_fence();
      attn_send(wB, 1, xch, warp, halo_out + 8 * 256, mb < 15);
      transpose8(wA);
      #pragma unroll 1
      for (int i = 8; i < 15; i++) m_step(a0, sbase, wgoff, r);
      attn_recv<2>(wP, 2, xch, wg, warp, halo_in + 8 * 256, mb > 0);
      m_step(a0, sbase, wgoff, r);
    }
    {
      undef_regs(a1);
      {
        const uint32_t slot = m_wait(sbase, r);
        mma_step(a1, slot + wgoff, slot + 16384, true, m_prev(sbase, r), [&] {
          fence_regs(a0);
          pack_half(kB, a0, 32, 1);
          attn_send(kB, 0, xch, warp, halo_out + 8 * 256, mb < 15);
        });
        m_next(r);
      }
      PROF(14, tid == 0);
      sched_fence();
      pack_half(kA, a0, 32, 0); pack_half(qA, a0, 0, 0); pack_half(qB, a0, 0, 1);
      m_step(a1, sbase, wgoff, r);
      attn_check<2>(wP, 2, warp, halo_in + 8 * 256, dl);
      uint4 kP[2];
      attn_recv<2>(kP, 0, xch, wg, warp, halo_in + 8 * 256, mb > 0);
      m_step(a1, sbase, wgoff, r);
      attn_check<2>(kP, 0, warp, halo_in + 8 * 256, dl);
      wgmma_wait<0>();
      PROF(15, tid == 0);
      float o[2][5][4];
      mbar_wait(sbase + B_STFREE, 0, dl);
      attn_core(qA, qB, kA, kB, wA, wB, kP, wP, noprev, lane, o);
      attn_store(o, 0, sbase, frag);
      attn_store(o, 1, sbase, frag);
      mbar_arrive_e(sbase + B_STREQ);
      fence_proxy_async_smem();
      bar_sync(NB_CONS, 256);
      PROF(16, tid == 0);
      #pragma unroll 1
      for (int i = 3; i < 8; i++) m_step(a1, sbase, wgoff, r);
      mma_step(a1, sbase + SM_STG + wgoff, m_wait(sbase, r) + 16384, false, m_prev(sbase, r));
      m_next(r);
      PROF(17, tid == 0);
      #pragma unroll 1
      for (int i = 0; i < 4; i++) { m_step(a1, sbase, wgoff, r); PROF(42, tid == 0 && i == 0); }
      PROF(43, tid == 0);
      const uint32_t xs = m_wait(sbase, r), xe = sbase + B_EM + 8 * r.st;
      PROF(44, tid == 0);
      ring_next(r);
      #pragma unroll
      for (int t = 0; t < 2; t++) {
        #pragma unroll
        for (int jj = 4 * t; jj < 4 * t + 4; jj++) ldmatrix_x4(xs + t * 16384 + frag.o[jj & 3], x2[4 * jj], x2[4 * jj + 1], x2[4 * jj + 2], x2[4 * jj + 3]);
        if (t == 1) mbar_arrive_e(xe);
        m_step(a1, sbase, wgoff, r);
      }
      m_step(a1, sbase, wgoff, r);
      PROF(45, tid == 0);
      mbar_wait(sbase + B_VEC, 0, dl);
      mbar_wait(sbase + B_STFREE, 1, dl);
      const uint32_t vec = sbase + SM_VEC + qd * 16;
      uint4 ga[4];
      #pragma unroll
      for (int q = 0; q < 4; q++) ga[q] = lds128(vec + q * 64);
      wgmma_wait<0>();
      mbar_arrive_e(m_prev(sbase, r));
      fence_regs(a1);
      PROF(18, tid == 0);
      float rs_[4] = {0.f, 0.f, 0.f, 0.f}, gl[4] = {0.f, 0.f, 0.f, 0.f}, gh[4] = {0.f, 0.f, 0.f, 0.f};
      #pragma unroll
      for (int jj = 0; jj < 8; jj++) {
        uint32_t* v = &x2[4 * jj];
        const uint32_t wl = (jj & 1) ? ga[jj >> 1].z : ga[jj >> 1].x, wh = (jj & 1) ? ga[jj >> 1].w : ga[jj >> 1].y;
        #pragma unroll
        for (int e = 0; e < 4; e++) v[e] = fma_bf2(e & 2 ? wh : wl, pack_bf16(a1[8 * jj + 2 * e], a1[8 * jj + 2 * e + 1]), v[e]);
        mma16(rs_, v[0], v[1], v[2], v[3], 0x3F803F80u, 0x3F803F80u);
        mma16(gl, v[0], v[1], v[2], v[3], v[0], v[2]);
        mma16(gh, v[0], v[1], v[2], v[3], v[1], v[3]);
      }
      uint4* const sm = mail0->st2 + (mb * 8 + wid) * 64 + g;
      st_rlx_v4(sm + j * 8, __float_as_uint(rs_[0]), __float_as_uint(g & 1 ? gl[1] : gl[0]), __float_as_uint(rs_[2]), __float_as_uint(g & 1 ? gh[3] : gh[2]),
                qd == (g >> 1));
      float s[2], q2[2];
      PROF(19, tid == 0);
      uint4 sb[4], cb[4];
      #pragma unroll
      for (int q = 0; q < 4; q++) { sb[q] = lds128(vec + 256 + q * 64); cb[q] = lds128(vec + 512 + q * 64); }
      uint4 p0, p1;
      while (true) {
        p0 = ld_rlx_v4(sm + qd * 16); p1 = ld_rlx_v4(sm + qd * 16 + 8);
        if (poll_done(max(max(max(p0.x, p0.y), max(p0.z, p0.w)), max(max(p1.x, p1.y), max(p1.z, p1.w))) != ~0u, dl)) break;
      }
      PROF(20, tid == 0);
      s[0] = __uint_as_float(p0.x) + __uint_as_float(p1.x); q2[0] = __uint_as_float(p0.y) + __uint_as_float(p1.y);
      s[1] = __uint_as_float(p0.z) + __uint_as_float(p1.z); q2[1] = __uint_as_float(p0.w) + __uint_as_float(p1.w);
      #pragma unroll
      for (int o2 = 1; o2 <= 2; o2 <<= 1)
        #pragma unroll
        for (int h = 0; h < 2; h++) { s[h] += __shfl_xor_sync(0xffffffffu, s[h], o2); q2[h] += __shfl_xor_sync(0xffffffffu, q2[h], o2); }
      #pragma unroll
      for (int h = 0; h < 2; h++) {
        const float m = s[h] * (1.f / D_);
        ln_row(ln, h, m, fast_rsqrt(fmaxf(q2[h] * (1.f / D_) - m * m, 0.f) + 1e-5f));
      }
      #pragma unroll
      for (int jj = 0; jj < 8; jj++) {
        const uint32_t cl = (jj & 1) ? cb[jj >> 1].z : cb[jj >> 1].x, ch = (jj & 1) ? cb[jj >> 1].w : cb[jj >> 1].y;
        const uint32_t sl = (jj & 1) ? sb[jj >> 1].z : sb[jj >> 1].x, sh = (jj & 1) ? sb[jj >> 1].w : sb[jj >> 1].y;
        stmatrix_x4(sbase + SM_STG + (jj >> 2) * 16384 + frag.o[jj & 3], ln_mod(x2[4 * jj], ln, 0, cl, sl), ln_mod(x2[4 * jj + 1], ln, 1, cl, sl),
                    ln_mod(x2[4 * jj + 2], ln, 0, ch, sh), ln_mod(x2[4 * jj + 3], ln, 1, ch, sh));
        if (jj == 3) mbar_arrive_e(sbase + B_STH);
      }
      mbar_arrive_e(sbase + B_STREQ);
      fence_proxy_async_smem();
      bar_sync(NB_WG + wg, 128);
      PROF(21, tid == 0);
    }

    undef_regs(a0);
    #pragma unroll
    for (int t = 0; t < 2; t++) {
      const uint32_t slot = m_wait(sbase, r);
      if (t == 0) mma_step<false>(a0, sbase + SM_STG + wgoff, slot, true, 0);
      else mma_step(a0, sbase + SM_STG + 16384 + wgoff, slot, false, m_prev(sbase, r));
      mma_step<false>(a1, sbase + SM_STG + t * 16384 + wgoff, slot + 16384, t == 0, 0);
      m_next(r);
    }
    PROF(22, tid == 0);
    #pragma unroll 1
    for (int t = 0; t < 7; t += 2) {
      g_switch(a1, a0, t == 0 ? 14 : 11, t > 0, 5 + t, sbase, wgoff, frag, r);
      if (t == 6) break;
      g_switch(a0, a1, t == 0 ? 9 : 11, true, 6 + t, sbase, wgoff, frag, r);
    }
    #pragma unroll 1
    for (int i = 5; i < 56 - DTAIL; i++) m_step(a1, sbase, wgoff, r);
    if (DTAIL) {
      if (wg == 1) { wgmma_wait<0>(); mbar_arrive_e(m_prev(sbase, r)); bar_sync(NB_ORD, 256); }
      #pragma unroll
      for (int i = 0; i < DTAIL; i++) {
        const uint32_t slot = m_wait(sbase, r);
        const uint32_t alo = ((slot + wgoff) >> 4) + (1u << 16), blo = ((slot + 16384) >> 4) + (512u << 16);
        wgmma_fence();
        #pragma unroll
        for (int k = 0; k < 4; k++) wgmma_m64n128k16_ss(a1, desc_from_lo(alo + k * 2), desc_from_lo(blo + k * 128), true);
        wgmma_commit();
        ring_next(r);
      }
      if (wg == 0) bar_arrive(NB_ORD, 256);
    }
    {
      mbar_wait(sbase + B_STFREE, 1, dl);
      mbar_wait(sbase + B_VEC + 8, 0, dl);
      uint4 gb[4];
      #pragma unroll
      for (int q = 0; q < 4; q++) gb[q] = lds128(sbase + SM_VEC + 768 + qd * 16 + q * 64);
      wgmma_wait<0>();
      fence_regs(a1);
      PROF(50, tid == 128);
      #pragma unroll
      for (int t = 0; t < 2; t++) {
        #pragma unroll
        for (int jj = 4 * t; jj < 4 * t + 4; jj++) {
          const uint32_t gl = (jj & 1) ? gb[jj >> 1].z : gb[jj >> 1].x, gh = (jj & 1) ? gb[jj >> 1].w : gb[jj >> 1].y;
          const int i = 8 * jj;
          stmatrix_x4(sbase + SM_STG + t * 16384 + frag.o[jj & 3],
                      fma_bf2(gl, pack_bf16(a1[i], a1[i + 1]), x2[4 * jj]), fma_bf2(gl, pack_bf16(a1[i + 2], a1[i + 3]), x2[4 * jj + 1]),
                      fma_bf2(gh, pack_bf16(a1[i + 4], a1[i + 5]), x2[4 * jj + 2]), fma_bf2(gh, pack_bf16(a1[i + 6], a1[i + 7]), x2[4 * jj + 3]));
        }
        fence_proxy_async_smem();
        tma_store_3d(&maps.out, slab + t * 16384, j * 128 + t * 64, mb * 64 + warp * 16, wg);
      }
      bulk_commit();
      st_rlx(tid == 0 ? flags + FO_EPOCH : &mail0->flags[FL_EPOCH], e1, j == 0 && (tid == 0 || (tid == 1 && mb == 0)));
      bulk_wait_read0();
      PROFN(51, tid == 128);
    }
  }
}

typedef CUresult (*PFN_encodeTiled)(CUtensorMap*, CUtensorMapDataType, cuuint32_t, void*, const cuuint64_t*, const cuuint64_t*,
                                    const cuuint32_t*, const cuuint32_t*, CUtensorMapInterleave, CUtensorMapSwizzle,
                                    CUtensorMapL2promotion, CUtensorMapFloatOOBfill);

void encode(PFN_encodeTiled fn, CUtensorMap* m, const void* ptr, int rank, const cuuint64_t* dims, const cuuint64_t* strides,
            const cuuint32_t* box) {
  const cuuint32_t es[5] = {1, 1, 1, 1, 1};
  fn(m, CU_TENSOR_MAP_DATA_TYPE_BFLOAT16, rank, const_cast<void*>(ptr), dims, strides, box, es, CU_TENSOR_MAP_INTERLEAVE_NONE,
     CU_TENSOR_MAP_SWIZZLE_128B, CU_TENSOR_MAP_L2_PROMOTION_L2_256B, CU_TENSOR_MAP_FLOAT_OOB_FILL_NONE);
}
void map2d(PFN_encodeTiled fn, CUtensorMap* m, const void* ptr, int cols, int rows, int boxrows) {
  const cuuint64_t dims[2] = {(cuuint64_t)cols, (cuuint64_t)rows}, strides[1] = {(cuuint64_t)cols * 2};
  const cuuint32_t box[2] = {64, (cuuint32_t)boxrows};
  encode(fn, m, ptr, 2, dims, strides, box);
}
void map_w2chunk(PFN_encodeTiled fn, CUtensorMap* m, const void* ptr, int cols, int rows) {
  const cuuint64_t dims[3] = {64, (cuuint64_t)rows, (cuuint64_t)cols / 64}, strides[2] = {(cuuint64_t)cols * 2, 128};
  const cuuint32_t box[3] = {64, 64, 2};
  encode(fn, m, ptr, 3, dims, strides, box);
}
void map_parity(PFN_encodeTiled fn, CUtensorMap* m, const void* ptr, int boxpairs, int boxpar) {
  const cuuint64_t dims[3] = {D_, S_ / 2, 2}, strides[2] = {D_ * 4, D_ * 2};
  const cuuint32_t box[3] = {64, (cuuint32_t)boxpairs, (cuuint32_t)boxpar};
  encode(fn, m, ptr, 3, dims, strides, box);
}

}

extern "C" void kernel_launch(void* const* d_in, const int* in_sizes, int n_in, void* d_out, int out_size) {
  (void)in_sizes; (void)n_in; (void)out_size;
  const bf16* x = (const bf16*)d_in[0];
  const bf16* wqkv = (const bf16*)d_in[1];
  const bf16* wo = (const bf16*)d_in[2];
  const bf16* w1 = (const bf16*)d_in[4];
  const bf16* w3 = (const bf16*)d_in[5];
  const bf16* w2 = (const bf16*)d_in[6];
  const bf16* cvec = (const bf16*)d_in[7];
  const bf16* w_mod = (const bf16*)d_in[8];

  static PFN_encodeTiled fn = nullptr;
  static Maps maps;
  static const void* cached[8] = {};
  static int sms = 0;
  static void* mail = nullptr;
  if (!fn) {
    void* p = nullptr; cudaDriverEntryPointQueryResult st;
    cudaGetDriverEntryPoint("cuTensorMapEncodeTiled", &p, cudaEnableDefault, &st);
    fn = (PFN_encodeTiled)p;
    cudaFuncSetAttribute(fused_block_kernel<0>, cudaFuncAttributeMaxDynamicSharedMemorySize, SM_TOTAL + SM_PROF);
    cudaFuncSetAttribute(fused_block_kernel<1>, cudaFuncAttributeMaxDynamicSharedMemorySize, SM_TOTAL + SM_PROF);
    cudaFuncSetAttribute(fused_block_kernel<2>, cudaFuncAttributeMaxDynamicSharedMemorySize, SM_TOTAL + SM_PROF);
    cudaGetSymbolAddress(&mail, g_mail);
    int dev = 0;
    cudaGetDevice(&dev);
    cudaDeviceGetAttribute(&sms, cudaDevAttrMultiProcessorCount, dev);
  }
  const void* cur[8] = {x, wqkv, wo, w1, w3, w2, d_out, w_mod};
  bool same = true;
  for (int i = 0; i < 8; i++) same = same && cached[i] == cur[i];
  if (!same) {
    void *o, *h2, *hh;
    cudaGetSymbolAddress(&hh, g_hh); cudaGetSymbolAddress(&o, g_o);
    h2 = o;
    map_parity(fn, &maps.x, x, 64, 2); map_parity(fn, &maps.out, d_out, 16, 1);
    map2d(fn, &maps.o, o, D_, S_, 128); map2d(fn, &maps.h2, h2, D_, S_, 128);
    {
      const cuuint64_t dims[3] = {512, (cuuint64_t)S_, 7}, strides[2] = {1024, (cuuint64_t)S_ * 1024};
      const cuuint32_t box[3] = {64, 128, 1};
      encode(fn, &maps.hh, hh, 3, dims, strides, box);
    }
    {
      const cuuint64_t dims[4] = {64, 1024, 16, 2}, strides[3] = {3072 * 2, 128, 2048};
      const cuuint64_t dimv[4] = {64, 1024, 8, 2}, stridev[3] = {3072 * 2, 128, 1024};
      const cuuint32_t box[4] = {64, 64, 1, 2};
      encode(fn, &maps.wqk, wqkv, 4, dims, strides, box);
      encode(fn, &maps.wvv, wqkv + 2048, 4, dimv, stridev, box);
      const cuuint64_t dim1[4] = {1024, 128, 8, 2}, stride1[3] = {3072 * 2, 128 * 3072 * 2, 2048};
      const cuuint32_t box1[4] = {64, 16, 4, 2};
      encode(fn, &maps.wq1, wqkv, 4, dim1, stride1, box1);
    }
    map_w2chunk(fn, &maps.wo, wo, D_, D_); map_w2chunk(fn, &maps.w2, w2, D_, F_);
    map2d(fn, &maps.w1, w1, F_, D_, 64); map2d(fn, &maps.w3, w3, F_, D_, 64);
    map2d(fn, &maps.wmod, w_mod, 6 * D_, D_, 256);
    for (int i = 0; i < 8; i++) cached[i] = cur[i];
  }
  if (sms == NCTA + NAUX) {
    fused_block_kernel<0><<<NCTA + NAUX, 384, SM_TOTAL + SM_PROF>>>(x, cvec, w_mod, (Mail*)mail, 0, maps);
  } else {
    fused_block_kernel<1><<<NAUX, 384, SM_TOTAL + SM_PROF>>>(x, cvec, w_mod, (Mail*)mail, 0, maps);
    fused_block_kernel<2><<<NCTA, 384, SM_TOTAL + SM_PROF>>>(x, cvec, w_mod, (Mail*)mail, 0, maps);
  }
}
```

```cpp
#include <cuda.h>
#include <cuda_runtime.h>
#include <cuda_bf16.h>
#include <stdint.h>

namespace {

typedef __nv_bfloat16 bf16;

constexpr int S_ = 2048, D_ = 1024, F_ = 3584;
constexpr int NCTA = 128, NAUX = 4;

__device__ __align__(1024) bf16 g_o[S_ * D_];
__device__ __align__(1024) bf16 g_hh[S_ * F_];
constexpr int FO_EPOCH = 0, FO_O = 1, FO_H2 = 3, FO_H1 = 11;
constexpr int FL_EPOCH = 16 * 32, FL_RESET = FL_EPOCH + 1, FL_LN1 = FL_EPOCH + 2, FL_H2 = FL_EPOCH + 3, FL_O = FL_EPOCH + 4;
struct Mail {
  unsigned flags[32 * 32];
  float mod[8 * 6 * D_];
  uint2 ln1[16 * 8 * 16];
  uint4 halo[16 * 16 * 2 * 4 * 32];
  uint4 st2[16 * 8 * 8 * 8];
};
__device__ __align__(1024) Mail g_mail;

template <int mode>
__device__ __forceinline__ int cta_role() {
  if (mode) return mode == 1 ? NCTA + (blockIdx.x & 3) : blockIdx.x & 127;
  uint32_t sm;
  asm("mov.u32 %0, %%smid;" : "=r"(sm));
  sm = (sm & ~3u) == 12 ? sm + 108 : (sm & ~3u) == 120 ? sm - 108 : sm;
  const int t = sm >> 1;
  int r;
  if (t < 32) r = (t & 7) * 16 + (t >> 3) * 2 + (sm & 1);
  else if (t < 60) r = (1 + (t - 32) % 7) * 16 + 8 + ((t - 32) / 7) * 2 + (sm & 1);
  else if (t < 62) r = NCTA + sm - 120;
  else r = sm - 116;
  return r;
}
#define PROF(slot, on) do {} while (0)
#define PROFN(slot, on) do {} while (0)
#define PROF_OUT(role, t) do {} while (0)
constexpr uint32_t SM_PROF = 0;

__device__ __forceinline__ uint32_t smem_u32(const void* p) { return (uint32_t)__cvta_generic_to_shared(p); }
#define ELECT "{\n.reg .pred p;\nelect.sync _|p, 0xffffffff;\n@p "
__device__ __forceinline__ void mbar_init_e(uint32_t bar, uint32_t count) {
  asm volatile(ELECT "mbarrier.init.shared::cta.b64 [%0], %1;\n}" :: "r"(bar), "r"(count) : "memory");
}
__device__ __forceinline__ void mbar_expect_tx_e(uint32_t bar, uint32_t bytes) {
  asm volatile(ELECT "mbarrier.arrive.expect_tx.shared::cta.b64 _, [%0], %1;\n}" :: "r"(bar), "r"(bytes) : "memory");
}
__device__ __forceinline__ void mbar_arrive_e(uint32_t bar) {
  asm volatile(ELECT "mbarrier.arrive.shared::cta.b64 _, [%0];\n}" :: "r"(bar) : "memory");
}
__device__ __forceinline__ uint32_t clock32() { uint32_t t; asm volatile("mov.u32 %0, %%clock;" : "=r"(t)); return t; }
__device__ __forceinline__ void mbar_wait(uint32_t bar, uint32_t parity, uint32_t dl) {
  asm volatile("{\n.reg .pred p, q;\n.reg .b32 t;\n"
               "mbarrier.try_wait.parity.shared::cta.b64 p, [%0], %1;\n"
               "@p bra LAB_DONE;\n"
               "LAB_WAIT:\n"
               "mbarrier.try_wait.parity.shared::cta.b64 p, [%0], %1;\n"
               "mov.u32 t, %%clock;\n"
               "sub.s32 t, t, %2;\n"
               "setp.lt.and.s32 q, t, 0, !p;\n"
               "@q bra LAB_WAIT;\n"
               "LAB_DONE:\n}" :: "r"(bar), "r"(parity), "r"(dl) : "memory");
}
__device__ __forceinline__ void mbar_sleep(uint32_t bar, uint32_t parity, uint32_t dl) {
  asm volatile("{\n.reg .pred p;\n.reg .b32 t;\n"
               "LAB_WAIT:\n"
               "mbarrier.try_wait.parity.shared::cta.b64 p, [%0], %1, 20000;\n"
               "@p bra LAB_DONE;\n"
               "mov.u32 t, %%clock;\n"
               "sub.s32 t, t, %2;\n"
               "setp.lt.s32 p, t, 0;\n"
               "@p bra LAB_WAIT;\n"
               "LAB_DONE:\n}" :: "r"(bar), "r"(parity), "r"(dl) : "memory");
}
__device__ __forceinline__ bool poll_done(bool ok, uint32_t dl) {
  return __all_sync(0xffffffffu, ok || (int)(clock32() - dl) >= 0);
}
__device__ __forceinline__ unsigned ld_relaxed(const unsigned* p) {
  unsigned v; asm volatile("ld.relaxed.gpu.global.u32 %0, [%1];" : "=r"(v) : "l"(p) : "memory"); return v;
}
__device__ __forceinline__ void red_add_e(unsigned* p, unsigned v) {
  asm volatile(ELECT "red.relaxed.gpu.global.add.u32 [%0], %1;\n}" :: "l"(p), "r"(v) : "memory");
}
__device__ __forceinline__ void wait_flag(const unsigned* p, unsigned target, uint32_t dl) {
  asm volatile("{\n.reg .pred p;\n.reg .b32 t;\n"
               "LAB_WAIT:\n"
               "ld.relaxed.gpu.global.u32 t, [%0];\n"
               "sub.s32 t, t, %1;\n"
               "setp.ge.s32 p, t, 0;\n"
               "@p bra LAB_DONE;\n"
               "mov.u32 t, %%clock;\n"
               "sub.s32 t, t, %2;\n"
               "setp.lt.s32 p, t, 0;\n"
               "@p bra LAB_WAIT;\n"
               "LAB_DONE:\n}" :: "l"(p), "r"(target), "r"(dl) : "memory");
}
__device__ __forceinline__ void wait_until(uint32_t t) { while ((int)(clock32() - t) < 0) {} }
__device__ __forceinline__ void fence_proxy_async_smem() { asm volatile("fence.proxy.async.shared::cta;" ::: "memory"); }

constexpr uint64_t EVICT_FIRST = 0x12F0000000000000ull;
template <bool STREAM = false>
__device__ __forceinline__ void tma_load_2d(uint32_t dst, const CUtensorMap* m, uint32_t bar, int c0, int c1) {
  if (STREAM)
    asm volatile(ELECT "cp.async.bulk.tensor.2d.shared::cluster.global.mbarrier::complete_tx::bytes.L2::cache_hint [%0], [%1, {%3, %4}], [%2], %5;\n}"
                 :: "r"(dst), "l"(m), "r"(bar), "r"(c0), "r"(c1), "l"(EVICT_FIRST) : "memory");
  else
    asm volatile(ELECT "cp.async.bulk.tensor.2d.shared::cluster.global.mbarrier::complete_tx::bytes [%0], [%1, {%3, %4}], [%2];\n}"
                 :: "r"(dst), "l"(m), "r"(bar), "r"(c0), "r"(c1) : "memory");
}
template <bool STREAM = false>
__device__ __forceinline__ void tma_load_3d(uint32_t dst, const CUtensorMap* m, uint32_t bar, int c0, int c1, int c2) {
  if (STREAM)
    asm volatile(ELECT "cp.async.bulk.tensor.3d.shared::cluster.global.mbarrier::complete_tx::bytes.L2::cache_hint [%0], [%1, {%3, %4, %5}], [%2], %6;\n}"
                 :: "r"(dst), "l"(m), "r"(bar), "r"(c0), "r"(c1), "r"(c2), "l"(EVICT_FIRST) : "memory");
  else
    asm volatile(ELECT "cp.async.bulk.tensor.3d.shared::cluster.global.mbarrier::complete_tx::bytes [%0], [%1, {%3, %4, %5}], [%2];\n}"
                 :: "r"(dst), "l"(m), "r"(bar), "r"(c0), "r"(c1), "r"(c2) : "memory");
}
template <bool STREAM = false>
__device__ __forceinline__ void tma_load_4d(uint32_t dst, const CUtensorMap* m, uint32_t bar, int c0, int c1, int c2, int c3) {
  if (STREAM)
    asm volatile(ELECT "cp.async.bulk.tensor.4d.shared::cluster.global.mbarrier::complete_tx::bytes.L2::cache_hint [%0], [%1, {%3, %4, %5, %6}], [%2], %7;\n}"
                 :: "r"(dst), "l"(m), "r"(bar), "r"(c0), "r"(c1), "r"(c2), "r"(c3), "l"(EVICT_FIRST) : "memory");
  else
    asm volatile(ELECT "cp.async.bulk.tensor.4d.shared::cluster.global.mbarrier::complete_tx::bytes [%0], [%1, {%3, %4, %5, %6}], [%2];\n}"
                 :: "r"(dst), "l"(m), "r"(bar), "r"(c0), "r"(c1), "r"(c2), "r"(c3) : "memory");
}
__device__ __forceinline__ void tma_store_2d(const CUtensorMap* m, uint32_t src, int c0, int c1) {
  asm volatile(ELECT "cp.async.bulk.tensor.2d.global.shared::cta.bulk_group [%0, {%2, %3}], [%1];\n}"
               :: "l"(m), "r"(src), "r"(c0), "r"(c1) : "memory");
}
__device__ __forceinline__ void tma_store_3d(const CUtensorMap* m, uint32_t src, int c0, int c1, int c2) {
  asm volatile(ELECT "cp.async.bulk.tensor.3d.global.shared::cta.bulk_group [%0, {%2, %3, %4}], [%1];\n}"
               :: "l"(m), "r"(src), "r"(c0), "r"(c1), "r"(c2) : "memory");
}
__device__ __forceinline__ void bulk_load(uint32_t dst, const void* src, uint32_t bytes, uint32_t bar) {
  asm volatile(ELECT "cp.async.bulk.shared::cluster.global.mbarrier::complete_tx::bytes [%0], [%1], %2, [%3];\n}"
               :: "r"(dst), "l"(src), "r"(bytes), "r"(bar) : "memory");
}
__device__ __forceinline__ void bulk_prefetch(const void* src, uint32_t bytes) {
  asm volatile(ELECT "cp.async.bulk.prefetch.L2.global [%0], %1;\n}" :: "l"(src), "r"(bytes) : "memory");
}
__device__ __forceinline__ void bulk_commit() { asm volatile("cp.async.bulk.commit_group;" ::: "memory"); }
__device__ __forceinline__ void bulk_wait0() { asm volatile("cp.async.bulk.wait_group 0;" ::: "memory"); }
__device__ __forceinline__ void bulk_wait_read0() { asm volatile("cp.async.bulk.wait_group.read 0;" ::: "memory"); }
__device__ __forceinline__ void prefetch_tmap(const CUtensorMap* m) { asm volatile(ELECT "prefetch.tensormap [%0];\n}" :: "l"(m) : "memory"); }
__device__ __forceinline__ void wgmma_fence() { asm volatile("wgmma.fence.sync.aligned;" ::: "memory"); }
__device__ __forceinline__ void wgmma_commit() { asm volatile("wgmma.commit_group.sync.aligned;" ::: "memory"); }
template <int N> __device__ __forceinline__ void wgmma_wait() { asm volatile("wgmma.wait_group.sync.aligned %0;" :: "n"(N) : "memory"); }
template <int R> __device__ __forceinline__ void reg_alloc() { asm volatile("setmaxnreg.inc.sync.aligned.u32 %0;" :: "n"(R)); }
template <int R> __device__ __forceinline__ void reg_dealloc() { asm volatile("setmaxnreg.dec.sync.aligned.u32 %0;" :: "n"(R)); }
__device__ __forceinline__ void bar_sync(int id, int n) { asm volatile("bar.sync %0, %1;" :: "r"(id), "r"(n) : "memory"); }
__device__ __forceinline__ void bar_arrive(int id, int n) { asm volatile("bar.arrive %0, %1;" :: "r"(id), "r"(n) : "memory"); }
__device__ __forceinline__ void sched_fence() {
  asm volatile("{\n.reg .pred p;\n.reg .b32 t;\nLAB_F:\nmov.u32 t, %%clock;\nsetp.eq.u32 p, t, %0;\n@p bra LAB_F;\n}" :: "n"(0) : "memory");
}
template <int N> __device__ __forceinline__ void fence_regs(float (&a)[N]) {
  #pragma unroll
  for (int i = 0; i < N; i++) asm volatile("" : "+f"(a[i]) :: "memory");
}
template <int N> __device__ __forceinline__ void undef_regs(float (&a)[N]) {
  #pragma unroll
  for (int i = 0; i < N; i++) asm volatile("" : "=f"(a[i]));
}

__device__ __forceinline__ uint64_t desc_from_lo(uint32_t lo) { return (uint64_t)lo | ((uint64_t)0x40000040u << 32); }
__device__ __forceinline__ uint32_t pack_bf16(float lo, float hi) {
  uint32_t r; asm("cvt.rn.bf16x2.f32 %0, %1, %2;" : "=r"(r) : "f"(hi), "f"(lo)); return r;
}
__device__ __forceinline__ uint32_t fma_bf2(uint32_t a, uint32_t b, uint32_t c) {
  uint32_t d; asm("fma.rn.bf16x2 %0, %1, %2, %3;" : "=r"(d) : "r"(a), "r"(b), "r"(c)); return d;
}
__device__ __forceinline__ float bf_lo(uint32_t v) { return __uint_as_float(v << 16); }
__device__ __forceinline__ float bf_hi(uint32_t v) { return __uint_as_float(v & 0xFFFF0000u); }
__device__ __forceinline__ float bf16_round(float x) { return bf_lo(pack_bf16(x, 0.f)); }
__device__ __forceinline__ void stmatrix_x4(uint32_t addr, uint32_t r0, uint32_t r1, uint32_t r2, uint32_t r3) {
  asm volatile("stmatrix.sync.aligned.m8n8.x4.shared.b16 [%0], {%1, %2, %3, %4};" :: "r"(addr), "r"(r0), "r"(r1), "r"(r2), "r"(r3) : "memory");
}
__device__ __forceinline__ void stmatrix_x4_if(uint32_t addr, uint32_t r0, uint32_t r1, uint32_t r2, uint32_t r3, bool on) {
  asm volatile("{\n.reg .pred p;\nsetp.ne.b32 p, %5, 0;\n@p stmatrix.sync.aligned.m8n8.x4.shared.b16 [%0], {%1, %2, %3, %4};\n}"
               :: "r"(addr), "r"(r0), "r"(r1), "r"(r2), "r"(r3), "r"((int)on) : "memory");
}
__device__ __forceinline__ void ldmatrix_x4(uint32_t addr, uint32_t& r0, uint32_t& r1, uint32_t& r2, uint32_t& r3) {
  asm volatile("ldmatrix.sync.aligned.m8n8.x4.shared.b16 {%0, %1, %2, %3}, [%4];" : "=r"(r0), "=r"(r1), "=r"(r2), "=r"(r3) : "r"(addr) : "memory");
}
__device__ __forceinline__ void ldmatrix_x4_t(uint32_t addr, uint32_t (&r)[4]) {
  asm volatile("ldmatrix.sync.aligned.m8n8.x4.trans.shared.b16 {%0, %1, %2, %3}, [%4];" : "=r"(r[0]), "=r"(r[1]), "=r"(r[2]), "=r"(r[3]) : "r"(addr) : "memory");
}
__device__ __forceinline__ uint32_t tagf(float v, unsigned par) { return (__float_as_uint(v) & ~1u) | par; }
__device__ __forceinline__ void st_rlx(void* p, uint32_t a, bool on) {
  asm volatile("{\n.reg .pred p;\nsetp.ne.b32 p, %2, 0;\n@p st.relaxed.gpu.global.u32 [%0], %1;\n}" :: "l"(p), "r"(a), "r"((int)on) : "memory");
}
__device__ __forceinline__ void st_rlx_v2(void* p, uint32_t a, uint32_t b, bool on) {
  asm volatile("{\n.reg .pred p;\nsetp.ne.b32 p, %3, 0;\n@p st.relaxed.gpu.global.v2.u32 [%0], {%1, %2};\n}" :: "l"(p), "r"(a), "r"(b), "r"((int)on) : "memory");
}
__device__ __forceinline__ uint2 ld_rlx_v2(const void* p) {
  uint2 v; asm volatile("ld.relaxed.gpu.global.v2.u32 {%0,%1}, [%2];" : "=r"(v.x), "=r"(v.y) : "l"(p) : "memory"); return v;
}
__device__ __forceinline__ void st_rlx_v4(void* p, uint32_t a, uint32_t b, uint32_t c, uint32_t d, bool on) {
  asm volatile("{\n.reg .pred p;\nsetp.ne.b32 p, %5, 0;\n@p st.relaxed.gpu.global.v4.u32 [%0], {%1, %2, %3, %4};\n}"
               :: "l"(p), "r"(a), "r"(b), "r"(c), "r"(d), "r"((int)on) : "memory");
}
__device__ __forceinline__ uint4 ld_rlx_v4(const void* p) {
  uint4 v; asm volatile("ld.relaxed.gpu.global.v4.u32 {%0,%1,%2,%3}, [%4];" : "=r"(v.x), "=r"(v.y), "=r"(v.z), "=r"(v.w) : "l"(p) : "memory"); return v;
}
__device__ __forceinline__ uint32_t movmatrix_t(uint32_t a) {
  uint32_t d; asm volatile("movmatrix.sync.aligned.m8n8.trans.b16 %0, %1;" : "=r"(d) : "r"(a)); return d;
}
__device__ __forceinline__ void mma16(float (&c)[4], uint32_t a0, uint32_t a1, uint32_t a2, uint32_t a3, uint32_t b0, uint32_t b1) {
  asm volatile("mma.sync.aligned.m16n8k16.row.col.f32.bf16.bf16.f32 {%0,%1,%2,%3}, {%4,%5,%6,%7}, {%8,%9}, {%0,%1,%2,%3};"
               : "+f"(c[0]), "+f"(c[1]), "+f"(c[2]), "+f"(c[3]) : "r"(a0), "r"(a1), "r"(a2), "r"(a3), "r"(b0), "r"(b1));
}
__device__ __forceinline__ void mma8(float (&c)[4], uint32_t a0, uint32_t a1, uint32_t b0) {
  asm volatile("mma.sync.aligned.m16n8k8.row.col.f32.bf16.bf16.f32 {%0,%1,%2,%3}, {%4,%5}, {%6}, {%0,%1,%2,%3};"
               : "+f"(c[0]), "+f"(c[1]), "+f"(c[2]), "+f"(c[3]) : "r"(a0), "r"(a1), "r"(b0));
}
__device__ __forceinline__ void sts128(uint32_t addr, uint32_t a, uint32_t b, uint32_t c, uint32_t d) {
  asm volatile("st.shared.v4.b32 [%0], {%1,%2,%3,%4};" :: "r"(addr), "r"(a), "r"(b), "r"(c), "r"(d) : "memory");
}
__device__ __forceinline__ uint4 lds128(uint32_t addr) {
  uint4 v; asm volatile("ld.shared.v4.b32 {%0,%1,%2,%3}, [%4];" : "=r"(v.x), "=r"(v.y), "=r"(v.z), "=r"(v.w) : "r"(addr) : "memory"); return v;
}
__device__ __forceinline__ uint32_t lds32(uint32_t addr) {
  uint32_t v; asm volatile("ld.shared.b32 %0, [%1];" : "=r"(v) : "r"(addr) : "memory"); return v;
}
__device__ __forceinline__ float2 lds64f(uint32_t addr) {
  float2 v; asm volatile("ld.shared.v2.f32 {%0,%1}, [%2];" : "=f"(v.x), "=f"(v.y) : "r"(addr) : "memory"); return v;
}
__device__ __forceinline__ void sts64(uint32_t addr, uint32_t a, uint32_t b) {
  asm volatile("st.shared.v2.b32 [%0], {%1, %2};" :: "r"(addr), "r"(a), "r"(b) : "memory");
}
__device__ __forceinline__ float fast_ex2(float x) { float y; asm("ex2.approx.ftz.f32 %0, %1;" : "=f"(y) : "f"(x)); return y; }
__device__ __forceinline__ float fast_rcp(float x) { float y; asm("rcp.approx.ftz.f32 %0, %1;" : "=f"(y) : "f"(x)); return y; }
__device__ __forceinline__ float fast_rsqrt(float x) { float y; asm("rsqrt.approx.ftz.f32 %0, %1;" : "=f"(y) : "f"(x)); return y; }
__device__ __forceinline__ float silu_f(float g) { return g * fast_rcp(1.f + fast_ex2(g * -1.4426950408889634f)); }
__device__ __forceinline__ float swiglu(float g, float u) {
  const float h = 0.5f * g;
  float t; asm("tanh.approx.f32 %0, %1;" : "=f"(t) : "f"(h));
  return fmaf(h, t, h) * u;
}

__device__ __forceinline__ void wgmma_m64n128k16_ss(float (&d)[64], uint64_t descA, uint64_t descB, int scaleD) {
  asm volatile("{\n.reg .pred p;\nsetp.ne.b32 p, %66, 0;\n"
    "wgmma.mma_async.sync.aligned.m64n128k16.f32.bf16.bf16 "
    "{%0, %1, %2, %3, %4, %5, %6, %7, %8, %9, %10, %11, %12, %13, %14, %15, "
    "%16, %17, %18, %19, %20, %21, %22, %23, %24, %25, %26, %27, %28, %29, %30, %31, "
    "%32, %33, %34, %35, %36, %37, %38, %39, %40, %41, %42, %43, %44, %45, %46, %47, "
    "%48, %49, %50, %51, %52, %53, %54, %55, %56, %57, %58, %59, %60, %61, %62, %63}, "
    "%64, %65, p, 1, 1, 0, 1;\n}\n"
    : "+f"(d[0]), "+f"(d[1]), "+f"(d[2]), "+f"(d[3]), "+f"(d[4]), "+f"(d[5]), "+f"(d[6]), "+f"(d[7]),
      "+f"(d[8]), "+f"(d[9]), "+f"(d[10]), "+f"(d[11]), "+f"(d[12]), "+f"(d[13]), "+f"(d[14]), "+f"(d[15]),
      "+f"(d[16]), "+f"(d[17]), "+f"(d[18]), "+f"(d[19]), "+f"(d[20]), "+f"(d[21]), "+f"(d[22]), "+f"(d[23]),
      "+f"(d[24]), "+f"(d[25]), "+f"(d[26]), "+f"(d[27]), "+f"(d[28]), "+f"(d[29]), "+f"(d[30]), "+f"(d[31]),
      "+f"(d[32]), "+f"(d[33]), "+f"(d[34]), "+f"(d[35]), "+f"(d[36]), "+f"(d[37]), "+f"(d[38]), "+f"(d[39]),
      "+f"(d[40]), "+f"(d[41]), "+f"(d[42]), "+f"(d[43]), "+f"(d[44]), "+f"(d[45]), "+f"(d[46]), "+f"(d[47]),
      "+f"(d[48]), "+f"(d[49]), "+f"(d[50]), "+f"(d[51]), "+f"(d[52]), "+f"(d[53]), "+f"(d[54]), "+f"(d[55]),
      "+f"(d[56]), "+f"(d[57]), "+f"(d[58]), "+f"(d[59]), "+f"(d[60]), "+f"(d[61]), "+f"(d[62]), "+f"(d[63])
    : "l"(descA), "l"(descB), "r"(scaleD));
}
__device__ __forceinline__ void wgmma_m64n256k16_rs(float (&d)[128], uint32_t a0, uint32_t a1, uint32_t a2, uint32_t a3, uint64_t descB, int scaleD) {
  asm volatile("{\n.reg .pred p;\nsetp.ne.b32 p, %133, 0;\n"
    "wgmma.mma_async.sync.aligned.m64n256k16.f32.bf16.bf16 "
    "{%0, %1, %2, %3, %4, %5, %6, %7, %8, %9, %10, %11, %12, %13, %14, %15, "
    "%16, %17, %18, %19, %20, %21, %22, %23, %24, %25, %26, %27, %28, %29, %30, %31, "
    "%32, %33, %34, %35, %36, %37, %38, %39, %40, %41, %42, %43, %44, %45, %46, %47, "
    "%48, %49, %50, %51, %52, %53, %54, %55, %56, %57, %58, %59, %60, %61, %62, %63, "
    "%64, %65, %66, %67, %68, %69, %70, %71, %72, %73, %74, %75, %76, %77, %78, %79, "
    "%80, %81, %82, %83, %84, %85, %86, %87, %88, %89, %90, %91, %92, %93, %94, %95, "
    "%96, %97, %98, %99, %100, %101, %102, %103, %104, %105, %106, %107, %108, %109, %110, %111, "
    "%112, %113, %114, %115, %116, %117, %118, %119, %120, %121, %122, %123, %124, %125, %126, %127}, "
    "{%128, %129, %130, %131}, %132, p, 1, 1, 1;\n}\n"
    : "+f"(d[0]), "+f"(d[1]), "+f"(d[2]), "+f"(d[3]), "+f"(d[4]), "+f"(d[5]), "+f"(d[6]), "+f"(d[7]),
      "+f"(d[8]), "+f"(d[9]), "+f"(d[10]), "+f"(d[11]), "+f"(d[12]), "+f"(d[13]), "+f"(d[14]), "+f"(d[15]),
      "+f"(d[16]), "+f"(d[17]), "+f"(d[18]), "+f"(d[19]), "+f"(d[20]), "+f"(d[21]), "+f"(d[22]), "+f"(d[23]),
      "+f"(d[24]), "+f"(d[25]), "+f"(d[26]), "+f"(d[27]), "+f"(d[28]), "+f"(d[29]), "+f"(d[30]), "+f"(d[31]),
      "+f"(d[32]), "+f"(d[33]), "+f"(d[34]), "+f"(d[35]), "+f"(d[36]), "+f"(d[37]), "+f"(d[38]), "+f"(d[39]),
      "+f"(d[40]), "+f"(d[41]), "+f"(d[42]), "+f"(d[43]), "+f"(d[44]), "+f"(d[45]), "+f"(d[46]), "+f"(d[47]),
      "+f"(d[48]), "+f"(d[49]), "+f"(d[50]), "+f"(d[51]), "+f"(d[52]), "+f"(d[53]), "+f"(d[54]), "+f"(d[55]),
      "+f"(d[56]), "+f"(d[57]), "+f"(d[58]), "+f"(d[59]), "+f"(d[60]), "+f"(d[61]), "+f"(d[62]), "+f"(d[63]),
      "+f"(d[64]), "+f"(d[65]), "+f"(d[66]), "+f"(d[67]), "+f"(d[68]), "+f"(d[69]), "+f"(d[70]), "+f"(d[71]),
      "+f"(d[72]), "+f"(d[73]), "+f"(d[74]), "+f"(d[75]), "+f"(d[76]), "+f"(d[77]), "+f"(d[78]), "+f"(d[79]),
      "+f"(d[80]), "+f"(d[81]), "+f"(d[82]), "+f"(d[83]), "+f"(d[84]), "+f"(d[85]), "+f"(d[86]), "+f"(d[87]),
      "+f"(d[88]), "+f"(d[89]), "+f"(d[90]), "+f"(d[91]), "+f"(d[92]), "+f"(d[93]), "+f"(d[94]), "+f"(d[95]),
      "+f"(d[96]), "+f"(d[97]), "+f"(d[98]), "+f"(d[99]), "+f"(d[100]), "+f"(d[101]), "+f"(d[102]), "+f"(d[103]),
      "+f"(d[104]), "+f"(d[105]), "+f"(d[106]), "+f"(d[107]), "+f"(d[108]), "+f"(d[109]), "+f"(d[110]), "+f"(d[111]),
      "+f"(d[112]), "+f"(d[113]), "+f"(d[114]), "+f"(d[115]), "+f"(d[116]), "+f"(d[117]), "+f"(d[118]), "+f"(d[119]),
      "+f"(d[120]), "+f"(d[121]), "+f"(d[122]), "+f"(d[123]), "+f"(d[124]), "+f"(d[125]), "+f"(d[126]), "+f"(d[127])
    : "r"(a0), "r"(a1), "r"(a2), "r"(a3), "l"(descB), "r"(scaleD));
}

constexpr uint32_t MSLOT = 32768, QSLOT = 49152;
constexpr int NM = 6;
constexpr uint32_t SM_X0 = 3 * QSLOT;
constexpr uint32_t SM_XR = SM_X0 + 16384;
constexpr uint32_t SM_STG = 196608;
constexpr uint32_t SM_XCH = SM_STG + 16384;
constexpr uint32_t SM_BAR = SM_STG + 32768;
constexpr uint32_t SM_VEC = SM_BAR + 512;
constexpr uint32_t SM_MODT = SM_VEC;
constexpr uint32_t SM_TOTAL = SM_VEC + 2048;
constexpr uint32_t B_X = SM_BAR  , B_EQ = B_X + 64, B_EM = B_EQ + 32, B_STREQ = B_EM + 48, B_STH = B_STREQ + 8, B_LN = B_STH + 8,
                   B_FQ = B_LN + 8, B_FM = B_FQ + 32, B_MOD = B_FM + 48, B_GATE = B_MOD + 8, B_STFREE = B_GATE + 8, B_VEC = B_STFREE + 8  ,
                   B_FLG = B_VEC + 16  , B_H2A = B_FLG + 88, B_RST = B_H2A + 8, B_END = B_RST + 8;
constexpr int NB_WG = 1  , NB_CONS = 3, NB_ORD = 4  ;
#define PF_BYTES 512
#define X_S1 7
#define X_POLL 5
#define SVC_WAIT mbar_sleep
#define PRD_WAIT mbar_wait
#define WPRE 2
#define HOLD1 1
#define HOLD2 0
#define ST0 0
#define QORD 2
#define QPOS 1
#define AUX_SLOW 68
#define AUX_GAP 500
#define DTAIL 4
#define EF 7
#define TRG_WAIT mbar_wait
#define ST_SPIN0 2
#define AUX_HOLD 3200
#define X_UP 1
#define X_GAP 250

struct Maps {
  CUtensorMap x, out;
  CUtensorMap o, h2, hh;
  CUtensorMap wqk, wvv, wq1, wo, w1, w3, w2;
  CUtensorMap wmod;
};

struct Ring { int st; uint32_t ph; int prev; uint32_t dl; };
__device__ __forceinline__ void ring_next(Ring& r) { if (++r.st == NM) { r.st = 0; r.ph ^= 1; } }

__device__ __forceinline__ void retire_prev(uint32_t rel, bool on) {
  wgmma_commit();
  wgmma_wait<1>();
  if (on) mbar_arrive_e(rel);
}
struct Nop { __device__ __forceinline__ void operator()() const {} };
template <bool REL = true, class F = Nop>
__device__ __forceinline__ void mma_step(float (&acc)[64], uint32_t a, uint32_t b, bool first, uint32_t rel, F urgent = F()) {
  const uint32_t alo = (a >> 4) + (1u << 16), blo = (b >> 4) + (512u << 16);
  wgmma_fence();
  #pragma unroll
  for (int k = 0; k < 4; k++) {
    wgmma_m64n128k16_ss(acc, desc_from_lo(alo + k * 2), desc_from_lo(blo + k * 128), k > 0 || !first);
    if (k == 0) { retire_prev(rel, REL); urgent(); }
  }
  wgmma_commit();
}
__device__ __forceinline__ uint32_t m_wait(uint32_t sbase, const Ring& r) {
  mbar_wait(sbase + B_FM + 8 * r.st, r.ph, r.dl);
  return sbase + r.st * MSLOT;
}
__device__ __forceinline__ uint32_t m_prev(uint32_t sbase, const Ring& r) { return sbase + B_EM + 8 * r.prev; }
__device__ __forceinline__ void m_next(Ring& r) { r.prev = r.st; ring_next(r); }
__device__ __forceinline__ void m_step(float (&acc)[64], uint32_t sbase, uint32_t wgoff, Ring& r, bool first = false) {
  const uint32_t slot = m_wait(sbase, r);
  mma_step(acc, slot + wgoff, slot + 16384, first, m_prev(sbase, r));
  m_next(r);
}

struct LnRow { uint32_t rs[2], nb[2]; };
__device__ __forceinline__ void ln_row(LnRow& l, int h, float mean, float rstd) {
  l.rs[h] = pack_bf16(rstd, rstd);
  const float nb = -mean * bf_lo(l.rs[h]);
  l.nb[h] = pack_bf16(nb, nb);
}
__device__ __forceinline__ uint32_t ln_mod(uint32_t x, const LnRow& l, int h, uint32_t c1, uint32_t s) {
  return fma_bf2(fma_bf2(x, l.rs[h], l.nb[h]), c1, s);
}

__device__ __forceinline__ uint32_t q_wait(int u, uint32_t sbase, uint32_t dl) {
  mbar_wait(sbase + B_FQ + 8 * (u & 3), (u >> 2) & 1, dl);
  return sbase + (u & 3) * QSLOT;
}
__device__ __forceinline__ uint32_t q_empty(int u, uint32_t sbase) { return sbase + B_EQ + 8 * (u & 3); }
struct Frag4 { uint32_t o[4]; };
__device__ __forceinline__ void q_load(uint32_t (&A)[16], uint4 (&p)[4], int kk, uint32_t tile, const Frag4& f, uint32_t t) {
  ldmatrix_x4(tile + f.o[kk], A[4 * kk], A[4 * kk + 1], A[4 * kk + 2], A[4 * kk + 3]);
  p[kk] = lds128(t + kk * 64);
}
__device__ __forceinline__ void q_norm(uint32_t (&A)[16], const uint4 (&p)[4], int kk, const LnRow& l) {
  A[4 * kk + 0] = ln_mod(A[4 * kk + 0], l, 0, p[kk].x, p[kk].z); A[4 * kk + 1] = ln_mod(A[4 * kk + 1], l, 1, p[kk].x, p[kk].z);
  A[4 * kk + 2] = ln_mod(A[4 * kk + 2], l, 0, p[kk].y, p[kk].w); A[4 * kk + 3] = ln_mod(A[4 * kk + 3], l, 1, p[kk].y, p[kk].w);
}
template <bool NEXT>
__device__ __forceinline__ void q_step_rs(float (&acc)[128], uint32_t (&A)[16], uint32_t (&N)[16], uint4 (&p)[4], int u, uint32_t sbase,
                                          const Frag4& f, uint32_t tab, const LnRow& l, int hq, bool first, uint32_t dl, int wg) {
  const uint32_t slot = first ? sbase : q_wait(u, sbase, dl);
  const uint32_t blo = ((slot + 16384) >> 4) + (512u << 16), t = tab + ((u + 1) & 7) * 256;
  #pragma unroll
  for (int kk = 0; kk < 4; kk++) q_norm(A, p, kk, l);
  if (first) {
    #pragma unroll
    for (int i = 0; i < 16; i++) asm volatile("" : "+r"(A[i]));
    mbar_wait(sbase + B_GATE, 0, dl);
    PROF(6, threadIdx.x == 0);
  }
  if (QORD == 1 && first && wg == 1) bar_sync(NB_ORD, 256);
  if (QORD == 2 && !(first && wg == 0)) bar_sync(NB_ORD + wg, 256);
  wgmma_fence();
  #pragma unroll
  for (int kk = 0; kk < 4; kk++) {
    wgmma_m64n256k16_rs(acc, A[4 * kk], A[4 * kk + 1], A[4 * kk + 2], A[4 * kk + 3], desc_from_lo(blo + kk * 128), kk > 0 || !first);
    if (kk == 0) retire_prev(q_empty(u - 1, sbase), !first);
    if (NEXT && kk < 2) { q_load(N, p, 2 * kk, slot, f, t); q_load(N, p, 2 * kk + 1, slot, f, t); }
    if (QORD == 1 && first && kk == QPOS && wg == 0) bar_arrive(NB_ORD, 256);
    if (QORD == 2 && kk == QPOS && (NEXT || wg == 0)) bar_arrive(NB_ORD + (wg ^ 1), 256);
    if (kk == 1) {
      const uint32_t dst = sbase + SM_STG + (u >> 3) * 16384 + (f.o[0] ^ ((u & 6) << 4));
      #pragma unroll
      for (int q = 0; q < 4; q++) stmatrix_x4_if(dst, A[4 * q], A[4 * q + 1], A[4 * q + 2], A[4 * q + 3], hq == q);
    }
  }
  wgmma_commit();
}

typedef uint32_t Frag8[8];
template <int N> __device__ __forceinline__ void pack_half(Frag8& f, const float (&acc)[N], int off, int half) {
  #pragma unroll
  for (int e = 0; e < 8; e++) { f[e] = pack_bf16(acc[off + 4 * e + 2 * half], acc[off + 4 * e + 2 * half + 1]); asm volatile("" : "+r"(f[e])); }
}
__device__ __forceinline__ void transpose8(Frag8& f) {
  #pragma unroll
  for (int e = 0; e < 8; e++) f[e] = movmatrix_t(f[e]);
}
__device__ __forceinline__ void attn_send(const Frag8& f, int kv, uint32_t xch, int warp, uint4* halo_out, bool has_next) {
  if (warp == 3) {
    st_rlx_v4(halo_out + kv * 64, f[0], f[1], f[2], f[3], has_next); st_rlx_v4(halo_out + kv * 64 + 32, f[4], f[5], f[6], f[7], has_next);
  } else {
    sts128(xch + 2048 + kv * 1024, f[0], f[1], f[2], f[3]); sts128(xch + 2048 + kv * 1024 + 512, f[4], f[5], f[6], f[7]);
  }
}
template <int N>
__device__ __forceinline__ void attn_recv(uint4* p, int first, uint32_t xch, int wg, int warp, const uint4* halo_in, bool has_prev) {
  bar_sync(NB_WG + wg, 128);
  #pragma unroll
  for (int e = 0; e < N; e++)
    asm volatile("{\n.reg .pred p, q;\nsetp.ne.b32 p, %6, 0;\nsetp.ne.b32 q, %7, 0;\n"
                 "mov.b32 %0, 0;\nmov.b32 %1, 0;\nmov.b32 %2, 0;\nmov.b32 %3, 0;\n"
                 "@p ld.shared.v4.b32 {%0,%1,%2,%3}, [%4];\n@q ld.relaxed.gpu.global.v4.u32 {%0,%1,%2,%3}, [%5];\n}"
                 : "=&r"(p[e].x), "=&r"(p[e].y), "=&r"(p[e].z), "=&r"(p[e].w)
                 : "r"(xch + (first + e) * 512), "l"(halo_in + (first + e) * 32), "r"((int)(warp > 0)), "r"((int)(warp == 0 && has_prev)) : "memory");
}
template <int N>
__device__ __forceinline__ void attn_check(uint4* p, int first, int warp, const uint4* halo_in, uint32_t dl) {
  if (warp == 0) {
    while (true) {
      uint32_t m = 0;
      #pragma unroll
      for (int e = 0; e < N; e++) m = max(max(m, max(p[e].x, p[e].y)), max(p[e].z, p[e].w));
      if (poll_done(m != ~0u, dl)) break;
      #pragma unroll
      for (int e = 0; e < N; e++) p[e] = ld_rlx_v4(halo_in + (first + e) * 32);
    }
  }
}
__device__ __forceinline__ void attn_core(const Frag8& qA, const Frag8& qB, const Frag8& kA, const Frag8& kB, const Frag8& vA, const Frag8& vB,
                                          const uint4* kP, const uint4* vP, bool noprev, int lane, float (&o)[2][5][4]) {
  const int g = lane >> 2, qd = lane & 3;
  const bool s0 = 2 * qd > g, s1 = 2 * qd + 1 > g;
  const uint32_t msk = (s0 ? 0xFFFFu : 0u) | (s1 ? 0xFFFF0000u : 0u);
  constexpr float SC = 0.17677669529663687f * 1.4426950408889634f;
  float s[2][3][4];
  #pragma unroll
  for (int h = 0; h < 2; h++)
    #pragma unroll
    for (int nb = 0; nb < 3; nb++) s[h][nb][0] = s[h][nb][1] = s[h][nb][2] = s[h][nb][3] = 0.f;
  #pragma unroll
  for (int kk = 0; kk < 2; kk++)
    #pragma unroll
    for (int h = 0; h < 2; h++) {
      const int e = 4 * h + 2 * kk;
      mma16(s[h][1], qA[e], qB[e], qA[e + 1], qB[e + 1], kA[e], kA[e + 1]);
      mma16(s[h][2], qA[e], qB[e], qA[e + 1], qB[e + 1], kB[e], kB[e + 1]);
      mma16(s[h][0], qA[e], qB[e], qA[e + 1], qB[e + 1], kk ? kP[h].z : kP[h].x, kk ? kP[h].w : kP[h].y);
    }
  float l[2][4], m[2][2];
  #pragma unroll
  for (int h = 0; h < 2; h++) {
    l[h][0] = s0 ? (noprev ? -INFINITY : s[h][0][0]) : s[h][1][0];
    l[h][1] = s1 ? (noprev ? -INFINITY : s[h][0][1]) : s[h][1][1];
    l[h][2] = s0 ? s[h][1][2] : s[h][2][2];
    l[h][3] = s1 ? s[h][1][3] : s[h][2][3];
    m[h][0] = fmaxf(l[h][0], l[h][1]); m[h][1] = fmaxf(l[h][2], l[h][3]);
  }
  #pragma unroll
  for (int x = 1; x <= 2; x <<= 1)
    #pragma unroll
    for (int e = 0; e < 4; e++) m[e >> 1][e & 1] = fmaxf(m[e >> 1][e & 1], __shfl_xor_sync(0xffffffffu, m[e >> 1][e & 1], x));
  #pragma unroll
  for (int h = 0; h < 2; h++) {
    #pragma unroll
    for (int e = 0; e < 4; e++) l[h][e] = fast_ex2((l[h][e] - m[h][e >> 1]) * SC);
    const uint32_t plo = pack_bf16(l[h][0], l[h][1]), phi = pack_bf16(l[h][2], l[h][3]);
    const uint32_t vp[4] = {vP[h].x, vP[h].y, vP[h].z, vP[h].w};
    #pragma unroll
    for (int d = 0; d < 5; d++) o[h][d][0] = o[h][d][1] = o[h][d][2] = o[h][d][3] = 0.f;
    mma8(o[h][4], plo, phi, 0x3F803F80u);
    #pragma unroll
    for (int d = 0; d < 4; d++) mma16(o[h][d], plo & ~msk, phi & msk, 0u, phi & ~msk, vA[4 * h + d], vB[4 * h + d]);
    #pragma unroll
    for (int d = 0; d < 4; d++) mma8(o[h][d], plo & msk, 0u, vp[d]);
  }
}
__device__ __forceinline__ void attn_store(const float (&o)[2][5][4], int h, uint32_t sbase, const Frag4& f) {
  const float r0 = fast_rcp(o[h][4][0]), r1 = fast_rcp(o[h][4][2]);
  #pragma unroll
  for (int d = 0; d < 4; d += 2)
    stmatrix_x4(sbase + SM_STG + f.o[2 * h + (d >> 1)],
                pack_bf16(o[h][d][0] * r0, o[h][d][1] * r0), pack_bf16(o[h][d][2] * r1, o[h][d][3] * r1),
                pack_bf16(o[h][d + 1][0] * r0, o[h][d + 1][1] * r0), pack_bf16(o[h][d + 1][2] * r1, o[h][d + 1][3] * r1));
}

__device__ __forceinline__ void request_store(uint32_t bar) {
  fence_proxy_async_smem();
  mbar_arrive_e(bar);
}

__device__ __forceinline__ void g_switch(float (&cur)[64], float (&prv)[64], int nrest, bool first, int n, uint32_t sbase, uint32_t wgoff,
                                         const Frag4& f, Ring& r) {
  #pragma unroll 1
  for (int i = 1; i < nrest; i++) m_step(prv, sbase, wgoff, r);
  m_step(prv, sbase, wgoff, r);
  m_step(cur, sbase, wgoff, r, first);
  mbar_wait(sbase + B_STFREE, (n - 1) & 1, r.dl);
  fence_regs(prv);
  PROF(28 + n, threadIdx.x == 0);
  #pragma unroll
  for (int jj = 0; jj < 4; jj++) {
    uint32_t p[4];
    #pragma unroll
    for (int e = 0; e < 4; e++) {
      const int i = jj * 8 + e * 2;
      p[e] = pack_bf16(swiglu(prv[i], prv[i + 32]), swiglu(prv[i + 1], prv[i + 33]));
    }
    stmatrix_x4(sbase + SM_STG + f.o[jj], p[0], p[1], p[2], p[3]);
    m_step(cur, sbase, wgoff, r);
  }
  request_store(sbase + B_STREQ);
}

__device__ __forceinline__ uint32_t bad2(uint32_t a, uint32_t b, unsigned par) {
  uint32_t d; asm("lop3.b32 %0, %1, %2, %3, 0x7E;" : "=r"(d) : "r"(a), "r"(b), "r"(par)); return d;
}
__device__ __forceinline__ uint32_t bad4(const uint4& v, unsigned par) { return bad2(v.x, v.y, par) | bad2(v.z, v.w, par); }
__device__ __forceinline__ uint32_t hi_halves(uint32_t lo, uint32_t hi) { return __byte_perm(lo, hi, 0x7632); }

__device__ __forceinline__ void gather_table(const float* src, uint32_t dst, uint32_t bar, unsigned par, uint32_t dl) {
  asm volatile("{\n.reg .pred p, e;\n.reg .b32 s<4>, c<4>, t<4>, w<4>;\n"
               "elect.sync _|e, 0xffffffff;\n"
               "LAB_POLL:\n"
               "ld.relaxed.gpu.global.v4.u32 {s0, s1, s2, s3}, [%0];\n"
               "ld.relaxed.gpu.global.v4.u32 {c0, c1, c2, c3}, [%0 + 4096];\n"
               "prmt.b32 w0, c0, c1, 0x7632;\nprmt.b32 w1, c2, c3, 0x7632;\nprmt.b32 w2, s0, s1, 0x7632;\nprmt.b32 w3, s2, s3, 0x7632;\n"
               "st.shared.v4.b32 [%1], {w0, w1, w2, w3};\n"
               "lop3.b32 t0, s0, s1, %3, 0x7E;\nlop3.b32 t1, s2, s3, %3, 0x7E;\nlop3.b32 t2, c0, c1, %3, 0x7E;\nlop3.b32 t3, c2, c3, %3, 0x7E;\n"
               "lop3.b32 t0, t0, t1, 1, 0xA8;\nlop3.b32 t2, t2, t3, 1, 0xA8;\n"
               "or.b32 t0, t0, t2;\n"
               "setp.eq.u32 p, t0, 0;\n"
               "vote.sync.all.pred p, p, 0xffffffff;\n"
               "@p bra.uni LAB_OK;\n"
               "mov.u32 t0, %%clock;\nsub.s32 t0, t0, %4;\nsetp.lt.s32 p, t0, 0;\n"
               "vote.sync.all.pred p, p, 0xffffffff;\n"
               "@p bra.uni LAB_POLL;\n"
               "LAB_OK:\n"
               "@e mbarrier.arrive.shared::cta.b64 _, [%2];\n}"
               :: "l"(src), "r"(dst), "r"(bar), "r"(par), "r"(dl) : "memory");
}

__device__ __forceinline__ int other_slot(int i, int j) { return i < 4 ? (~j & 4) + i : (j & 4) + i - 4 + (i - 4 >= (j & 3)); }

__device__ __forceinline__ int aux_col(int a, int u) { return u < 8 ? (a & 1) * 1024 + (2 * u + (a >> 1)) * 64 : 2048 + ((u - 8) * 4 + a) * 64; }
constexpr int NA = 7;
constexpr uint32_t A_FULL = SM_BAR, A_EMPTY = SM_BAR + 64, A_SUM = SM_BAR + 128, A_FREE = SM_BAR + 136, SM_RED = SM_VEC;
__device__ __forceinline__ void aux_role(const Maps& maps, const bf16* __restrict__ cvec, Mail* mail0, int zero, int a, uint32_t sbase, int wid) {
  const int tid = threadIdx.x, lane = tid & 31;
  const uint32_t dl = clock32() + 800000000u;
  int st = 0; uint32_t ph = 0;
  if (wid == 8) {
    prefetch_tmap(&maps.wmod);
    #pragma unroll
    for (int i = 0; i < 18; i++) mbar_init_e(sbase + A_FULL + 8 * i, i < 8 ? 1 : i < 17 ? 8 : 2);
    fence_proxy_async_smem();
    bar_arrive(0, 352);
    PROF(39, lane == 0);
    #pragma unroll
    for (int i = 0; i < NA; i++) {
      mbar_expect_tx_e(sbase + A_FULL + 8 * i, 32768);
      tma_load_2d(sbase + i * MSLOT, &maps.wmod, sbase + A_FULL + 8 * i, aux_col(a, i >> 2), (i & 3) * 256);
    }
    PROF(40, lane == 0);
    #pragma unroll 1
    for (int i = NA; i < 96; i++) {
      if (i >= AUX_SLOW) wait_until(clock32() + AUX_GAP);
      if (i == 8) wait_until(dl - 800000000u + AUX_HOLD);
      mbar_wait(sbase + A_EMPTY + 8 * st, ph, dl);
      mbar_expect_tx_e(sbase + A_FULL + 8 * st, 32768);
      tma_load_2d<(EF & 1) != 0>(sbase + st * MSLOT, &maps.wmod, sbase + A_FULL + 8 * st, aux_col(a, i >> 2), (i & 3) * 256);
      if (++st == NA) { st = 0; ph ^= 1; }
    }
  } else if (wid < 8) {
    const int g = lane >> 2, qd = lane & 3;
    uint32_t sc[16];
    const uint2 c = *reinterpret_cast<const uint2*>(cvec + tid * 4);
    sts64(sbase + SM_RED + tid * 8, pack_bf16(silu_f(bf_lo(c.x)), silu_f(bf_hi(c.x))), pack_bf16(silu_f(bf_lo(c.y)), silu_f(bf_hi(c.y))));
    bar_sync(0, 352);
    #pragma unroll
    for (int i = 0; i < 16; i++) sc[i] = lds32(sbase + SM_RED + ((i >> 2) * 256 + wid * 32 + (i & 3) * 8 + qd * 2) * 2);
    bar_sync(NB_CONS, 256);
    PROF(38, tid == 0);
    const uint32_t aoff = (wid * 32 + (lane & 7) + (lane >> 4) * 8) * 128 + ((((lane >> 3) & 1) ^ (lane & 7)) << 4);
    uint32_t w[2][8][4];
    auto fetch = [&](uint32_t (&f)[8][4]) {
      mbar_wait(sbase + A_FULL + 8 * st, ph, dl);
      #pragma unroll
      for (int e = 0; e < 8; e++) ldmatrix_x4_t((sbase + st * MSLOT + aoff + (e >> 2) * 2048) ^ ((e & 3) << 5), f[e]);
      if (++st == NA) { st = 0; ph ^= 1; }
    };
    #pragma unroll 1
    for (int u = 0; u < 24; u++) {
      float acc[4][4];
      #pragma unroll
      for (int m = 0; m < 4; m++) acc[m][0] = acc[m][1] = acc[m][2] = acc[m][3] = 0.f;
      fetch(w[0]);
      #pragma unroll
      for (int q = 0; q < 4; q++) {
        PROF(30 + (u & 1) * 4 + q, u < 2 && tid == 0);
        const uint32_t rel = sbase + A_EMPTY + 8 * (st == 0 ? NA - 1 : st - 1);
        if (q < 3) fetch(w[(q + 1) & 1]);
        uint32_t dep = 0;
        #pragma unroll
        for (int e = 0; e < 8; e++) dep |= w[q & 1][e][0];
        mbar_arrive_e(rel + (dep & zero));
        if (q == 1) mbar_wait(sbase + A_FREE, (u & 1) ^ 1, dl);
        #pragma unroll
        for (int e = 0; e < 8; e++) {
          const uint32_t (&f)[4] = w[q & 1][e];
          mma16(acc[e & 3], f[0], f[1], f[2], f[3], sc[4 * q + 2 * (e >> 2)], sc[4 * q + 2 * (e >> 2) + 1]);
        }
      }
      const float v0 = qd & 2 ? (qd & 1 ? acc[3][0] : acc[2][0]) : (qd & 1 ? acc[1][0] : acc[0][0]);
      const float v1 = qd & 2 ? (qd & 1 ? acc[3][2] : acc[2][2]) : (qd & 1 ? acc[1][2] : acc[0][2]);
      sts64(sbase + SM_RED + wid * 256 + (qd * 8 + g) * 8, __float_as_uint(v0), __float_as_uint(v1));
      mbar_arrive_e(sbase + A_SUM);
    }
  } else if (wid < 11) {
    float* const mail = &mail0->mod[(wid - 9) * 4 * 6 * D_ + 2 * lane];
    unsigned par = ld_relaxed(&mail0->flags[FL_EPOCH + (lane >> 5)]);
    bar_sync(0, 352);
    par = (par + 1) & 1;
    #pragma unroll 1
    for (int u = -2; u < 24; u++) {
      if (u >= 0) {
        const int col = aux_col(a, u);
        const float add = (col >> 10) == 1 || (col >> 10) == 4 ? 1.f : 0.f;
        mbar_wait(sbase + A_SUM, u & 1, dl);
        float2 v[8];
        #pragma unroll
        for (int w = 0; w < 8; w++) v[w] = lds64f(sbase + SM_RED + w * 256 + lane * 8);
        const float t0 = ((v[0].x + v[1].x) + (v[2].x + v[3].x)) + ((v[4].x + v[5].x) + (v[6].x + v[7].x));
        const float t1 = ((v[0].y + v[1].y) + (v[2].y + v[3].y)) + ((v[4].y + v[5].y) + (v[6].y + v[7].y));
        const uint32_t w = pack_bf16(add + bf16_round(t0), add + bf16_round(t1)), o = __shfl_xor_sync(0xffffffffu, w, 1);
        const uint32_t m0 = (lane & 1) ? (o & 0xFFFF0000u) : (w << 16), m1 = (lane & 1) ? (w & 0xFFFF0000u) : (o << 16);
        #pragma unroll
        for (int c = 0; c < 4; c++) st_rlx_v2(mail + c * 6 * D_ + col, m0 | par, m1 | par, true);
        mbar_arrive_e(sbase + A_FREE);
        PROF(1 + u, tid == 288);
      }
      #pragma unroll 1
      for (int v = 2 * (u + 2); v < 2 * (u + 3) && v < 24; v++)
        #pragma unroll
        for (int c = 0; c < 4; c++) st_rlx_v2(mail + c * 6 * D_ + aux_col(a, v), par ^ 1, par ^ 1, true);
    }
  }
}

template <int MODE>
__global__ void __launch_bounds__(384, 1)
fused_block_kernel(const bf16* __restrict__ x, const bf16* __restrict__ cvec, const bf16* __restrict__ wmod, Mail* mail0, int zero,
                   const __grid_constant__ Maps maps) {
  extern __shared__ __align__(1024) uint8_t smem_raw[];
  const uint32_t sbase = smem_u32(smem_raw);
  const int tid = threadIdx.x, lane = tid & 31;
  PROFN(0, tid == 0);
  const int wid = __shfl_sync(0xffffffffu, tid >> 5, 0);
  const int b = cta_role<MODE>();
  if (b >= NCTA) { aux_role(maps, cvec, mail0, zero, b - NCTA, sbase, wid); return; }
  const int jg = b >> 6, mb = jg ? 31 - (b >> 2) : (b >> 2), j = 4 * jg + (b & 3);
  const uint32_t dl = clock32() + 800000000u;
  unsigned* const flags = &mail0->flags[mb * 32];
  const int row0 = mb * 128;

  if (wid >= 8) {
    if (wid == 8) {
      #pragma unroll
      for (int i = 0; i < 8; i++) mbar_init_e(sbase + B_X + 8 * i, 1);
      fence_proxy_async_smem();
      #pragma unroll
      for (int q = 0; q < X_UP; q++) {
        mbar_expect_tx_e(sbase + B_X + 8 * q, 4096);
        bulk_load(sbase + SM_XR + q * 4096, x + (size_t)(row0 + j * 16 + 2 * q) * D_, 4096, sbase + B_X + 8 * q);
      }
    } else if (wid == 11) {
      #pragma unroll
      for (int i = 0; i < 12; i++) prefetch_tmap(&maps.x + i);
    } else if (wid == 9) {
      #pragma unroll
      for (uint32_t bar = B_EQ; bar < B_FM; bar += 8) mbar_init_e(sbase + bar, bar < B_FQ ? 8 : bar == B_FQ + 8 || bar == B_FQ + 24 ? 2 : 1);
      fence_proxy_async_smem();
    } else {
      #pragma unroll
      for (uint32_t bar = B_FM; bar < B_END; bar += 8) mbar_init_e(sbase + bar, 1);
      fence_proxy_async_smem();
    }
    bar_sync(0, 384);
    reg_dealloc<40>();
    PROF(92, tid == 256);
    if (wid == 8) {
      uint32_t tnext = clock32();
      #pragma unroll 1
      for (int q = X_UP; q < 8; q++) {
        wait_until(tnext);
        mbar_expect_tx_e(sbase + B_X + 8 * q, 4096);
        bulk_load(sbase + SM_XR + q * 4096, x + (size_t)(row0 + j * 16 + 2 * q) * D_, 4096, sbase + B_X + 8 * q);
        tnext += X_GAP;
      }
      #pragma unroll 1
      for (int u = 0; u < 16; u++) {
        const int st = u & 3;
        if (u == 1) PRD_WAIT(X_S1 < 8 ? sbase + B_X + 8 * X_S1 : sbase + B_MOD, 0, dl);
        if (u == 2) { PRD_WAIT(sbase + B_GATE, 0, dl); PROFN(60, lane == 0); }
        if (u == 3) PRD_WAIT(sbase + B_EQ, 0, dl);
        PRD_WAIT(sbase + B_EQ + 8 * st, ((u >> 2) & 1) ^ 1, dl);
        const uint32_t slot = sbase + st * QSLOT, fb = sbase + B_FQ + 8 * st;
        mbar_expect_tx_e(fb, u == 0 ? 65536 : u == 15 ? 32768 : 49152);
        if (u == 0) tma_load_3d(sbase + SM_X0, &maps.x, fb, 0, mb * 64, 0);
        tma_load_4d<(EF & 2) != 0>(slot + 16384, &maps.wqk, fb, 0, u * 64, j, 0);
        tma_load_4d<(EF & 2) != 0>(slot + 32768, &maps.wvv, fb, 0, u * 64, j, 0);
        if (u < 15) tma_load_3d(slot, &maps.x, fb, u * 64 + 64, mb * 64, 0);
      }
      PRD_WAIT(sbase + B_RST, 0, dl);
      mbar_arrive_e(sbase + B_FQ + 24);
      const unsigned e1 = 1 + ld_relaxed(flags + FO_EPOCH);
      Ring r{0, 1, 0, dl};
      uint32_t slot, fb;
      auto acquire = [&](uint32_t bytes) {
        PRD_WAIT(sbase + B_EM + 8 * r.st, r.ph, dl);
        slot = sbase + r.st * MSLOT; fb = sbase + B_FM + 8 * r.st;
        mbar_expect_tx_e(fb, bytes);
        ring_next(r);
      };
      auto hold = [&](int n) { Ring h = r; for (int i = 0; i < n; i++) ring_next(h); PRD_WAIT(sbase + B_EM + 8 * h.st, h.ph, dl); };
      #pragma unroll 1
      for (int kt = 0; kt < 16; kt++) {
        if (kt < 5) PRD_WAIT(sbase + B_EQ + 8 * (kt - (kt >= 2)), 1, dl);
        if (kt == 8) hold(HOLD1);
        if ((kt & 7) == 0) { PROF(46, lane == 0 && kt == 8); PRD_WAIT(sbase + B_FLG + kt, 0, dl); PROF(47, lane == 0 && kt == 8); }
        acquire(32768);
        tma_load_4d<(EF & 2) != 0>(slot + 16384, &maps.wq1, fb, (j + 8) * 64, (kt & 1) * 64 + (kt & 6) * 8, (kt >> 3) * 4, 0);
        tma_load_3d(slot, &maps.hh, fb, (kt & 7) * 64, row0, kt >> 3);
      }
      hold(HOLD2);
      PROF(82, lane == 0);
      PRD_WAIT(sbase + B_FLG + 16, 0, dl);
      PROF(83, lane == 0);
      #pragma unroll 1
      for (int kt = 0; kt < 8; kt++) {
        if (kt == 4) {
          acquire(32768);
          tma_load_3d(slot, &maps.x, fb, j * 128, mb * 64, 0);
          tma_load_3d(slot + 16384, &maps.x, fb, j * 128 + 64, mb * 64, 0);
        }
        acquire(32768);
        tma_load_3d<(EF & 2) != 0>(slot + 16384, &maps.wo, fb, 0, kt * 64, 2 * j);
        tma_load_2d(slot, &maps.o, fb, kt * 64, row0);
      }
      acquire(16384);
      tma_load_3d<(EF & 2) != 0>(slot + 16384, &maps.wo, fb, 0, (8 + j) * 64, 2 * j);
      {
        constexpr int NPRE = WPRE;
        Ring ra = r;
        #pragma unroll 1
        for (int i = 0; i < 7; i++) {
          const int kt = 8 + other_slot(i, j);
          acquire(32768);
          tma_load_3d<(EF & 2) != 0>(slot + 16384, &maps.wo, fb, 0, kt * 64, 2 * j);
          if (i == NPRE - 1) {
            wait_flag(&mail0->flags[FL_O], e1 * NCTA, dl);
            PROFN(61, lane == 0);
            #pragma unroll 1
            for (int q = 0; q < NPRE - 1; q++) { tma_load_2d(sbase + ra.st * MSLOT, &maps.o, sbase + B_FM + 8 * ra.st, (8 + other_slot(q, j)) * 64, row0); ring_next(ra); }
          }
          if (i >= NPRE - 1) tma_load_2d(slot, &maps.o, fb, kt * 64, row0);
        }
      }
      #pragma unroll 1
      for (int t = 0; t < 2; t++) {
        acquire(32768);
        tma_load_2d<(EF & 4) != 0>(slot, &maps.w1, fb, j * 64, (2 * j + t) * 64);
        tma_load_2d<(EF & 4) != 0>(slot + 8192, &maps.w3, fb, j * 64, (2 * j + t) * 64);
        tma_load_2d<(EF & 4) != 0>(slot + 16384, &maps.w1, fb, (8 + j) * 64, (2 * j + t) * 64);
        tma_load_2d<(EF & 4) != 0>(slot + 24576, &maps.w3, fb, (8 + j) * 64, (2 * j + t) * 64);
      }
      {
        Ring ra = r;
        #pragma unroll 1
        for (int i = 0; i < 4; i++) {
          const int kt = 2 * ((~j & 4) + i);
          acquire(32768);
          tma_load_2d<(EF & 4) != 0>(slot + 16384, &maps.w1, fb, j * 64, kt * 64);
          tma_load_2d<(EF & 4) != 0>(slot + 24576, &maps.w3, fb, j * 64, kt * 64);
        }
        wait_flag(&mail0->flags[FL_H2], e1 * NCTA, dl);
        PROFN(62, lane == 0);
        mbar_arrive_e(sbase + B_H2A);
        #pragma unroll 1
        for (int i = 0; i < 4; i++) { tma_load_2d(sbase + ra.st * MSLOT, &maps.h2, sbase + B_FM + 8 * ra.st, ((~j & 4) + i) * 128, row0); ring_next(ra); }
      }
      #pragma unroll 1
      for (int gt = 0; gt < 7; gt++) {
        const int ncol = (8 * gt + j) * 64;
        #pragma unroll 1
        for (int i = (gt == 0 ? 4 : 0); i < (gt < 2 ? 14 : 16); i++) {
          const int kt = gt >= 2 ? i : i < 7 ? 2 * other_slot(i, j) : 2 * other_slot(i - 7, j) + 1;
          if (gt == 0 && i == 7) PRD_WAIT(sbase + B_FLG + 24, 0, dl);
          acquire(32768);
          tma_load_2d<(EF & 4) != 0>(slot + 16384, &maps.w1, fb, ncol, kt * 64);
          tma_load_2d<(EF & 4) != 0>(slot + 24576, &maps.w3, fb, ncol, kt * 64);
          tma_load_2d(slot, &maps.h2, fb, kt * 64, row0);
        }
      }
      #pragma unroll 1
      for (int kt = 0; kt < 56; kt++) {
        if ((kt & 7) == 0) PRD_WAIT(sbase + B_FLG + 32 + kt, 0, dl);
        acquire(32768);
        tma_load_3d<(EF & 8) != 0>(slot + 16384, &maps.w2, fb, 0, kt * 64, 2 * j);
        tma_load_3d<(EF & 16) != 0>(slot, &maps.hh, fb, (kt & 7) * 64, row0, kt >> 3);
      }
    } else {
      const unsigned e1 = 1 + ld_relaxed(wid == 9 ? flags + FO_EPOCH : &mail0->flags[FL_EPOCH]), par = e1 & 1;
      if (wid == 9) {
        SVC_WAIT(sbase + B_GATE, 0, dl);
        #pragma unroll 1
        for (int e = 0; e < 16; e++) st_rlx_v4(mail0->halo + (mb * 16 + j + (e & 8)) * 256 + (e & 7) * 32 + lane, ~0u, ~0u, ~0u, ~0u, true);
        #pragma unroll 1
        for (int e = 0; e < 2; e++) st_rlx_v4(mail0->st2 + ((mb * 8 + e * 4 + (lane >> 3)) * 8 + j) * 8 + (lane & 7), ~0u, ~0u, ~0u, ~0u, true);
        __threadfence();
        red_add_e(&mail0->flags[FL_RESET], 1);
        #pragma unroll 1
        for (int n = 0; n < 12; n++) {
          if (n == 4) {
            mbar_wait(sbase + B_STH, 0, dl);
            tma_store_2d(&maps.h2, sbase + SM_STG, j * 128, row0);
            bulk_commit();
            bulk_wait0();
            red_add_e(&mail0->flags[FL_H2], 1);
            PROF(84, lane == 0);
            mbar_wait(sbase + B_H2A, 0, dl);
          }
          if (n >= ST_SPIN0 && n <= 4) mbar_wait(sbase + B_STREQ, n & 1, dl); else SVC_WAIT(sbase + B_STREQ, n & 1, dl);
          if (n == 2 || n == 3) tma_store_2d(&maps.o, sbase + SM_STG, (j + 8 * (n - 2)) * 64, row0);
          else if (n == 4) tma_store_2d(&maps.h2, sbase + SM_STG + 16384, j * 128 + 64, row0);
          else tma_store_3d(&maps.hh, sbase + SM_STG + (n == 1 ? 16384 : 0), j * 64, row0, n < 2 ? n : n - 5);
          bulk_commit();
          bulk_wait0();
          red_add_e(n == 3 ? &mail0->flags[FL_O] : flags + (n < 2 ? FO_H1 + n : n - 1), 1);
          mbar_arrive_e(sbase + B_STFREE);
          PROFN(70 + n, lane == 0 && n > 0);
        }
      } else {
        mbar_wait(sbase + B_X + 8 * X_POLL, 0, dl);
        const float* const mail = &mail0->mod[(b & 7) * 6 * D_ + lane * 4];
        if (wid == 10) {
          #pragma unroll 1
          for (int p = 0; p < 8; p++) {
            if (p >= 2) TRG_WAIT(p == 2 ? q_empty(0, sbase) : q_empty(2 * p - 5, sbase), p == 2 ? 0 : ((2 * p - 5) >> 2) & 1, dl);
            gather_table(mail + p * 128, sbase + SM_MODT + (p & 3) * 512 + lane * 16, p == 0 ? sbase + B_MOD : sbase + B_FQ + 8 * ((2 * p - 1) & 3), par, dl);
            PROF(63 + p, lane == 0 && p < 7);
          }
          const uint32_t vdst = sbase + SM_VEC + (lane >> 3) * 64 + (lane & 3) * 16 + ((lane >> 2) & 1) * 8;
          #pragma unroll 1
          for (int v = 0; v < 2; v++) {
            SVC_WAIT(sbase + B_FLG + 16 + 16 * v, 0, dl);
            uint4 m[3];
            while (true) {
              #pragma unroll
              for (int e = 0; e < 3; e++) m[e] = ld_rlx_v4(mail + (2 + v + e) * 1024 + j * 128);
              if (poll_done(((bad4(m[0], par) | bad4(m[1], par) | bad4(m[2], par)) & 1) == 0, dl)) break;
              __nanosleep(200);
            }
            #pragma unroll
            for (int e = 0; e < 3; e++) sts64(vdst + (v + e) * 256, hi_halves(m[e].x, m[e].y), hi_halves(m[e].z, m[e].w));
            mbar_arrive_e(sbase + B_VEC + 8 * v);
            PROF(70, lane == 0 && v == 0);
          }
        } else {
          mbar_wait(sbase + B_LN, 0, dl);
          red_add_e(&mail0->flags[FL_LN1], 1);
          wait_flag(&mail0->flags[FL_LN1], e1 * NCTA, dl);
          mbar_arrive_e(sbase + B_GATE);
          PROF(41, lane == 0);
          __nanosleep(2000);
          wait_flag(&mail0->flags[FL_RESET], e1 * NCTA, dl);
          mbar_arrive_e(sbase + B_RST);
          #pragma unroll 1
          for (int i = 0; i < 11; i++) {
            const unsigned* f = flags + (i < 2 ? FO_H1 + i : i == 2 ? FO_O : FO_H2 + i - 3);
            if (i == 3) SVC_WAIT(sbase + B_H2A, 0, dl);
            while (!poll_done((int)(ld_relaxed(f) - e1 * 8) >= 0, dl)) { if (i > 3 || i == 0) __nanosleep(200); }
            mbar_arrive_e(sbase + B_FLG + 8 * i);
          }
        }
      }
    }
  } else {
    const int wg = wid >> 2, warp = wid & 3;
    const int g = lane >> 2, qd = lane & 3;
    bulk_prefetch(wmod + (size_t)(b * 8 + wid) * (6 * D_), PF_BYTES);
    bulk_prefetch(wmod + (size_t)(b * 8 + wid) * (6 * D_) + D_, PF_BYTES);
    bar_sync(0, 384);
    const unsigned e1 = 1 + ld_relaxed(flags + FO_EPOCH), par = e1 & 1;
    reg_alloc<232>();
    PROF(1, tid == 0);
    const uint32_t wgoff = wg * 8192;
    Frag4 frag;
    #pragma unroll
    for (int q = 0; q < 4; q++) frag.o[q] = wid * 2048 + (lane & 15) * 128 + (((2 * q + (lane >> 4)) ^ (lane & 7)) << 4);
    const uint32_t slab = sbase + SM_STG + wid * 2048;

    LnRow ln;
    {
      uint2* const lmail = &mail0->ln1[(mb * 8 + (lane & 1) * 4 + (j >> 1)) * 16 + (j & 1) * 8 + wid];
      st_rlx_v2(lmail, par ^ 1, par ^ 1, lane < 2);
      mbar_wait(sbase + B_X + 8 * wid, 0, dl);
      PROF(3, tid == 224); PROF(93, tid == 0);
      float s[2][2] = {{0.f, 0.f}, {0.f, 0.f}}, q2[2][2] = {{0.f, 0.f}, {0.f, 0.f}};
      #pragma unroll
      for (int c = 0; c < 8; c++) {
        const uint4 v = lds128(sbase + SM_XR + wid * 4096 + c * 512 + lane * 16);
        const uint32_t vv[4] = {v.x, v.y, v.z, v.w};
        #pragma unroll
        for (int e = 0; e < 4; e++) {
          const float lo = bf_lo(vv[e]), hi = bf_hi(vv[e]);
          s[c >> 2][0] += lo; s[c >> 2][1] += hi; q2[c >> 2][0] = fmaf(lo, lo, q2[c >> 2][0]); q2[c >> 2][1] = fmaf(hi, hi, q2[c >> 2][1]);
        }
      }
      const bool odd = lane & 1;
      float sm = (s[0][0] + s[0][1]), so = (s[1][0] + s[1][1]), qm = (q2[0][0] + q2[0][1]), qo = (q2[1][0] + q2[1][1]);
      { const float a = odd ? so : sm, c = odd ? qo : qm;
        sm = a + __shfl_xor_sync(0xffffffffu, odd ? sm : so, 1); qm = c + __shfl_xor_sync(0xffffffffu, odd ? qm : qo, 1); }
      #pragma unroll
      for (int o = 2; o < 32; o <<= 1) { sm += __shfl_xor_sync(0xffffffffu, sm, o); qm += __shfl_xor_sync(0xffffffffu, qm, o); }
      sm *= (1.f / D_);
      st_rlx_v2(lmail, tagf(fast_rsqrt(fmaxf(qm * (1.f / D_) - sm * sm, 0.f) + 1e-5f), par), tagf(sm, par), lane < 2);
      mbar_arrive_e(sbase + B_LN);
      PROF(4, tid == 224);
    }

    uint4* const halo_out = mail0->halo + ((mb * 16 + j) * 2 + wg) * 128 + lane;
    const uint4* const halo_in = halo_out - 16 * 256;
    const uint32_t xch = sbase + SM_XCH + wid * 2048 + lane * 16;
    const bool noprev = mb == 0 && warp == 0;
    float a0[64], a1[64];
    uint32_t x2[32];
    Ring r{zero, 0, 0, dl};
    Frag8 qA, qB, kA, kB, vA, vB, wA, wB;
    {
      float acc[128];
      uint32_t A0[16], A1[16];
      undef_regs(acc);
      const uint32_t tab = sbase + SM_MODT + qd * 16;
      uint4 p[4];
      mbar_wait(sbase + B_LN, 0, dl);
      const uint2* const lin = &mail0->ln1[(mb * 8 + wid) * 16 + g];
      uint2 v0, v1;
      do { v0 = ld_rlx_v2(lin); v1 = ld_rlx_v2(lin + 8); } while (!poll_done(((bad2(v0.x, v0.y, par) | bad2(v1.x, v1.y, par)) & 1) == 0, dl));
      ln_row(ln, 0, __uint_as_float(v0.y), __uint_as_float(v0.x));
      ln_row(ln, 1, __uint_as_float(v1.y), __uint_as_float(v1.x));
      q_wait(0, sbase, dl);
      mbar_wait(sbase + B_MOD, 0, dl);
      #pragma unroll
      for (int kk = 0; kk < 4; kk++) q_load(A0, p, kk, sbase + SM_X0, frag, tab);
      PROF(5, tid == 0);
      const int hq0 = (j & 1) ? 4 : j >> 1, hq1 = (j & 1) ? j >> 1 : 4;
      q_step_rs<true>(acc, A0, A1, p, 0, sbase, frag, tab, ln, hq0, true, dl, wg);
      #pragma unroll 1
      for (int u = 1; u < 15; u += 2) {
        q_step_rs<true>(acc, A1, A0, p, u, sbase, frag, tab, ln, hq1, false, dl, wg);
        if (u == 7) request_store(sbase + B_STREQ);
        q_step_rs<true>(acc, A0, A1, p, u + 1, sbase, frag, tab, ln, hq0, false, dl, wg);
      }
      q_step_rs<false>(acc, A1, A0, p, 15, sbase, frag, tab, ln, hq1, false, dl, wg);
      mbar_wait(sbase + B_STFREE, 0, dl);
      request_store(sbase + B_STREQ);
      wgmma_wait<0>();
      undef_regs(a0);
      { const uint32_t slot = m_wait(sbase, r); mma_step(a0, slot + wgoff, slot + 16384, true, q_empty(15, sbase)); m_next(r); }
      fence_regs(acc);
      PROF(8, tid == 0);
      sched_fence();
      pack_half(kB, acc, 32, 1); pack_half(vB, acc, 64, 1); transpose8(vB);
      m_step(a0, sbase, wgoff, r);
      sched_fence();
      attn_send(kB, 0, xch - 16384, warp, halo_out, mb < 15); attn_send(vB, 1, xch - 16384, warp, halo_out, mb < 15);
      pack_half(qA, acc, 0, 0); pack_half(qB, acc, 0, 1); pack_half(kA, acc, 32, 0);
      m_step(a0, sbase, wgoff, r);
      sched_fence();
      pack_half(vA, acc, 64, 0); pack_half(wB, acc, 96, 1); pack_half(wA, acc, 96, 0); transpose8(vA);
    }
    uint4 wP[2];
    {
      m_step(a0, sbase, wgoff, r);
      uint4 pv[4];
      attn_recv<4>(pv, 0, xch - 16384, wg, warp, halo_in, mb > 0);
      m_step(a0, sbase, wgoff, r);
      mbar_wait(sbase + B_STFREE, 1, dl);
      transpose8(wB);
      m_step(a0, sbase, wgoff, r);
      attn_check<4>(pv, 0, warp, halo_in, dl);
      wgmma_wait<0>();
      PROF(9, tid == 0);
      float o[2][5][4];
      sched_fence();
      attn_core(qA, qB, kA, kB, vA, vB, pv, pv + 2, noprev, lane, o);
      if (ST0 == 0) { attn_store(o, 0, sbase, frag); attn_store(o, 1, sbase, frag); request_store(sbase + B_STREQ); }
      if (ST0 == 1) attn_store(o, 0, sbase, frag);
      sched_fence();
      bar_sync(NB_CONS, 256);
      PROF(10, tid == 0);
      m_step(a0, sbase, wgoff, r);
      sched_fence();
      if (ST0 == 2) attn_store(o, 0, sbase, frag);
      if (ST0 >= 1) { attn_store(o, 1, sbase, frag); request_store(sbase + B_STREQ); }
      m_step(a0, sbase, wgoff, r);
      sched_fence();
      attn_send(wB, 1, xch, warp, halo_out + 8 * 256, mb < 15);
      transpose8(wA);
      #pragma unroll 1
      for (int i = 8; i < 15; i++) m_step(a0, sbase, wgoff, r);
      attn_recv<2>(wP, 2, xch, wg, warp, halo_in + 8 * 256, mb > 0);
      m_step(a0, sbase, wgoff, r);
    }
    {
      undef_regs(a1);
      {
        const uint32_t slot = m_wait(sbase, r);
        mma_step(a1, slot + wgoff, slot + 16384, true, m_prev(sbase, r), [&] {
          fence_regs(a0);
          pack_half(kB, a0, 32, 1);
          attn_send(kB, 0, xch, warp, halo_out + 8 * 256, mb < 15);
        });
        m_next(r);
      }
      PROF(14, tid == 0);
      sched_fence();
      pack_half(kA, a0, 32, 0); pack_half(qA, a0, 0, 0); pack_half(qB, a0, 0, 1);
      m_step(a1, sbase, wgoff, r);
      attn_check<2>(wP, 2, warp, halo_in + 8 * 256, dl);
      uint4 kP[2];
      attn_recv<2>(kP, 0, xch, wg, warp, halo_in + 8 * 256, mb > 0);
      m_step(a1, sbase, wgoff, r);
      attn_check<2>(kP, 0, warp, halo_in + 8 * 256, dl);
      wgmma_wait<0>();
      PROF(15, tid == 0);
      float o[2][5][4];
      mbar_wait(sbase + B_STFREE, 0, dl);
      attn_core(qA, qB, kA, kB, wA, wB, kP, wP, noprev, lane, o);
      attn_store(o, 0, sbase, frag);
      attn_store(o, 1, sbase, frag);
      request_store(sbase + B_STREQ);
      bar_sync(NB_CONS, 256);
      PROF(16, tid == 0);
      auto residual = [&] {
        const uint32_t xs = m_wait(sbase, r), xe = sbase + B_EM + 8 * r.st;
        ring_next(r);
        #pragma unroll
        for (int t = 0; t < 2; t++) {
          #pragma unroll
          for (int jj = 4 * t; jj < 4 * t + 4; jj++) ldmatrix_x4(xs + t * 16384 + frag.o[jj & 3], x2[4 * jj], x2[4 * jj + 1], x2[4 * jj + 2], x2[4 * jj + 3]);
          if (t == 1) {
            uint32_t dep = 0;
            #pragma unroll
            for (int jj = 0; jj < 8; jj++) dep |= x2[4 * jj];
            mbar_arrive_e(xe + (dep & zero));
          }
          m_step(a1, sbase, wgoff, r);
        }
      };
      m_step(a1, sbase, wgoff, r);
      residual();
      #pragma unroll 1
      for (int i = 6; i < 8; i++) m_step(a1, sbase, wgoff, r);
      mma_step(a1, sbase + SM_STG + wgoff, m_wait(sbase, r) + 16384, false, m_prev(sbase, r));
      m_next(r);
      PROF(17, tid == 0);
      #pragma unroll 1
      for (int i = 0; i < 7; i++) { m_step(a1, sbase, wgoff, r); PROF(42, tid == 0 && i == 0); }
      PROF(45, tid == 0);
      mbar_wait(sbase + B_VEC, 0, dl);
      mbar_wait(sbase + B_STFREE, 1, dl);
      const uint32_t vec = sbase + SM_VEC + qd * 16;
      uint4 ga[4];
      #pragma unroll
      for (int q = 0; q < 4; q++) ga[q] = lds128(vec + q * 64);
      wgmma_wait<0>();
      mbar_arrive_e(m_prev(sbase, r));
      fence_regs(a1);
      PROF(18, tid == 0);
      float rs_[4] = {0.f, 0.f, 0.f, 0.f}, gl[4] = {0.f, 0.f, 0.f, 0.f}, gh[4] = {0.f, 0.f, 0.f, 0.f};
      #pragma unroll
      for (int jj = 0; jj < 8; jj++) {
        uint32_t* v = &x2[4 * jj];
        const uint32_t wl = (jj & 1) ? ga[jj >> 1].z : ga[jj >> 1].x, wh = (jj & 1) ? ga[jj >> 1].w : ga[jj >> 1].y;
        #pragma unroll
        for (int e = 0; e < 4; e++) v[e] = fma_bf2(e & 2 ? wh : wl, pack_bf16(a1[8 * jj + 2 * e], a1[8 * jj + 2 * e + 1]), v[e]);
        mma16(rs_, v[0], v[1], v[2], v[3], 0x3F803F80u, 0x3F803F80u);
        mma16(gl, v[0], v[1], v[2], v[3], v[0], v[2]);
        mma16(gh, v[0], v[1], v[2], v[3], v[1], v[3]);
      }
      uint4* const sm = mail0->st2 + (mb * 8 + wid) * 64 + g;
      st_rlx_v4(sm + j * 8, __float_as_uint(rs_[0]), __float_as_uint(g & 1 ? gl[1] : gl[0]), __float_as_uint(rs_[2]), __float_as_uint(g & 1 ? gh[3] : gh[2]),
                qd == (g >> 1));
      float s[2], q2[2];
      PROF(19, tid == 0);
      uint4 sb[4], cb[4];
      #pragma unroll
      for (int q = 0; q < 4; q++) { sb[q] = lds128(vec + 256 + q * 64); cb[q] = lds128(vec + 512 + q * 64); }
      uint4 p0, p1;
      while (true) {
        p0 = ld_rlx_v4(sm + qd * 16); p1 = ld_rlx_v4(sm + qd * 16 + 8);
        if (poll_done(max(max(max(p0.x, p0.y), max(p0.z, p0.w)), max(max(p1.x, p1.y), max(p1.z, p1.w))) != ~0u, dl)) break;
      }
      PROF(20, tid == 0);
      s[0] = __uint_as_float(p0.x) + __uint_as_float(p1.x); q2[0] = __uint_as_float(p0.y) + __uint_as_float(p1.y);
      s[1] = __uint_as_float(p0.z) + __uint_as_float(p1.z); q2[1] = __uint_as_float(p0.w) + __uint_as_float(p1.w);
      #pragma unroll
      for (int o2 = 1; o2 <= 2; o2 <<= 1)
        #pragma unroll
        for (int h = 0; h < 2; h++) { s[h] += __shfl_xor_sync(0xffffffffu, s[h], o2); q2[h] += __shfl_xor_sync(0xffffffffu, q2[h], o2); }
      #pragma unroll
      for (int h = 0; h < 2; h++) {
        const float m = s[h] * (1.f / D_);
        ln_row(ln, h, m, fast_rsqrt(fmaxf(q2[h] * (1.f / D_) - m * m, 0.f) + 1e-5f));
      }
      #pragma unroll
      for (int jj = 0; jj < 8; jj++) {
        const uint32_t cl = (jj & 1) ? cb[jj >> 1].z : cb[jj >> 1].x, ch = (jj & 1) ? cb[jj >> 1].w : cb[jj >> 1].y;
        const uint32_t sl = (jj & 1) ? sb[jj >> 1].z : sb[jj >> 1].x, sh = (jj & 1) ? sb[jj >> 1].w : sb[jj >> 1].y;
        stmatrix_x4(sbase + SM_STG + (jj >> 2) * 16384 + frag.o[jj & 3], ln_mod(x2[4 * jj], ln, 0, cl, sl), ln_mod(x2[4 * jj + 1], ln, 1, cl, sl),
                    ln_mod(x2[4 * jj + 2], ln, 0, ch, sh), ln_mod(x2[4 * jj + 3], ln, 1, ch, sh));
        if (jj == 3) request_store(sbase + B_STH);
      }
      request_store(sbase + B_STREQ);
      bar_sync(NB_WG + wg, 128);
      PROF(21, tid == 0);
    }

    undef_regs(a0);
    #pragma unroll
    for (int t = 0; t < 2; t++) {
      const uint32_t slot = m_wait(sbase, r);
      if (t == 0) mma_step<false>(a0, sbase + SM_STG + wgoff, slot, true, 0);
      else mma_step(a0, sbase + SM_STG + 16384 + wgoff, slot, false, m_prev(sbase, r));
      mma_step<false>(a1, sbase + SM_STG + t * 16384 + wgoff, slot + 16384, t == 0, 0);
      m_next(r);
    }
    PROF(22, tid == 0);
    #pragma unroll 1
    for (int t = 0; t < 7; t += 2) {
      g_switch(a1, a0, t == 0 ? 14 : 11, t > 0, 5 + t, sbase, wgoff, frag, r);
      if (t == 6) break;
      g_switch(a0, a1, t == 0 ? 9 : 11, true, 6 + t, sbase, wgoff, frag, r);
    }
    #pragma unroll 1
    for (int i = 5; i < 56 - DTAIL; i++) m_step(a1, sbase, wgoff, r);
    if (DTAIL) {
      if (wg == 1) { wgmma_wait<0>(); mbar_arrive_e(m_prev(sbase, r)); bar_sync(NB_ORD, 256); }
      #pragma unroll
      for (int i = 0; i < DTAIL; i++) {
        const uint32_t slot = m_wait(sbase, r);
        const uint32_t alo = ((slot + wgoff) >> 4) + (1u << 16), blo = ((slot + 16384) >> 4) + (512u << 16);
        wgmma_fence();
        #pragma unroll
        for (int k = 0; k < 4; k++) wgmma_m64n128k16_ss(a1, desc_from_lo(alo + k * 2), desc_from_lo(blo + k * 128), true);
        wgmma_commit();
        ring_next(r);
      }
      if (wg == 0) bar_arrive(NB_ORD, 256);
    }
    {
      mbar_wait(sbase + B_STFREE, 1, dl);
      mbar_wait(sbase + B_VEC + 8, 0, dl);
      uint4 gb[4];
      #pragma unroll
      for (int q = 0; q < 4; q++) gb[q] = lds128(sbase + SM_VEC + 768 + qd * 16 + q * 64);
      wgmma_wait<0>();
      fence_regs(a1);
      PROF(50, tid == 128);
      #pragma unroll
      for (int t = 0; t < 2; t++) {
        #pragma unroll
        for (int jj = 4 * t; jj < 4 * t + 4; jj++) {
          const uint32_t gl = (jj & 1) ? gb[jj >> 1].z : gb[jj >> 1].x, gh = (jj & 1) ? gb[jj >> 1].w : gb[jj >> 1].y;
          const int i = 8 * jj;
          stmatrix_x4(sbase + SM_STG + t * 16384 + frag.o[jj & 3],
                      fma_bf2(gl, pack_bf16(a1[i], a1[i + 1]), x2[4 * jj]), fma_bf2(gl, pack_bf16(a1[i + 2], a1[i + 3]), x2[4 * jj + 1]),
                      fma_bf2(gh, pack_bf16(a1[i + 4], a1[i + 5]), x2[4 * jj + 2]), fma_bf2(gh, pack_bf16(a1[i + 6], a1[i + 7]), x2[4 * jj + 3]));
        }
        fence_proxy_async_smem();
        tma_store_3d(&maps.out, slab + t * 16384, j * 128 + t * 64, mb * 64 + warp * 16, wg);
      }
      bulk_commit();
      st_rlx(tid == 0 ? flags + FO_EPOCH : &mail0->flags[FL_EPOCH], e1, j == 0 && (tid == 0 || (tid == 1 && mb == 0)));
      bulk_wait_read0();
      PROFN(51, tid == 128);
    }
  }
}

typedef CUresult (*PFN_encodeTiled)(CUtensorMap*, CUtensorMapDataType, cuuint32_t, void*, const cuuint64_t*, const cuuint64_t*,
                                    const cuuint32_t*, const cuuint32_t*, CUtensorMapInterleave, CUtensorMapSwizzle,
                                    CUtensorMapL2promotion, CUtensorMapFloatOOBfill);

void encode(PFN_encodeTiled fn, CUtensorMap* m, const void* ptr, int rank, const cuuint64_t* dims, const cuuint64_t* strides,
            const cuuint32_t* box) {
  const cuuint32_t es[5] = {1, 1, 1, 1, 1};
  fn(m, CU_TENSOR_MAP_DATA_TYPE_BFLOAT16, rank, const_cast<void*>(ptr), dims, strides, box, es, CU_TENSOR_MAP_INTERLEAVE_NONE,
     CU_TENSOR_MAP_SWIZZLE_128B, CU_TENSOR_MAP_L2_PROMOTION_L2_256B, CU_TENSOR_MAP_FLOAT_OOB_FILL_NONE);
}
void map2d(PFN_encodeTiled fn, CUtensorMap* m, const void* ptr, int cols, int rows, int boxrows) {
  const cuuint64_t dims[2] = {(cuuint64_t)cols, (cuuint64_t)rows}, strides[1] = {(cuuint64_t)cols * 2};
  const cuuint32_t box[2] = {64, (cuuint32_t)boxrows};
  encode(fn, m, ptr, 2, dims, strides, box);
}
void map_w2chunk(PFN_encodeTiled fn, CUtensorMap* m, const void* ptr, int cols, int rows) {
  const cuuint64_t dims[3] = {64, (cuuint64_t)rows, (cuuint64_t)cols / 64}, strides[2] = {(cuuint64_t)cols * 2, 128};
  const cuuint32_t box[3] = {64, 64, 2};
  encode(fn, m, ptr, 3, dims, strides, box);
}
void map_parity(PFN_encodeTiled fn, CUtensorMap* m, const void* ptr, int boxpairs, int boxpar) {
  const cuuint64_t dims[3] = {D_, S_ / 2, 2}, strides[2] = {D_ * 4, D_ * 2};
  const cuuint32_t box[3] = {64, (cuuint32_t)boxpairs, (cuuint32_t)boxpar};
  encode(fn, m, ptr, 3, dims, strides, box);
}

}

extern "C" void kernel_launch(void* const* d_in, const int* in_sizes, int n_in, void* d_out, int out_size) {
  (void)in_sizes; (void)n_in; (void)out_size;
  const bf16* x = (const bf16*)d_in[0];
  const bf16* wqkv = (const bf16*)d_in[1];
  const bf16* wo = (const bf16*)d_in[2];
  const bf16* w1 = (const bf16*)d_in[4];
  const bf16* w3 = (const bf16*)d_in[5];
  const bf16* w2 = (const bf16*)d_in[6];
  const bf16* cvec = (const bf16*)d_in[7];
  const bf16* w_mod = (const bf16*)d_in[8];

  static PFN_encodeTiled fn = nullptr;
  static Maps maps;
  static const void* cached[8] = {};
  static int sms = 0;
  static void* mail = nullptr;
  if (!fn) {
    void* p = nullptr; cudaDriverEntryPointQueryResult st;
    cudaGetDriverEntryPoint("cuTensorMapEncodeTiled", &p, cudaEnableDefault, &st);
    fn = (PFN_encodeTiled)p;
    cudaFuncSetAttribute(fused_block_kernel<0>, cudaFuncAttributeMaxDynamicSharedMemorySize, SM_TOTAL + SM_PROF);
    cudaFuncSetAttribute(fused_block_kernel<1>, cudaFuncAttributeMaxDynamicSharedMemorySize, SM_TOTAL + SM_PROF);
    cudaFuncSetAttribute(fused_block_kernel<2>, cudaFuncAttributeMaxDynamicSharedMemorySize, SM_TOTAL + SM_PROF);
    cudaGetSymbolAddress(&mail, g_mail);
    int dev = 0;
    cudaGetDevice(&dev);
    cudaDeviceGetAttribute(&sms, cudaDevAttrMultiProcessorCount, dev);
  }
  const void* cur[8] = {x, wqkv, wo, w1, w3, w2, d_out, w_mod};
  bool same = true;
  for (int i = 0; i < 8; i++) same = same && cached[i] == cur[i];
  if (!same) {
    void *o, *h2, *hh;
    cudaGetSymbolAddress(&hh, g_hh); cudaGetSymbolAddress(&o, g_o);
    h2 = o;
    map_parity(fn, &maps.x, x, 64, 2); map_parity(fn, &maps.out, d_out, 16, 1);
    map2d(fn, &maps.o, o, D_, S_, 128); map2d(fn, &maps.h2, h2, D_, S_, 128);
    {
      const cuuint64_t dims[3] = {512, (cuuint64_t)S_, 7}, strides[2] = {1024, (cuuint64_t)S_ * 1024};
      const cuuint32_t box[3] = {64, 128, 1};
      encode(fn, &maps.hh, hh, 3, dims, strides, box);
    }
    {
      const cuuint64_t dims[4] = {64, 1024, 16, 2}, strides[3] = {3072 * 2, 128, 2048};
      const cuuint64_t dimv[4] = {64, 1024, 8, 2}, stridev[3] = {3072 * 2, 128, 1024};
      const cuuint32_t box[4] = {64, 64, 1, 2};
      encode(fn, &maps.wqk, wqkv, 4, dims, strides, box);
      encode(fn, &maps.wvv, wqkv + 2048, 4, dimv, stridev, box);
      const cuuint64_t dim1[4] = {1024, 128, 8, 2}, stride1[3] = {3072 * 2, 128 * 3072 * 2, 2048};
      const cuuint32_t box1[4] = {64, 16, 4, 2};
      encode(fn, &maps.wq1, wqkv, 4, dim1, stride1, box1);
    }
    map_w2chunk(fn, &maps.wo, wo, D_, D_); map_w2chunk(fn, &maps.w2, w2, D_, F_);
    map2d(fn, &maps.w1, w1, F_, D_, 64); map2d(fn, &maps.w3, w3, F_, D_, 64);
    map2d(fn, &maps.wmod, w_mod, 6 * D_, D_, 256);
    for (int i = 0; i < 8; i++) cached[i] = cur[i];
  }
  if (sms == NCTA + NAUX) {
    fused_block_kernel<0><<<NCTA + NAUX, 384, SM_TOTAL + SM_PROF>>>(x, cvec, w_mod, (Mail*)mail, 0, maps);
  } else {
    fused_block_kernel<1><<<NAUX, 384, SM_TOTAL + SM_PROF>>>(x, cvec, w_mod, (Mail*)mail, 0, maps);
    fused_block_kernel<2><<<NCTA, 384, SM_TOTAL + SM_PROF>>>(x, cvec, w_mod, (Mail*)mail, 0, maps);
  }
}
```

```cpp
#include <cuda.h>
#include <cuda_runtime.h>
#include <cuda_bf16.h>
#include <stdint.h>

namespace {

typedef __nv_bfloat16 bf16;

constexpr int S_ = 2048, D_ = 1024, F_ = 3584;
constexpr int NCTA = 128, NAUX = 4;

__device__ __align__(1024) bf16 g_o[S_ * D_];
__device__ __align__(1024) bf16 g_hh[S_ * F_];
constexpr int FO_EPOCH = 0, FO_O = 1, FO_H2 = 3, FO_H1 = 11;
constexpr int FL_EPOCH = 16 * 32, FL_RESET = FL_EPOCH + 1, FL_LN1 = FL_EPOCH + 2, FL_H2 = FL_EPOCH + 3, FL_O = FL_EPOCH + 4;
struct Mail {
  unsigned flags[32 * 32];
  float mod[8 * 6 * D_];
  uint2 ln1[16 * 8 * 16];
  uint4 halo[16 * 16 * 2 * 4 * 32];
  uint4 st2[16 * 8 * 8 * 8];
};
__device__ __align__(1024) Mail g_mail;

template <int mode>
__device__ __forceinline__ int cta_role() {
  if (mode) return mode == 1 ? NCTA + (blockIdx.x & 3) : blockIdx.x & 127;
  uint32_t sm;
  asm("mov.u32 %0, %%smid;" : "=r"(sm));
  sm = (sm & ~3u) == 12 ? sm + 108 : (sm & ~3u) == 120 ? sm - 108 : sm;
  const int t = sm >> 1;
  int r;
  if (t < 32) r = (t & 7) * 16 + (t >> 3) * 2 + (sm & 1);
  else if (t < 60) r = (1 + (t - 32) % 7) * 16 + 8 + ((t - 32) / 7) * 2 + (sm & 1);
  else if (t < 62) r = NCTA + sm - 120;
  else r = sm - 116;
  return r;
}
#define PROF(slot, on) do {} while (0)
#define PROFN(slot, on) do {} while (0)
#define PROF_OUT(role, t) do {} while (0)
constexpr uint32_t SM_PROF = 0;

__device__ __forceinline__ uint32_t smem_u32(const void* p) { return (uint32_t)__cvta_generic_to_shared(p); }
#define ELECT "{\n.reg .pred p;\nelect.sync _|p, 0xffffffff;\n@p "
__device__ __forceinline__ void mbar_init_e(uint32_t bar, uint32_t count) {
  asm volatile(ELECT "mbarrier.init.shared::cta.b64 [%0], %1;\n}" :: "r"(bar), "r"(count) : "memory");
}
__device__ __forceinline__ void mbar_expect_tx_e(uint32_t bar, uint32_t bytes) {
  asm volatile(ELECT "mbarrier.arrive.expect_tx.shared::cta.b64 _, [%0], %1;\n}" :: "r"(bar), "r"(bytes) : "memory");
}
__device__ __forceinline__ void mbar_arrive_e(uint32_t bar) {
  asm volatile(ELECT "mbarrier.arrive.shared::cta.b64 _, [%0];\n}" :: "r"(bar) : "memory");
}
__device__ __forceinline__ uint32_t clock32() { uint32_t t; asm volatile("mov.u32 %0, %%clock;" : "=r"(t)); return t; }
__device__ __forceinline__ void mbar_wait(uint32_t bar, uint32_t parity, uint32_t dl) {
  asm volatile("{\n.reg .pred p, q;\n.reg .b32 t;\n"
               "mbarrier.try_wait.parity.shared::cta.b64 p, [%0], %1;\n"
               "@p bra LAB_DONE;\n"
               "LAB_WAIT:\n"
               "mbarrier.try_wait.parity.shared::cta.b64 p, [%0], %1;\n"
               "mov.u32 t, %%clock;\n"
               "sub.s32 t, t, %2;\n"
               "setp.lt.and.s32 q, t, 0, !p;\n"
               "@q bra LAB_WAIT;\n"
               "LAB_DONE:\n}" :: "r"(bar), "r"(parity), "r"(dl) : "memory");
}
__device__ __forceinline__ void mbar_sleep(uint32_t bar, uint32_t parity, uint32_t dl) {
  asm volatile("{\n.reg .pred p;\n.reg .b32 t;\n"
               "LAB_WAIT:\n"
               "mbarrier.try_wait.parity.shared::cta.b64 p, [%0], %1, 20000;\n"
               "@p bra LAB_DONE;\n"
               "mov.u32 t, %%clock;\n"
               "sub.s32 t, t, %2;\n"
               "setp.lt.s32 p, t, 0;\n"
               "@p bra LAB_WAIT;\n"
               "LAB_DONE:\n}" :: "r"(bar), "r"(parity), "r"(dl) : "memory");
}
__device__ __forceinline__ bool poll_done(bool ok, uint32_t dl) {
  return __all_sync(0xffffffffu, ok || (int)(clock32() - dl) >= 0);
}
__device__ __forceinline__ unsigned ld_relaxed(const unsigned* p) {
  unsigned v; asm volatile("ld.relaxed.gpu.global.u32 %0, [%1];" : "=r"(v) : "l"(p) : "memory"); return v;
}
__device__ __forceinline__ void red_add_e(unsigned* p, unsigned v) {
  asm volatile(ELECT "red.relaxed.gpu.global.add.u32 [%0], %1;\n}" :: "l"(p), "r"(v) : "memory");
}
__device__ __forceinline__ void wait_flag(const unsigned* p, unsigned target, uint32_t dl) {
  asm volatile("{\n.reg .pred p;\n.reg .b32 t;\n"
               "LAB_WAIT:\n"
               "ld.relaxed.gpu.global.u32 t, [%0];\n"
               "sub.s32 t, t, %1;\n"
               "setp.ge.s32 p, t, 0;\n"
               "@p bra LAB_DONE;\n"
               "mov.u32 t, %%clock;\n"
               "sub.s32 t, t, %2;\n"
               "setp.lt.s32 p, t, 0;\n"
               "@p bra LAB_WAIT;\n"
               "LAB_DONE:\n}" :: "l"(p), "r"(target), "r"(dl) : "memory");
}
__device__ __forceinline__ void wait_until(uint32_t t) { while ((int)(clock32() - t) < 0) {} }
__device__ __forceinline__ void fence_proxy_async_smem() { asm volatile("fence.proxy.async.shared::cta;" ::: "memory"); }

constexpr uint64_t EVICT_FIRST = 0x12F0000000000000ull;
template <bool STREAM = false>
__device__ __forceinline__ void tma_load_2d(uint32_t dst, const CUtensorMap* m, uint32_t bar, int c0, int c1) {
  if (STREAM)
    asm volatile(ELECT "cp.async.bulk.tensor.2d.shared::cluster.global.mbarrier::complete_tx::bytes.L2::cache_hint [%0], [%1, {%3, %4}], [%2], %5;\n}"
                 :: "r"(dst), "l"(m), "r"(bar), "r"(c0), "r"(c1), "l"(EVICT_FIRST) : "memory");
  else
    asm volatile(ELECT "cp.async.bulk.tensor.2d.shared::cluster.global.mbarrier::complete_tx::bytes [%0], [%1, {%3, %4}], [%2];\n}"
                 :: "r"(dst), "l"(m), "r"(bar), "r"(c0), "r"(c1) : "memory");
}
template <bool STREAM = false>
__device__ __forceinline__ void tma_load_3d(uint32_t dst, const CUtensorMap* m, uint32_t bar, int c0, int c1, int c2) {
  if (STREAM)
    asm volatile(ELECT "cp.async.bulk.tensor.3d.shared::cluster.global.mbarrier::complete_tx::bytes.L2::cache_hint [%0], [%1, {%3, %4, %5}], [%2], %6;\n}"
                 :: "r"(dst), "l"(m), "r"(bar), "r"(c0), "r"(c1), "r"(c2), "l"(EVICT_FIRST) : "memory");
  else
    asm volatile(ELECT "cp.async.bulk.tensor.3d.shared::cluster.global.mbarrier::complete_tx::bytes [%0], [%1, {%3, %4, %5}], [%2];\n}"
                 :: "r"(dst), "l"(m), "r"(bar), "r"(c0), "r"(c1), "r"(c2) : "memory");
}
template <bool STREAM = false>
__device__ __forceinline__ void tma_load_4d(uint32_t dst, const CUtensorMap* m, uint32_t bar, int c0, int c1, int c2, int c3) {
  if (STREAM)
    asm volatile(ELECT "cp.async.bulk.tensor.4d.shared::cluster.global.mbarrier::complete_tx::bytes.L2::cache_hint [%0], [%1, {%3, %4, %5, %6}], [%2], %7;\n}"
                 :: "r"(dst), "l"(m), "r"(bar), "r"(c0), "r"(c1), "r"(c2), "r"(c3), "l"(EVICT_FIRST) : "memory");
  else
    asm volatile(ELECT "cp.async.bulk.tensor.4d.shared::cluster.global.mbarrier::complete_tx::bytes [%0], [%1, {%3, %4, %5, %6}], [%2];\n}"
                 :: "r"(dst), "l"(m), "r"(bar), "r"(c0), "r"(c1), "r"(c2), "r"(c3) : "memory");
}
__device__ __forceinline__ void tma_store_2d(const CUtensorMap* m, uint32_t src, int c0, int c1) {
  asm volatile(ELECT "cp.async.bulk.tensor.2d.global.shared::cta.bulk_group [%0, {%2, %3}], [%1];\n}"
               :: "l"(m), "r"(src), "r"(c0), "r"(c1) : "memory");
}
__device__ __forceinline__ void tma_store_3d(const CUtensorMap* m, uint32_t src, int c0, int c1, int c2) {
  asm volatile(ELECT "cp.async.bulk.tensor.3d.global.shared::cta.bulk_group [%0, {%2, %3, %4}], [%1];\n}"
               :: "l"(m), "r"(src), "r"(c0), "r"(c1), "r"(c2) : "memory");
}
__device__ __forceinline__ void bulk_load(uint32_t dst, const void* src, uint32_t bytes, uint32_t bar) {
  asm volatile(ELECT "cp.async.bulk.shared::cluster.global.mbarrier::complete_tx::bytes [%0], [%1], %2, [%3];\n}"
               :: "r"(dst), "l"(src), "r"(bytes), "r"(bar) : "memory");
}
__device__ __forceinline__ void bulk_prefetch(const void* src, uint32_t bytes) {
  asm volatile(ELECT "cp.async.bulk.prefetch.L2.global [%0], %1;\n}" :: "l"(src), "r"(bytes) : "memory");
}
__device__ __forceinline__ void bulk_commit() { asm volatile("cp.async.bulk.commit_group;" ::: "memory"); }
__device__ __forceinline__ void bulk_wait0() { asm volatile("cp.async.bulk.wait_group 0;" ::: "memory"); }
__device__ __forceinline__ void bulk_wait_read0() { asm volatile("cp.async.bulk.wait_group.read 0;" ::: "memory"); }
__device__ __forceinline__ void prefetch_tmap(const CUtensorMap* m) { asm volatile(ELECT "prefetch.tensormap [%0];\n}" :: "l"(m) : "memory"); }
__device__ __forceinline__ void wgmma_fence() { asm volatile("wgmma.fence.sync.aligned;" ::: "memory"); }
__device__ __forceinline__ void wgmma_commit() { asm volatile("wgmma.commit_group.sync.aligned;" ::: "memory"); }
template <int N> __device__ __forceinline__ void wgmma_wait() { asm volatile("wgmma.wait_group.sync.aligned %0;" :: "n"(N) : "memory"); }
template <int R> __device__ __forceinline__ void reg_alloc() { asm volatile("setmaxnreg.inc.sync.aligned.u32 %0;" :: "n"(R)); }
template <int R> __device__ __forceinline__ void reg_dealloc() { asm volatile("setmaxnreg.dec.sync.aligned.u32 %0;" :: "n"(R)); }
__device__ __forceinline__ void bar_sync(int id, int n) { asm volatile("bar.sync %0, %1;" :: "r"(id), "r"(n) : "memory"); }
__device__ __forceinline__ void bar_arrive(int id, int n) { asm volatile("bar.arrive %0, %1;" :: "r"(id), "r"(n) : "memory"); }
__device__ __forceinline__ void sched_fence(int zero) {
  asm volatile("{\n.reg .pred p;\n.reg .b32 t;\nsetp.eq.s32 p, %0, 0;\n@p bra.uni LAB_S;\n"
               "LAB_F:\nmov.u32 t, %%clock;\nsetp.eq.u32 p, t, 0;\n@p bra LAB_F;\nLAB_S:\n}" :: "r"(zero) : "memory");
}
template <int N> __device__ __forceinline__ void fence_regs(float (&a)[N]) {
  #pragma unroll
  for (int i = 0; i < N; i++) asm volatile("" : "+f"(a[i]) :: "memory");
}
template <int N> __device__ __forceinline__ void undef_regs(float (&a)[N]) {
  #pragma unroll
  for (int i = 0; i < N; i++) asm volatile("" : "=f"(a[i]));
}

__device__ __forceinline__ uint64_t desc_from_lo(uint32_t lo) { return (uint64_t)lo | ((uint64_t)0x40000040u << 32); }
__device__ __forceinline__ uint32_t pack_bf16(float lo, float hi) {
  uint32_t r; asm("cvt.rn.bf16x2.f32 %0, %1, %2;" : "=r"(r) : "f"(hi), "f"(lo)); return r;
}
__device__ __forceinline__ uint32_t fma_bf2(uint32_t a, uint32_t b, uint32_t c) {
  uint32_t d; asm("fma.rn.bf16x2 %0, %1, %2, %3;" : "=r"(d) : "r"(a), "r"(b), "r"(c)); return d;
}
__device__ __forceinline__ float bf_lo(uint32_t v) { return __uint_as_float(v << 16); }
__device__ __forceinline__ float bf_hi(uint32_t v) { return __uint_as_float(v & 0xFFFF0000u); }
__device__ __forceinline__ float bf16_round(float x) { return bf_lo(pack_bf16(x, 0.f)); }
__device__ __forceinline__ void stmatrix_x4(uint32_t addr, uint32_t r0, uint32_t r1, uint32_t r2, uint32_t r3) {
  asm volatile("stmatrix.sync.aligned.m8n8.x4.shared.b16 [%0], {%1, %2, %3, %4};" :: "r"(addr), "r"(r0), "r"(r1), "r"(r2), "r"(r3) : "memory");
}
__device__ __forceinline__ void stmatrix_x4_t(uint32_t addr, uint32_t r0, uint32_t r1, uint32_t r2, uint32_t r3) {
  asm volatile("stmatrix.sync.aligned.m8n8.x4.trans.shared.b16 [%0], {%1, %2, %3, %4};" :: "r"(addr), "r"(r0), "r"(r1), "r"(r2), "r"(r3) : "memory");
}
__device__ __forceinline__ void stmatrix_x4_if(uint32_t addr, uint32_t r0, uint32_t r1, uint32_t r2, uint32_t r3, bool on) {
  asm volatile("{\n.reg .pred p;\nsetp.ne.b32 p, %5, 0;\n@p stmatrix.sync.aligned.m8n8.x4.shared.b16 [%0], {%1, %2, %3, %4};\n}"
               :: "r"(addr), "r"(r0), "r"(r1), "r"(r2), "r"(r3), "r"((int)on) : "memory");
}
__device__ __forceinline__ void ldmatrix_x4(uint32_t addr, uint32_t& r0, uint32_t& r1, uint32_t& r2, uint32_t& r3) {
  asm volatile("ldmatrix.sync.aligned.m8n8.x4.shared.b16 {%0, %1, %2, %3}, [%4];" : "=r"(r0), "=r"(r1), "=r"(r2), "=r"(r3) : "r"(addr) : "memory");
}
__device__ __forceinline__ void ldmatrix_x4_t(uint32_t addr, uint32_t (&r)[4]) {
  asm volatile("ldmatrix.sync.aligned.m8n8.x4.trans.shared.b16 {%0, %1, %2, %3}, [%4];" : "=r"(r[0]), "=r"(r[1]), "=r"(r[2]), "=r"(r[3]) : "r"(addr) : "memory");
}
__device__ __forceinline__ uint32_t tagf(float v, unsigned par) { return (__float_as_uint(v) & ~1u) | par; }
__device__ __forceinline__ void st_rlx(void* p, uint32_t a, bool on) {
  asm volatile("{\n.reg .pred p;\nsetp.ne.b32 p, %2, 0;\n@p st.relaxed.gpu.global.u32 [%0], %1;\n}" :: "l"(p), "r"(a), "r"((int)on) : "memory");
}
__device__ __forceinline__ void st_rlx_v2(void* p, uint32_t a, uint32_t b, bool on) {
  asm volatile("{\n.reg .pred p;\nsetp.ne.b32 p, %3, 0;\n@p st.relaxed.gpu.global.v2.u32 [%0], {%1, %2};\n}" :: "l"(p), "r"(a), "r"(b), "r"((int)on) : "memory");
}
__device__ __forceinline__ uint2 ld_rlx_v2(const void* p) {
  uint2 v; asm volatile("ld.relaxed.gpu.global.v2.u32 {%0,%1}, [%2];" : "=r"(v.x), "=r"(v.y) : "l"(p) : "memory"); return v;
}
__device__ __forceinline__ void st_rlx_v4(void* p, uint32_t a, uint32_t b, uint32_t c, uint32_t d, bool on) {
  asm volatile("{\n.reg .pred p;\nsetp.ne.b32 p, %5, 0;\n@p st.relaxed.gpu.global.v4.u32 [%0], {%1, %2, %3, %4};\n}"
               :: "l"(p), "r"(a), "r"(b), "r"(c), "r"(d), "r"((int)on) : "memory");
}
__device__ __forceinline__ uint4 ld_rlx_v4(const void* p) {
  uint4 v; asm volatile("ld.relaxed.gpu.global.v4.u32 {%0,%1,%2,%3}, [%4];" : "=r"(v.x), "=r"(v.y), "=r"(v.z), "=r"(v.w) : "l"(p) : "memory"); return v;
}
__device__ __forceinline__ uint32_t movmatrix_t(uint32_t a) {
  uint32_t d; asm volatile("movmatrix.sync.aligned.m8n8.trans.b16 %0, %1;" : "=r"(d) : "r"(a)); return d;
}
__device__ __forceinline__ void mma16(float (&c)[4], uint32_t a0, uint32_t a1, uint32_t a2, uint32_t a3, uint32_t b0, uint32_t b1) {
  asm volatile("mma.sync.aligned.m16n8k16.row.col.f32.bf16.bf16.f32 {%0,%1,%2,%3}, {%4,%5,%6,%7}, {%8,%9}, {%0,%1,%2,%3};"
               : "+f"(c[0]), "+f"(c[1]), "+f"(c[2]), "+f"(c[3]) : "r"(a0), "r"(a1), "r"(a2), "r"(a3), "r"(b0), "r"(b1));
}
__device__ __forceinline__ void sts128(uint32_t addr, uint32_t a, uint32_t b, uint32_t c, uint32_t d) {
  asm volatile("st.shared.v4.b32 [%0], {%1,%2,%3,%4};" :: "r"(addr), "r"(a), "r"(b), "r"(c), "r"(d) : "memory");
}
__device__ __forceinline__ uint4 lds128(uint32_t addr) {
  uint4 v; asm volatile("ld.shared.v4.b32 {%0,%1,%2,%3}, [%4];" : "=r"(v.x), "=r"(v.y), "=r"(v.z), "=r"(v.w) : "r"(addr) : "memory"); return v;
}
__device__ __forceinline__ uint32_t lds32(uint32_t addr) {
  uint32_t v; asm volatile("ld.shared.b32 %0, [%1];" : "=r"(v) : "r"(addr) : "memory"); return v;
}
__device__ __forceinline__ float2 lds64f(uint32_t addr) {
  float2 v; asm volatile("ld.shared.v2.f32 {%0,%1}, [%2];" : "=f"(v.x), "=f"(v.y) : "r"(addr) : "memory"); return v;
}
__device__ __forceinline__ void sts64(uint32_t addr, uint32_t a, uint32_t b) {
  asm volatile("st.shared.v2.b32 [%0], {%1, %2};" :: "r"(addr), "r"(a), "r"(b) : "memory");
}
__device__ __forceinline__ float fast_ex2(float x) { float y; asm("ex2.approx.ftz.f32 %0, %1;" : "=f"(y) : "f"(x)); return y; }
__device__ __forceinline__ float fast_rcp(float x) { float y; asm("rcp.approx.ftz.f32 %0, %1;" : "=f"(y) : "f"(x)); return y; }
__device__ __forceinline__ float fast_rsqrt(float x) { float y; asm("rsqrt.approx.ftz.f32 %0, %1;" : "=f"(y) : "f"(x)); return y; }
__device__ __forceinline__ float silu_f(float g) { return g * fast_rcp(1.f + fast_ex2(g * -1.4426950408889634f)); }
__device__ __forceinline__ float swiglu(float g, float u) {
  const float h = 0.5f * g;
  float t; asm("tanh.approx.f32 %0, %1;" : "=f"(t) : "f"(h));
  return fmaf(h, t, h) * u;
}

__device__ __forceinline__ void wgmma_m64n128k16_ss(float (&d)[64], uint64_t descA, uint64_t descB, int scaleD) {
  asm volatile("{\n.reg .pred p;\nsetp.ne.b32 p, %66, 0;\n"
    "wgmma.mma_async.sync.aligned.m64n128k16.f32.bf16.bf16 "
    "{%0, %1, %2, %3, %4, %5, %6, %7, %8, %9, %10, %11, %12, %13, %14, %15, "
    "%16, %17, %18, %19, %20, %21, %22, %23, %24, %25, %26, %27, %28, %29, %30, %31, "
    "%32, %33, %34, %35, %36, %37, %38, %39, %40, %41, %42, %43, %44, %45, %46, %47, "
    "%48, %49, %50, %51, %52, %53, %54, %55, %56, %57, %58, %59, %60, %61, %62, %63}, "
    "%64, %65, p, 1, 1, 0, 1;\n}\n"
    : "+f"(d[0]), "+f"(d[1]), "+f"(d[2]), "+f"(d[3]), "+f"(d[4]), "+f"(d[5]), "+f"(d[6]), "+f"(d[7]),
      "+f"(d[8]), "+f"(d[9]), "+f"(d[10]), "+f"(d[11]), "+f"(d[12]), "+f"(d[13]), "+f"(d[14]), "+f"(d[15]),
      "+f"(d[16]), "+f"(d[17]), "+f"(d[18]), "+f"(d[19]), "+f"(d[20]), "+f"(d[21]), "+f"(d[22]), "+f"(d[23]),
      "+f"(d[24]), "+f"(d[25]), "+f"(d[26]), "+f"(d[27]), "+f"(d[28]), "+f"(d[29]), "+f"(d[30]), "+f"(d[31]),
      "+f"(d[32]), "+f"(d[33]), "+f"(d[34]), "+f"(d[35]), "+f"(d[36]), "+f"(d[37]), "+f"(d[38]), "+f"(d[39]),
      "+f"(d[40]), "+f"(d[41]), "+f"(d[42]), "+f"(d[43]), "+f"(d[44]), "+f"(d[45]), "+f"(d[46]), "+f"(d[47]),
      "+f"(d[48]), "+f"(d[49]), "+f"(d[50]), "+f"(d[51]), "+f"(d[52]), "+f"(d[53]), "+f"(d[54]), "+f"(d[55]),
      "+f"(d[56]), "+f"(d[57]), "+f"(d[58]), "+f"(d[59]), "+f"(d[60]), "+f"(d[61]), "+f"(d[62]), "+f"(d[63])
    : "l"(descA), "l"(descB), "r"(scaleD));
}
__device__ __forceinline__ void wgmma_m64n256k16_rs(float (&d)[128], uint32_t a0, uint32_t a1, uint32_t a2, uint32_t a3, uint64_t descB, int scaleD) {
  asm volatile("{\n.reg .pred p;\nsetp.ne.b32 p, %133, 0;\n"
    "wgmma.mma_async.sync.aligned.m64n256k16.f32.bf16.bf16 "
    "{%0, %1, %2, %3, %4, %5, %6, %7, %8, %9, %10, %11, %12, %13, %14, %15, "
    "%16, %17, %18, %19, %20, %21, %22, %23, %24, %25, %26, %27, %28, %29, %30, %31, "
    "%32, %33, %34, %35, %36, %37, %38, %39, %40, %41, %42, %43, %44, %45, %46, %47, "
    "%48, %49, %50, %51, %52, %53, %54, %55, %56, %57, %58, %59, %60, %61, %62, %63, "
    "%64, %65, %66, %67, %68, %69, %70, %71, %72, %73, %74, %75, %76, %77, %78, %79, "
    "%80, %81, %82, %83, %84, %85, %86, %87, %88, %89, %90, %91, %92, %93, %94, %95, "
    "%96, %97, %98, %99, %100, %101, %102, %103, %104, %105, %106, %107, %108, %109, %110, %111, "
    "%112, %113, %114, %115, %116, %117, %118, %119, %120, %121, %122, %123, %124, %125, %126, %127}, "
    "{%128, %129, %130, %131}, %132, p, 1, 1, 1;\n}\n"
    : "+f"(d[0]), "+f"(d[1]), "+f"(d[2]), "+f"(d[3]), "+f"(d[4]), "+f"(d[5]), "+f"(d[6]), "+f"(d[7]),
      "+f"(d[8]), "+f"(d[9]), "+f"(d[10]), "+f"(d[11]), "+f"(d[12]), "+f"(d[13]), "+f"(d[14]), "+f"(d[15]),
      "+f"(d[16]), "+f"(d[17]), "+f"(d[18]), "+f"(d[19]), "+f"(d[20]), "+f"(d[21]), "+f"(d[22]), "+f"(d[23]),
      "+f"(d[24]), "+f"(d[25]), "+f"(d[26]), "+f"(d[27]), "+f"(d[28]), "+f"(d[29]), "+f"(d[30]), "+f"(d[31]),
      "+f"(d[32]), "+f"(d[33]), "+f"(d[34]), "+f"(d[35]), "+f"(d[36]), "+f"(d[37]), "+f"(d[38]), "+f"(d[39]),
      "+f"(d[40]), "+f"(d[41]), "+f"(d[42]), "+f"(d[43]), "+f"(d[44]), "+f"(d[45]), "+f"(d[46]), "+f"(d[47]),
      "+f"(d[48]), "+f"(d[49]), "+f"(d[50]), "+f"(d[51]), "+f"(d[52]), "+f"(d[53]), "+f"(d[54]), "+f"(d[55]),
      "+f"(d[56]), "+f"(d[57]), "+f"(d[58]), "+f"(d[59]), "+f"(d[60]), "+f"(d[61]), "+f"(d[62]), "+f"(d[63]),
      "+f"(d[64]), "+f"(d[65]), "+f"(d[66]), "+f"(d[67]), "+f"(d[68]), "+f"(d[69]), "+f"(d[70]), "+f"(d[71]),
      "+f"(d[72]), "+f"(d[73]), "+f"(d[74]), "+f"(d[75]), "+f"(d[76]), "+f"(d[77]), "+f"(d[78]), "+f"(d[79]),
      "+f"(d[80]), "+f"(d[81]), "+f"(d[82]), "+f"(d[83]), "+f"(d[84]), "+f"(d[85]), "+f"(d[86]), "+f"(d[87]),
      "+f"(d[88]), "+f"(d[89]), "+f"(d[90]), "+f"(d[91]), "+f"(d[92]), "+f"(d[93]), "+f"(d[94]), "+f"(d[95]),
      "+f"(d[96]), "+f"(d[97]), "+f"(d[98]), "+f"(d[99]), "+f"(d[100]), "+f"(d[101]), "+f"(d[102]), "+f"(d[103]),
      "+f"(d[104]), "+f"(d[105]), "+f"(d[106]), "+f"(d[107]), "+f"(d[108]), "+f"(d[109]), "+f"(d[110]), "+f"(d[111]),
      "+f"(d[112]), "+f"(d[113]), "+f"(d[114]), "+f"(d[115]), "+f"(d[116]), "+f"(d[117]), "+f"(d[118]), "+f"(d[119]),
      "+f"(d[120]), "+f"(d[121]), "+f"(d[122]), "+f"(d[123]), "+f"(d[124]), "+f"(d[125]), "+f"(d[126]), "+f"(d[127])
    : "r"(a0), "r"(a1), "r"(a2), "r"(a3), "l"(descB), "r"(scaleD));
}

constexpr uint32_t MSLOT = 32768, QSLOT = 49152;
constexpr int NM = 6;
constexpr uint32_t SM_X0 = 3 * QSLOT;
constexpr uint32_t SM_XR = SM_X0 + 16384;
constexpr uint32_t SM_STG = 196608;
constexpr uint32_t SM_XCH = SM_STG + 16384;
constexpr uint32_t SM_BAR = SM_STG + 32768;
constexpr uint32_t SM_VEC = SM_BAR + 512;
constexpr uint32_t SM_MODT = SM_VEC;
constexpr uint32_t SM_TOTAL = SM_VEC + 2048;
constexpr uint32_t B_X = SM_BAR  , B_EQ = B_X + 64, B_EM = B_EQ + 32, B_STREQ = B_EM + 48, B_STH = B_STREQ + 8, B_LN = B_STH + 8,
                   B_FQ = B_LN + 8, B_FM = B_FQ + 32, B_MOD = B_FM + 48, B_GATE = B_MOD + 8, B_STFREE = B_GATE + 8, B_VEC = B_STFREE + 8  ,
                   B_FLG = B_VEC + 16  , B_H2A = B_FLG + 88, B_RST = B_H2A + 8, B_END = B_RST + 8;
constexpr int NB_WG = 1  , NB_CONS = 3, NB_ORD = 4  ;
#define PF_BYTES 512
#define X_S1 7
#define X_POLL 5
#define SVC_WAIT mbar_sleep
#define PRD_WAIT mbar_wait
#define WPRE 2
#define QORD 2
#define QPOS 1
#define AUX_SLOW 68
#define AUX_GAP 500
#define DTAIL 4
#define EF 7
#define TRG_WAIT mbar_wait
#define ST_SPIN0 2
#define AUX_HOLD 3200
#define X_UP 1
#define X_GAP 250

struct Maps {
  CUtensorMap x, out;
  CUtensorMap o, h2, hh;
  CUtensorMap wqk, wvv, wq1, wo, w1, w3, w2;
  CUtensorMap wmod;
};

struct Ring { int st; uint32_t ph; int prev; uint32_t dl;
};
__device__ __forceinline__ void ring_next(Ring& r) { if (++r.st == NM) { r.st = 0; r.ph ^= 1; } }

__device__ __forceinline__ void retire_prev(uint32_t rel, bool on) {
  wgmma_commit();
  wgmma_wait<1>();
  if (on) mbar_arrive_e(rel);
}
struct Nop { __device__ __forceinline__ void operator()() const {} };
template <bool REL = true, class F = Nop>
__device__ __forceinline__ void mma_step(float (&acc)[64], uint32_t a, uint32_t b, bool first, uint32_t rel, F urgent = F()) {
  const uint32_t alo = (a >> 4) + (1u << 16), blo = (b >> 4) + (512u << 16);
  wgmma_fence();
  #pragma unroll
  for (int k = 0; k < 4; k++) {
    wgmma_m64n128k16_ss(acc, desc_from_lo(alo + k * 2), desc_from_lo(blo + k * 128), k > 0 || !first);
    if (k == 0) { retire_prev(rel, REL); urgent(); }
  }
  wgmma_commit();
}
__device__ __forceinline__ uint32_t m_wait(uint32_t sbase, const Ring& r) {
  mbar_wait(sbase + B_FM + 8 * r.st, r.ph, r.dl);
  return sbase + r.st * MSLOT;
}
__device__ __forceinline__ uint32_t m_prev(uint32_t sbase, const Ring& r) { return sbase + B_EM + 8 * r.prev; }
__device__ __forceinline__ void m_next(Ring& r) {
  r.prev = r.st; ring_next(r);
}
__device__ __forceinline__ void m_step(float (&acc)[64], uint32_t sbase, uint32_t wgoff, Ring& r, bool first = false) {
  const uint32_t slot = m_wait(sbase, r);
  mma_step(acc, slot + wgoff, slot + 16384, first, m_prev(sbase, r));
  m_next(r);
}

struct LnRow { uint32_t rs[2], nb[2]; };
__device__ __forceinline__ void ln_row(LnRow& l, int h, float mean, float rstd) {
  l.rs[h] = pack_bf16(rstd, rstd);
  const float nb = -mean * bf_lo(l.rs[h]);
  l.nb[h] = pack_bf16(nb, nb);
}
__device__ __forceinline__ uint32_t ln_mod(uint32_t x, const LnRow& l, int h, uint32_t c1, uint32_t s) {
  return fma_bf2(fma_bf2(x, l.rs[h], l.nb[h]), c1, s);
}

__device__ __forceinline__ uint32_t q_wait(int u, uint32_t sbase, uint32_t dl) {
  mbar_wait(sbase + B_FQ + 8 * (u & 3), (u >> 2) & 1, dl);
  return sbase + (u & 3) * QSLOT;
}
__device__ __forceinline__ uint32_t q_empty(int u, uint32_t sbase) { return sbase + B_EQ + 8 * (u & 3); }
struct Frag4 { uint32_t o[4]; };
__device__ __forceinline__ void q_load(uint32_t (&A)[16], uint4 (&p)[4], int kk, uint32_t tile, const Frag4& f, uint32_t t) {
  ldmatrix_x4(tile + f.o[kk], A[4 * kk], A[4 * kk + 1], A[4 * kk + 2], A[4 * kk + 3]);
  p[kk] = lds128(t + kk * 64);
}
__device__ __forceinline__ void q_norm(uint32_t (&A)[16], const uint4 (&p)[4], int kk, const LnRow& l) {
  A[4 * kk + 0] = ln_mod(A[4 * kk + 0], l, 0, p[kk].x, p[kk].z); A[4 * kk + 1] = ln_mod(A[4 * kk + 1], l, 1, p[kk].x, p[kk].z);
  A[4 * kk + 2] = ln_mod(A[4 * kk + 2], l, 0, p[kk].y, p[kk].w); A[4 * kk + 3] = ln_mod(A[4 * kk + 3], l, 1, p[kk].y, p[kk].w);
}
template <bool NEXT>
__device__ __forceinline__ void q_step_rs(float (&acc)[128], uint32_t (&A)[16], uint32_t (&N)[16], uint4 (&p)[4], int u, uint32_t sbase,
                                          const Frag4& f, uint32_t tab, const LnRow& l, int hq, bool first, uint32_t dl, int wg) {
  const uint32_t slot = first ? sbase : q_wait(u, sbase, dl);
  const uint32_t blo = ((slot + 16384) >> 4) + (512u << 16), t = tab + ((u + 1) & 7) * 256;
  #pragma unroll
  for (int kk = 0; kk < 4; kk++) q_norm(A, p, kk, l);
  if (first) {
    #pragma unroll
    for (int i = 0; i < 16; i++) asm volatile("" : "+r"(A[i]));
    mbar_wait(sbase + B_GATE, 0, dl);
    PROF(6, threadIdx.x == 0);
  }
  if (QORD == 1 && first && wg == 1) bar_sync(NB_ORD, 256);
  if (QORD == 2 && !(first && wg == 0)) bar_sync(NB_ORD + wg, 256);
  wgmma_fence();
  #pragma unroll
  for (int kk = 0; kk < 4; kk++) {
    wgmma_m64n256k16_rs(acc, A[4 * kk], A[4 * kk + 1], A[4 * kk + 2], A[4 * kk + 3], desc_from_lo(blo + kk * 128), kk > 0 || !first);
    if (kk == 0) retire_prev(q_empty(u - 1, sbase), !first);
    if (NEXT && kk < 2) { q_load(N, p, 2 * kk, slot, f, t); q_load(N, p, 2 * kk + 1, slot, f, t); }
    if (QORD == 1 && first && kk == QPOS && wg == 0) bar_arrive(NB_ORD, 256);
    if (QORD == 2 && kk == QPOS && (NEXT || wg == 0)) bar_arrive(NB_ORD + (wg ^ 1), 256);
    if (kk == 1) {
      const uint32_t dst = sbase + SM_STG + (u >> 3) * 16384 + (f.o[0] ^ ((u & 6) << 4));
      #pragma unroll
      for (int q = 0; q < 4; q++) stmatrix_x4_if(dst, A[4 * q], A[4 * q + 1], A[4 * q + 2], A[4 * q + 3], hq == q);
    }
  }
  wgmma_commit();
}

typedef uint32_t Frag8[8];
template <int N> __device__ __forceinline__ void pack_half(Frag8& f, const float (&acc)[N], int off, int half) {
  #pragma unroll
  for (int e = 0; e < 8; e++) { f[e] = pack_bf16(acc[off + 4 * e + 2 * half], acc[off + 4 * e + 2 * half + 1]); asm volatile("" : "+r"(f[e])); }
}
__device__ __forceinline__ void transpose8(Frag8& f) {
  #pragma unroll
  for (int e = 0; e < 8; e++) f[e] = movmatrix_t(f[e]);
}
__device__ __forceinline__ void attn_send(const Frag8& f, int kv, uint32_t xch, int warp, uint4* halo_out, bool has_next) {
  if (warp == 3) {
    st_rlx_v4(halo_out + kv * 64, f[0], f[1], f[2], f[3], has_next); st_rlx_v4(halo_out + kv * 64 + 32, f[4], f[5], f[6], f[7], has_next);
  } else {
    sts128(xch + 2048 + kv * 1024, f[0], f[1], f[2], f[3]); sts128(xch + 2048 + kv * 1024 + 512, f[4], f[5], f[6], f[7]);
  }
}
template <int N>
__device__ __forceinline__ void attn_recv(uint4* p, int first, uint32_t xch, int wg, int warp, const uint4* halo_in, bool has_prev) {
  bar_sync(NB_WG + wg, 128);
  #pragma unroll
  for (int e = 0; e < N; e++)
    asm volatile("{\n.reg .pred p, q;\nsetp.ne.b32 p, %6, 0;\nsetp.ne.b32 q, %7, 0;\n"
                 "mov.b32 %0, 0;\nmov.b32 %1, 0;\nmov.b32 %2, 0;\nmov.b32 %3, 0;\n"
                 "@p ld.shared.v4.b32 {%0,%1,%2,%3}, [%4];\n@q ld.relaxed.gpu.global.v4.u32 {%0,%1,%2,%3}, [%5];\n}"
                 : "=&r"(p[e].x), "=&r"(p[e].y), "=&r"(p[e].z), "=&r"(p[e].w)
                 : "r"(xch + (first + e) * 512), "l"(halo_in + (first + e) * 32), "r"((int)(warp > 0)), "r"((int)(warp == 0 && has_prev)) : "memory");
}
template <int N>
__device__ __forceinline__ void attn_check(uint4* p, int first, int warp, const uint4* halo_in, uint32_t dl) {
  if (warp == 0) {
    while (true) {
      uint32_t m = 0;
      #pragma unroll
      for (int e = 0; e < N; e++) m = max(max(m, max(p[e].x, p[e].y)), max(p[e].z, p[e].w));
      if (poll_done(m != ~0u, dl)) break;
      #pragma unroll
      for (int e = 0; e < N; e++) p[e] = ld_rlx_v4(halo_in + (first + e) * 32);
    }
  }
}
__device__ __forceinline__ void attn_core(const Frag8& qA, const Frag8& qB, const Frag8& kA, const Frag8& kB, const Frag8& vA, const Frag8& vB,
                                          const uint4* kP, const uint4* vP, bool noprev, int lane, float (&o)[2][5][4]) {
  const int g = lane >> 2, qd = lane & 3;
  const bool s0 = 2 * qd > g, s1 = 2 * qd + 1 > g;
  const uint32_t msk = (s0 ? 0xFFFFu : 0u) | (s1 ? 0xFFFF0000u : 0u);
  constexpr float SC = 0.17677669529663687f * 1.4426950408889634f;
  float s[2][3][4];
  #pragma unroll
  for (int h = 0; h < 2; h++) {
    #pragma unroll
    for (int nb = 0; nb < 3; nb++) s[h][nb][0] = s[h][nb][1] = s[h][nb][2] = s[h][nb][3] = 0.f;
    #pragma unroll
    for (int kk = 0; kk < 2; kk++) {
      const int e = 4 * h + 2 * kk;
      mma16(s[h][1], qA[e], qB[e], qA[e + 1], qB[e + 1], kA[e], kA[e + 1]);
      mma16(s[h][2], qA[e], qB[e], qA[e + 1], qB[e + 1], kB[e], kB[e + 1]);
      mma16(s[h][0], qA[e], qB[e], qA[e + 1], qB[e + 1], kk ? kP[h].z : kP[h].x, kk ? kP[h].w : kP[h].y);
    }
  }
  #pragma unroll
  for (int h = 0; h < 2; h++) {
    float l[4], m[2];
    l[0] = s0 ? (noprev ? -INFINITY : s[h][0][0]) : s[h][1][0];
    l[1] = s1 ? (noprev ? -INFINITY : s[h][0][1]) : s[h][1][1];
    l[2] = s0 ? s[h][1][2] : s[h][2][2];
    l[3] = s1 ? s[h][1][3] : s[h][2][3];
    m[0] = fmaxf(l[0], l[1]); m[1] = fmaxf(l[2], l[3]);
    #pragma unroll
    for (int x = 1; x <= 2; x <<= 1)
      #pragma unroll
      for (int e = 0; e < 2; e++) m[e] = fmaxf(m[e], __shfl_xor_sync(0xffffffffu, m[e], x));
    #pragma unroll
    for (int e = 0; e < 4; e++) l[e] = fast_ex2((l[e] - m[e >> 1]) * SC);
    const uint32_t plo = pack_bf16(l[0], l[1]), phi = pack_bf16(l[2], l[3]);
    const uint32_t vp[4] = {vP[h].x, vP[h].y, vP[h].z, vP[h].w};
    #pragma unroll
    for (int d = 0; d < 5; d++) o[h][d][0] = o[h][d][1] = o[h][d][2] = o[h][d][3] = 0.f;
    mma16(o[h][4], 0x3F803F80u, 0u, 0u, 0x3F803F80u, plo, phi);
    #pragma unroll
    for (int m2 = 0; m2 < 2; m2++) {
      const int e = 4 * h + 2 * m2;
      mma16(o[h][2 * m2], vp[2 * m2], vp[2 * m2 + 1], vA[e], vA[e + 1], plo & msk, plo & ~msk);
      mma16(o[h][2 * m2 + 1], vA[e], vA[e + 1], vB[e], vB[e + 1], phi & msk, phi & ~msk);
    }
  }
}
__device__ __forceinline__ void attn_store(const float (&o)[2][5][4], int h, uint32_t sbase, const Frag4& f) {
  float r[4];
  #pragma unroll
  for (int e = 0; e < 4; e++) r[e] = fast_rcp(o[h][4][e]);
  #pragma unroll
  for (int m = 0; m < 2; m++) {
    const float (&lo)[4] = o[h][2 * m], (&hi)[4] = o[h][2 * m + 1];
    stmatrix_x4_t(sbase + SM_STG + f.o[2 * h + m], pack_bf16(lo[0] * r[0], lo[1] * r[1]), pack_bf16(hi[0] * r[2], hi[1] * r[3]),
                  pack_bf16(lo[2] * r[0], lo[3] * r[1]), pack_bf16(hi[2] * r[2], hi[3] * r[3]));
  }
}

__device__ __forceinline__ void request_store(uint32_t bar) {
  fence_proxy_async_smem();
  mbar_arrive_e(bar);
}

__device__ __forceinline__ void g_switch(float (&cur)[64], float (&prv)[64], int nrest, bool first, int n, uint32_t sbase, uint32_t wgoff,
                                         const Frag4& f, Ring& r) {
  #pragma unroll 1
  for (int i = 1; i < nrest; i++) m_step(prv, sbase, wgoff, r);
  m_step(prv, sbase, wgoff, r);
  m_step(cur, sbase, wgoff, r, first);
  mbar_wait(sbase + B_STFREE, (n - 1) & 1, r.dl);
  fence_regs(prv);
  PROF(28 + n, threadIdx.x == 0);
  #pragma unroll
  for (int jj = 0; jj < 4; jj++) {
    uint32_t p[4];
    #pragma unroll
    for (int e = 0; e < 4; e++) {
      const int i = jj * 8 + e * 2;
      p[e] = pack_bf16(swiglu(prv[i], prv[i + 32]), swiglu(prv[i + 1], prv[i + 33]));
    }
    stmatrix_x4(sbase + SM_STG + f.o[jj], p[0], p[1], p[2], p[3]);
    m_step(cur, sbase, wgoff, r);
  }
  request_store(sbase + B_STREQ);
}

__device__ __forceinline__ uint32_t bad2(uint32_t a, uint32_t b, unsigned par) {
  uint32_t d; asm("lop3.b32 %0, %1, %2, %3, 0x7E;" : "=r"(d) : "r"(a), "r"(b), "r"(par)); return d;
}
__device__ __forceinline__ uint32_t bad4(const uint4& v, unsigned par) { return bad2(v.x, v.y, par) | bad2(v.z, v.w, par); }
__device__ __forceinline__ uint32_t hi_halves(uint32_t lo, uint32_t hi) { return __byte_perm(lo, hi, 0x7632); }

__device__ __forceinline__ void gather_table(const float* src, uint32_t dst, uint32_t bar, unsigned par, uint32_t dl) {
  asm volatile("{\n.reg .pred p, e;\n.reg .b32 s<4>, c<4>, t<4>, w<4>;\n"
               "elect.sync _|e, 0xffffffff;\n"
               "LAB_POLL:\n"
               "ld.relaxed.gpu.global.v4.u32 {s0, s1, s2, s3}, [%0];\n"
               "ld.relaxed.gpu.global.v4.u32 {c0, c1, c2, c3}, [%0 + 4096];\n"
               "prmt.b32 w0, c0, c1, 0x7632;\nprmt.b32 w1, c2, c3, 0x7632;\nprmt.b32 w2, s0, s1, 0x7632;\nprmt.b32 w3, s2, s3, 0x7632;\n"
               "st.shared.v4.b32 [%1], {w0, w1, w2, w3};\n"
               "lop3.b32 t0, s0, s1, %3, 0x7E;\nlop3.b32 t1, s2, s3, %3, 0x7E;\nlop3.b32 t2, c0, c1, %3, 0x7E;\nlop3.b32 t3, c2, c3, %3, 0x7E;\n"
               "lop3.b32 t0, t0, t1, 1, 0xA8;\nlop3.b32 t2, t2, t3, 1, 0xA8;\n"
               "or.b32 t0, t0, t2;\n"
               "setp.eq.u32 p, t0, 0;\n"
               "vote.sync.all.pred p, p, 0xffffffff;\n"
               "@p bra.uni LAB_OK;\n"
               "mov.u32 t0, %%clock;\nsub.s32 t0, t0, %4;\nsetp.lt.s32 p, t0, 0;\n"
               "vote.sync.all.pred p, p, 0xffffffff;\n"
               "@p bra.uni LAB_POLL;\n"
               "LAB_OK:\n"
               "@e mbarrier.arrive.shared::cta.b64 _, [%2];\n}"
               :: "l"(src), "r"(dst), "r"(bar), "r"(par), "r"(dl) : "memory");
}

__device__ __forceinline__ int other_slot(int i, int j) { return i < 4 ? (~j & 4) + i : (j & 4) + i - 4 + (i - 4 >= (j & 3)); }

__device__ __forceinline__ int aux_col(int a, int u) { return u < 8 ? (a & 1) * 1024 + (2 * u + (a >> 1)) * 64 : 2048 + ((u - 8) * 4 + a) * 64; }
constexpr int NA = 7;
constexpr uint32_t A_FULL = SM_BAR, A_EMPTY = SM_BAR + 64, A_SUM = SM_BAR + 128, A_FREE = SM_BAR + 136, SM_RED = SM_VEC;
__device__ __forceinline__ void aux_role(const Maps& maps, const bf16* __restrict__ cvec, Mail* mail0, int zero, int a, uint32_t sbase, int wid) {
  const int tid = threadIdx.x, lane = tid & 31;
  const uint32_t dl = clock32() + 800000000u;
  int st = 0; uint32_t ph = 0;
  if (wid == 8) {
    prefetch_tmap(&maps.wmod);
    #pragma unroll
    for (int i = 0; i < 18; i++) mbar_init_e(sbase + A_FULL + 8 * i, i < 8 ? 1 : i < 17 ? 8 : 2);
    fence_proxy_async_smem();
    bar_arrive(0, 352);
    PROF(39, lane == 0);
    #pragma unroll
    for (int i = 0; i < NA; i++) {
      mbar_expect_tx_e(sbase + A_FULL + 8 * i, 32768);
      tma_load_2d(sbase + i * MSLOT, &maps.wmod, sbase + A_FULL + 8 * i, aux_col(a, i >> 2), (i & 3) * 256);
    }
    PROF(40, lane == 0);
    #pragma unroll 1
    for (int i = NA; i < 96; i++) {
      if (i >= AUX_SLOW) wait_until(clock32() + AUX_GAP);
      if (i == 8) wait_until(dl - 800000000u + AUX_HOLD);
      mbar_wait(sbase + A_EMPTY + 8 * st, ph, dl);
      mbar_expect_tx_e(sbase + A_FULL + 8 * st, 32768);
      tma_load_2d<(EF & 1) != 0>(sbase + st * MSLOT, &maps.wmod, sbase + A_FULL + 8 * st, aux_col(a, i >> 2), (i & 3) * 256);
      if (++st == NA) { st = 0; ph ^= 1; }
    }
  } else if (wid < 8) {
    const int g = lane >> 2, qd = lane & 3;
    uint32_t sc[16];
    const uint2 c = *reinterpret_cast<const uint2*>(cvec + tid * 4);
    sts64(sbase + SM_RED + tid * 8, pack_bf16(silu_f(bf_lo(c.x)), silu_f(bf_hi(c.x))), pack_bf16(silu_f(bf_lo(c.y)), silu_f(bf_hi(c.y))));
    bar_sync(0, 352);
    #pragma unroll
    for (int i = 0; i < 16; i++) sc[i] = lds32(sbase + SM_RED + ((i >> 2) * 256 + wid * 32 + (i & 3) * 8 + qd * 2) * 2);
    bar_sync(NB_CONS, 256);
    PROF(38, tid == 0);
    const uint32_t aoff = (wid * 32 + (lane & 7) + (lane >> 4) * 8) * 128 + ((((lane >> 3) & 1) ^ (lane & 7)) << 4);
    uint32_t w[2][8][4];
    auto fetch = [&](uint32_t (&f)[8][4]) {
      mbar_wait(sbase + A_FULL + 8 * st, ph, dl);
      #pragma unroll
      for (int e = 0; e < 8; e++) ldmatrix_x4_t((sbase + st * MSLOT + aoff + (e >> 2) * 2048) ^ ((e & 3) << 5), f[e]);
      if (++st == NA) { st = 0; ph ^= 1; }
    };
    #pragma unroll 1
    for (int u = 0; u < 24; u++) {
      float acc[4][4];
      #pragma unroll
      for (int m = 0; m < 4; m++) acc[m][0] = acc[m][1] = acc[m][2] = acc[m][3] = 0.f;
      fetch(w[0]);
      #pragma unroll
      for (int q = 0; q < 4; q++) {
        PROF(30 + (u & 1) * 4 + q, u < 2 && tid == 0);
        const uint32_t rel = sbase + A_EMPTY + 8 * (st == 0 ? NA - 1 : st - 1);
        if (q < 3) fetch(w[(q + 1) & 1]);
        uint32_t dep = 0;
        #pragma unroll
        for (int e = 0; e < 8; e++) dep |= w[q & 1][e][0];
        mbar_arrive_e(rel + (dep & zero));
        if (q == 1) mbar_wait(sbase + A_FREE, (u & 1) ^ 1, dl);
        #pragma unroll
        for (int e = 0; e < 8; e++) {
          const uint32_t (&f)[4] = w[q & 1][e];
          mma16(acc[e & 3], f[0], f[1], f[2], f[3], sc[4 * q + 2 * (e >> 2)], sc[4 * q + 2 * (e >> 2) + 1]);
        }
      }
      const float v0 = qd & 2 ? (qd & 1 ? acc[3][0] : acc[2][0]) : (qd & 1 ? acc[1][0] : acc[0][0]);
      const float v1 = qd & 2 ? (qd & 1 ? acc[3][2] : acc[2][2]) : (qd & 1 ? acc[1][2] : acc[0][2]);
      sts64(sbase + SM_RED + wid * 256 + (qd * 8 + g) * 8, __float_as_uint(v0), __float_as_uint(v1));
      mbar_arrive_e(sbase + A_SUM);
    }
  } else if (wid < 11) {
    float* const mail = &mail0->mod[(wid - 9) * 4 * 6 * D_ + 2 * lane];
    unsigned par = ld_relaxed(&mail0->flags[FL_EPOCH + (lane >> 5)]);
    bar_sync(0, 352);
    par = (par + 1) & 1;
    #pragma unroll 1
    for (int u = -2; u < 24; u++) {
      if (u >= 0) {
        const int col = aux_col(a, u);
        const float add = (col >> 10) == 1 || (col >> 10) == 4 ? 1.f : 0.f;
        mbar_wait(sbase + A_SUM, u & 1, dl);
        float2 v[8];
        #pragma unroll
        for (int w = 0; w < 8; w++) v[w] = lds64f(sbase + SM_RED + w * 256 + lane * 8);
        const float t0 = ((v[0].x + v[1].x) + (v[2].x + v[3].x)) + ((v[4].x + v[5].x) + (v[6].x + v[7].x));
        const float t1 = ((v[0].y + v[1].y) + (v[2].y + v[3].y)) + ((v[4].y + v[5].y) + (v[6].y + v[7].y));
        const uint32_t w = pack_bf16(add + bf16_round(t0), add + bf16_round(t1)), o = __shfl_xor_sync(0xffffffffu, w, 1);
        const uint32_t m0 = (lane & 1) ? (o & 0xFFFF0000u) : (w << 16), m1 = (lane & 1) ? (w & 0xFFFF0000u) : (o << 16);
        #pragma unroll
        for (int c = 0; c < 4; c++) st_rlx_v2(mail + c * 6 * D_ + col, m0 | par, m1 | par, true);
        mbar_arrive_e(sbase + A_FREE);
        PROF(1 + u, tid == 288);
      }
      #pragma unroll 1
      for (int v = 2 * (u + 2); v < 2 * (u + 3) && v < 24; v++)
        #pragma unroll
        for (int c = 0; c < 4; c++) st_rlx_v2(mail + c * 6 * D_ + aux_col(a, v), par ^ 1, par ^ 1, true);
    }
  }
}

template <int MODE>
__global__ void __launch_bounds__(384, 1)
fused_block_kernel(const bf16* __restrict__ x, const bf16* __restrict__ cvec, const bf16* __restrict__ wmod, Mail* mail0, int zero,
                   const __grid_constant__ Maps maps) {
  extern __shared__ __align__(1024) uint8_t smem_raw[];
  const uint32_t sbase = smem_u32(smem_raw);
  const int tid = threadIdx.x, lane = tid & 31;
  PROFN(0, tid == 0);
  const int wid = __shfl_sync(0xffffffffu, tid >> 5, 0);
  const int b = cta_role<MODE>();
  if (b >= NCTA) { aux_role(maps, cvec, mail0, zero, b - NCTA, sbase, wid); return; }
  const int jg = b >> 6, mb = jg ? 31 - (b >> 2) : (b >> 2), j = 4 * jg + (b & 3);
  const uint32_t dl = clock32() + 800000000u;
  unsigned* const flags = &mail0->flags[mb * 32];
  const int row0 = mb * 128;

  if (wid >= 8) {
    if (wid == 8) {
      #pragma unroll
      for (int i = 0; i < 8; i++) mbar_init_e(sbase + B_X + 8 * i, 1);
      fence_proxy_async_smem();
      #pragma unroll
      for (int q = 0; q < X_UP; q++) {
        mbar_expect_tx_e(sbase + B_X + 8 * q, 4096);
        bulk_load(sbase + SM_XR + q * 4096, x + (size_t)(row0 + j * 16 + 2 * q) * D_, 4096, sbase + B_X + 8 * q);
      }
    } else if (wid == 11) {
      #pragma unroll
      for (int i = 0; i < 12; i++) prefetch_tmap(&maps.x + i);
    } else if (wid == 9) {
      #pragma unroll
      for (uint32_t bar = B_EQ; bar < B_FM; bar += 8) mbar_init_e(sbase + bar, bar < B_FQ ? 8 : bar == B_FQ + 8 || bar == B_FQ + 24 ? 2 : 1);
      fence_proxy_async_smem();
    } else {
      #pragma unroll
      for (uint32_t bar = B_FM; bar < B_END; bar += 8) mbar_init_e(sbase + bar, 1);
      fence_proxy_async_smem();
    }
    bar_sync(0, 384);
    reg_dealloc<40>();
    PROF(92, tid == 256);
    if (wid == 8) {
      uint32_t tnext = clock32();
      #pragma unroll 1
      for (int q = X_UP; q < 8; q++) {
        wait_until(tnext);
        mbar_expect_tx_e(sbase + B_X + 8 * q, 4096);
        bulk_load(sbase + SM_XR + q * 4096, x + (size_t)(row0 + j * 16 + 2 * q) * D_, 4096, sbase + B_X + 8 * q);
        tnext += X_GAP;
      }
      #pragma unroll 1
      for (int u = 0; u < 16; u++) {
        const int st = u & 3;
        if (u == 1) PRD_WAIT(X_S1 < 8 ? sbase + B_X + 8 * X_S1 : sbase + B_MOD, 0, dl);
        if (u == 2) { PRD_WAIT(sbase + B_GATE, 0, dl); PROFN(60, lane == 0); }
        if (u == 3) PRD_WAIT(sbase + B_EQ, 0, dl);
        PRD_WAIT(sbase + B_EQ + 8 * st, ((u >> 2) & 1) ^ 1, dl);
        const uint32_t slot = sbase + st * QSLOT, fb = sbase + B_FQ + 8 * st;
        mbar_expect_tx_e(fb, u == 0 ? 65536 : u == 15 ? 32768 : 49152);
        if (u == 0) tma_load_3d(sbase + SM_X0, &maps.x, fb, 0, mb * 64, 0);
        tma_load_4d<(EF & 2) != 0>(slot + 16384, &maps.wqk, fb, 0, u * 64, j, 0);
        tma_load_4d<(EF & 2) != 0>(slot + 32768, &maps.wvv, fb, 0, u * 64, j, 0);
        if (u < 15) tma_load_3d(slot, &maps.x, fb, u * 64 + 64, mb * 64, 0);
      }
      PRD_WAIT(sbase + B_RST, 0, dl);
      mbar_arrive_e(sbase + B_FQ + 24);
      const unsigned e1 = 1 + ld_relaxed(flags + FO_EPOCH);
      Ring r{0, 1, 0, dl};
      uint32_t slot, fb;
      auto acquire = [&](uint32_t bytes) {
        PRD_WAIT(sbase + B_EM + 8 * r.st, r.ph, dl);
        slot = sbase + r.st * MSLOT; fb = sbase + B_FM + 8 * r.st;
        mbar_expect_tx_e(fb, bytes);
        ring_next(r);
      };
      #pragma unroll 1
      for (int kt = 0; kt < 16; kt++) {
        if (kt < 5) PRD_WAIT(sbase + B_EQ + 8 * (kt - (kt >= 2)), 1, dl);
        if ((kt & 7) == 0) { PROF(46, lane == 0 && kt == 8); PRD_WAIT(sbase + B_FLG + kt, 0, dl); PROF(47, lane == 0 && kt == 8); }
        acquire(32768);
        tma_load_4d<(EF & 2) != 0>(slot + 16384, &maps.wq1, fb, (j + 8) * 64, (kt & 1) * 64 + (kt & 6) * 8, (kt >> 3) * 4, 0);
        tma_load_3d(slot, &maps.hh, fb, (kt & 7) * 64, row0, kt >> 3);
      }
      PROF(82, lane == 0);
      PRD_WAIT(sbase + B_FLG + 16, 0, dl);
      PROF(83, lane == 0);
      #pragma unroll 1
      for (int kt = 0; kt < 8; kt++) {
        if (kt == 4) {
          acquire(32768);
          tma_load_3d(slot, &maps.x, fb, j * 128, mb * 64, 0);
          tma_load_3d(slot + 16384, &maps.x, fb, j * 128 + 64, mb * 64, 0);
        }
        acquire(32768);
        tma_load_3d<(EF & 2) != 0>(slot + 16384, &maps.wo, fb, 0, kt * 64, 2 * j);
        tma_load_2d(slot, &maps.o, fb, kt * 64, row0);
      }
      acquire(16384);
      tma_load_3d<(EF & 2) != 0>(slot + 16384, &maps.wo, fb, 0, (8 + j) * 64, 2 * j);
      {
        constexpr int NPRE = WPRE;
        Ring ra = r;
        #pragma unroll 1
        for (int i = 0; i < 7; i++) {
          const int kt = 8 + other_slot(i, j);
          acquire(32768);
          tma_load_3d<(EF & 2) != 0>(slot + 16384, &maps.wo, fb, 0, kt * 64, 2 * j);
          if (i == NPRE - 1) {
            wait_flag(&mail0->flags[FL_O], e1 * NCTA, dl);
            PROFN(61, lane == 0);
            #pragma unroll 1
            for (int q = 0; q < NPRE - 1; q++) { tma_load_2d(sbase + ra.st * MSLOT, &maps.o, sbase + B_FM + 8 * ra.st, (8 + other_slot(q, j)) * 64, row0); ring_next(ra); }
          }
          if (i >= NPRE - 1) tma_load_2d(slot, &maps.o, fb, kt * 64, row0);
        }
      }
      #pragma unroll 1
      for (int t = 0; t < 2; t++) {
        acquire(32768);
        tma_load_2d<(EF & 4) != 0>(slot, &maps.w1, fb, j * 64, (2 * j + t) * 64);
        tma_load_2d<(EF & 4) != 0>(slot + 8192, &maps.w3, fb, j * 64, (2 * j + t) * 64);
        tma_load_2d<(EF & 4) != 0>(slot + 16384, &maps.w1, fb, (8 + j) * 64, (2 * j + t) * 64);
        tma_load_2d<(EF & 4) != 0>(slot + 24576, &maps.w3, fb, (8 + j) * 64, (2 * j + t) * 64);
      }
      {
        Ring ra = r;
        #pragma unroll 1
        for (int i = 0; i < 4; i++) {
          const int kt = 2 * ((~j & 4) + i);
          acquire(32768);
          tma_load_2d<(EF & 4) != 0>(slot + 16384, &maps.w1, fb, j * 64, kt * 64);
          tma_load_2d<(EF & 4) != 0>(slot + 24576, &maps.w3, fb, j * 64, kt * 64);
        }
        wait_flag(&mail0->flags[FL_H2], e1 * NCTA, dl);
        PROFN(62, lane == 0);
        mbar_arrive_e(sbase + B_H2A);
        #pragma unroll 1
        for (int i = 0; i < 4; i++) { tma_load_2d(sbase + ra.st * MSLOT, &maps.h2, sbase + B_FM + 8 * ra.st, ((~j & 4) + i) * 128, row0); ring_next(ra); }
      }
      #pragma unroll 1
      for (int gt = 0; gt < 7; gt++) {
        const int ncol = (8 * gt + j) * 64;
        #pragma unroll 1
        for (int i = (gt == 0 ? 4 : 0); i < (gt < 2 ? 14 : 16); i++) {
          const int kt = gt >= 2 ? i : i < 7 ? 2 * other_slot(i, j) : 2 * other_slot(i - 7, j) + 1;
          if (gt == 0 && i == 7) PRD_WAIT(sbase + B_FLG + 24, 0, dl);
          acquire(32768);
          tma_load_2d<(EF & 4) != 0>(slot + 16384, &maps.w1, fb, ncol, kt * 64);
          tma_load_2d<(EF & 4) != 0>(slot + 24576, &maps.w3, fb, ncol, kt * 64);
          tma_load_2d(slot, &maps.h2, fb, kt * 64, row0);
        }
      }
      #pragma unroll 1
      for (int kt = 0; kt < 56; kt++) {
        if ((kt & 7) == 0) PRD_WAIT(sbase + B_FLG + 32 + kt, 0, dl);
        acquire(32768);
        tma_load_3d<(EF & 8) != 0>(slot + 16384, &maps.w2, fb, 0, kt * 64, 2 * j);
        tma_load_3d<(EF & 16) != 0>(slot, &maps.hh, fb, (kt & 7) * 64, row0, kt >> 3);
      }
    } else {
      const unsigned e1 = 1 + ld_relaxed(wid == 9 ? flags + FO_EPOCH : &mail0->flags[FL_EPOCH]), par = e1 & 1;
      if (wid == 9) {
        SVC_WAIT(sbase + B_GATE, 0, dl);
        #pragma unroll 1
        for (int e = 0; e < 16; e++) st_rlx_v4(mail0->halo + (mb * 16 + j + (e & 8)) * 256 + (e & 7) * 32 + lane, ~0u, ~0u, ~0u, ~0u, true);
        #pragma unroll 1
        for (int e = 0; e < 2; e++) st_rlx_v4(mail0->st2 + ((mb * 8 + e * 4 + (lane >> 3)) * 8 + j) * 8 + (lane & 7), ~0u, ~0u, ~0u, ~0u, true);
        __threadfence();
        red_add_e(&mail0->flags[FL_RESET], 1);
        #pragma unroll 1
        for (int n = 0; n < 12; n++) {
          if (n == 4) {
            mbar_wait(sbase + B_STH, 0, dl);
            tma_store_2d(&maps.h2, sbase + SM_STG, j * 128, row0);
            bulk_commit();
            bulk_wait0();
            red_add_e(&mail0->flags[FL_H2], 1);
            PROF(84, lane == 0);
            mbar_wait(sbase + B_H2A, 0, dl);
          }
          if (n >= ST_SPIN0 && n <= 4) mbar_wait(sbase + B_STREQ, n & 1, dl); else SVC_WAIT(sbase + B_STREQ, n & 1, dl);
          if (n == 2 || n == 3) tma_store_2d(&maps.o, sbase + SM_STG, (j + 8 * (n - 2)) * 64, row0);
          else if (n == 4) tma_store_2d(&maps.h2, sbase + SM_STG + 16384, j * 128 + 64, row0);
          else tma_store_3d(&maps.hh, sbase + SM_STG + (n == 1 ? 16384 : 0), j * 64, row0, n < 2 ? n : n - 5);
          bulk_commit();
          bulk_wait0();
          red_add_e(n == 3 ? &mail0->flags[FL_O] : flags + (n < 2 ? FO_H1 + n : n - 1), 1);
          mbar_arrive_e(sbase + B_STFREE);
          PROFN(70 + n, lane == 0 && n > 0);
        }
      } else {
        mbar_wait(sbase + B_X + 8 * X_POLL, 0, dl);
        const float* const mail = &mail0->mod[(b & 7) * 6 * D_ + lane * 4];
        if (wid == 10) {
          #pragma unroll 1
          for (int p = 0; p < 8; p++) {
            if (p >= 2) TRG_WAIT(p == 2 ? q_empty(0, sbase) : q_empty(2 * p - 5, sbase), p == 2 ? 0 : ((2 * p - 5) >> 2) & 1, dl);
            gather_table(mail + p * 128, sbase + SM_MODT + (p & 3) * 512 + lane * 16, p == 0 ? sbase + B_MOD : sbase + B_FQ + 8 * ((2 * p - 1) & 3), par, dl);
            PROF(63 + p, lane == 0 && p < 7);
          }
          const uint32_t vdst = sbase + SM_VEC + (lane >> 3) * 64 + (lane & 3) * 16 + ((lane >> 2) & 1) * 8;
          #pragma unroll 1
          for (int v = 0; v < 2; v++) {
            SVC_WAIT(sbase + B_FLG + 16 + 16 * v, 0, dl);
            uint4 m[3];
            while (true) {
              #pragma unroll
              for (int e = 0; e < 3; e++) m[e] = ld_rlx_v4(mail + (2 + v + e) * 1024 + j * 128);
              if (poll_done(((bad4(m[0], par) | bad4(m[1], par) | bad4(m[2], par)) & 1) == 0, dl)) break;
              __nanosleep(200);
            }
            #pragma unroll
            for (int e = 0; e < 3; e++) sts64(vdst + (v + e) * 256, hi_halves(m[e].x, m[e].y), hi_halves(m[e].z, m[e].w));
            mbar_arrive_e(sbase + B_VEC + 8 * v);
            PROF(70, lane == 0 && v == 0);
          }
        } else {
          mbar_wait(sbase + B_LN, 0, dl);
          red_add_e(&mail0->flags[FL_LN1], 1);
          wait_flag(&mail0->flags[FL_LN1], e1 * NCTA, dl);
          mbar_arrive_e(sbase + B_GATE);
          PROF(41, lane == 0);
          __nanosleep(2000);
          wait_flag(&mail0->flags[FL_RESET], e1 * NCTA, dl);
          mbar_arrive_e(sbase + B_RST);
          #pragma unroll 1
          for (int i = 0; i < 11; i++) {
            const unsigned* f = flags + (i < 2 ? FO_H1 + i : i == 2 ? FO_O : FO_H2 + i - 3);
            if (i == 3) SVC_WAIT(sbase + B_H2A, 0, dl);
            while (!poll_done((int)(ld_relaxed(f) - e1 * 8) >= 0, dl)) { if (i > 3 || i == 0) __nanosleep(200); }
            mbar_arrive_e(sbase + B_FLG + 8 * i);
          }
        }
      }
    }
  } else {
    const int wg = wid >> 2, warp = wid & 3;
    const int g = lane >> 2, qd = lane & 3;
    bulk_prefetch(wmod + (size_t)(b * 8 + wid) * (6 * D_), PF_BYTES);
    bulk_prefetch(wmod + (size_t)(b * 8 + wid) * (6 * D_) + D_, PF_BYTES);
    bar_sync(0, 384);
    const unsigned e1 = 1 + ld_relaxed(flags + FO_EPOCH), par = e1 & 1;
    reg_alloc<232>();
    PROF(1, tid == 0);
    const uint32_t wgoff = wg * 8192;
    Frag4 frag;
    #pragma unroll
    for (int q = 0; q < 4; q++) frag.o[q] = wid * 2048 + (lane & 15) * 128 + (((2 * q + (lane >> 4)) ^ (lane & 7)) << 4);
    const uint32_t slab = sbase + SM_STG + wid * 2048;

    LnRow ln;
    {
      uint2* const lmail = &mail0->ln1[(mb * 8 + (lane & 1) * 4 + (j >> 1)) * 16 + (j & 1) * 8 + wid];
      st_rlx_v2(lmail, par ^ 1, par ^ 1, lane < 2);
      mbar_wait(sbase + B_X + 8 * wid, 0, dl);
      PROF(3, tid == 224); PROF(93, tid == 0);
      float s[2][2] = {{0.f, 0.f}, {0.f, 0.f}}, q2[2][2] = {{0.f, 0.f}, {0.f, 0.f}};
      #pragma unroll
      for (int c = 0; c < 8; c++) {
        const uint4 v = lds128(sbase + SM_XR + wid * 4096 + c * 512 + lane * 16);
        const uint32_t vv[4] = {v.x, v.y, v.z, v.w};
        #pragma unroll
        for (int e = 0; e < 4; e++) {
          const float lo = bf_lo(vv[e]), hi = bf_hi(vv[e]);
          s[c >> 2][0] += lo; s[c >> 2][1] += hi; q2[c >> 2][0] = fmaf(lo, lo, q2[c >> 2][0]); q2[c >> 2][1] = fmaf(hi, hi, q2[c >> 2][1]);
        }
      }
      const bool odd = lane & 1;
      float sm = (s[0][0] + s[0][1]), so = (s[1][0] + s[1][1]), qm = (q2[0][0] + q2[0][1]), qo = (q2[1][0] + q2[1][1]);
      { const float a = odd ? so : sm, c = odd ? qo : qm;
        sm = a + __shfl_xor_sync(0xffffffffu, odd ? sm : so, 1); qm = c + __shfl_xor_sync(0xffffffffu, odd ? qm : qo, 1); }
      #pragma unroll
      for (int o = 2; o < 32; o <<= 1) { sm += __shfl_xor_sync(0xffffffffu, sm, o); qm += __shfl_xor_sync(0xffffffffu, qm, o); }
      sm *= (1.f / D_);
      st_rlx_v2(lmail, tagf(fast_rsqrt(fmaxf(qm * (1.f / D_) - sm * sm, 0.f) + 1e-5f), par), tagf(sm, par), lane < 2);
      mbar_arrive_e(sbase + B_LN);
      PROF(4, tid == 224);
    }

    uint4* const halo_out = mail0->halo + ((mb * 16 + j) * 2 + wg) * 128 + lane;
    const uint4* const halo_in = halo_out - 16 * 256;
    const uint32_t xch = sbase + SM_XCH + wid * 2048 + lane * 16;
    const bool noprev = mb == 0 && warp == 0;
    float a0[64], a1[64];
    uint32_t x2[32];
    Ring r{zero, 0, 0, dl};
    Frag8 qA, qB, kA, kB, vA, vB, wA, wB;
    {
      float acc[128];
      uint32_t A0[16], A1[16];
      undef_regs(acc);
      const uint32_t tab = sbase + SM_MODT + qd * 16;
      uint4 p[4];
      mbar_wait(sbase + B_LN, 0, dl);
      const uint2* const lin = &mail0->ln1[(mb * 8 + wid) * 16 + g];
      uint2 v0, v1;
      do { v0 = ld_rlx_v2(lin); v1 = ld_rlx_v2(lin + 8); } while (!poll_done(((bad2(v0.x, v0.y, par) | bad2(v1.x, v1.y, par)) & 1) == 0, dl));
      ln_row(ln, 0, __uint_as_float(v0.y), __uint_as_float(v0.x));
      ln_row(ln, 1, __uint_as_float(v1.y), __uint_as_float(v1.x));
      q_wait(0, sbase, dl);
      mbar_wait(sbase + B_MOD, 0, dl);
      #pragma unroll
      for (int kk = 0; kk < 4; kk++) q_load(A0, p, kk, sbase + SM_X0, frag, tab);
      PROF(5, tid == 0);
      const int hq0 = (j & 1) ? 4 : j >> 1, hq1 = (j & 1) ? j >> 1 : 4;
      q_step_rs<true>(acc, A0, A1, p, 0, sbase, frag, tab, ln, hq0, true, dl, wg);
      #pragma unroll 1
      for (int u = 1; u < 15; u += 2) {
        q_step_rs<true>(acc, A1, A0, p, u, sbase, frag, tab, ln, hq1, false, dl, wg);
        if (u == 7) request_store(sbase + B_STREQ);
        q_step_rs<true>(acc, A0, A1, p, u + 1, sbase, frag, tab, ln, hq0, false, dl, wg);
      }
      q_step_rs<false>(acc, A1, A0, p, 15, sbase, frag, tab, ln, hq1, false, dl, wg);
      mbar_wait(sbase + B_STFREE, 0, dl);
      request_store(sbase + B_STREQ);
      wgmma_wait<0>();
      undef_regs(a0);
      { const uint32_t slot = m_wait(sbase, r); mma_step(a0, slot + wgoff, slot + 16384, true, q_empty(15, sbase)); m_next(r); }
      fence_regs(acc);
      PROF(8, tid == 0);
      sched_fence(zero);
      pack_half(vB, acc, 64, 1); transpose8(vB);
      m_step(a0, sbase, wgoff, r);
      sched_fence(zero);
      pack_half(kB, acc, 32, 1);
      attn_send(vB, 1, xch - 16384, warp, halo_out, mb < 15); attn_send(kB, 0, xch - 16384, warp, halo_out, mb < 15);
      m_step(a0, sbase, wgoff, r);
      sched_fence(zero);
      pack_half(qA, acc, 0, 0); pack_half(qB, acc, 0, 1); pack_half(kA, acc, 32, 0); pack_half(wB, acc, 96, 1); pack_half(wA, acc, 96, 0);
      m_step(a0, sbase, wgoff, r);
      sched_fence(zero);
      pack_half(vA, acc, 64, 0); transpose8(vA);
    }
    uint4 wP[2];
    {
      m_step(a0, sbase, wgoff, r);
      uint4 pv[4];
      attn_recv<4>(pv, 0, xch - 16384, wg, warp, halo_in, mb > 0);
      m_step(a0, sbase, wgoff, r);
      mbar_wait(sbase + B_STFREE, 1, dl);
      transpose8(wB);
      m_step(a0, sbase, wgoff, r);
      attn_check<4>(pv, 0, warp, halo_in, dl);
      wgmma_wait<0>();
      PROF(9, tid == 0);
      float o[2][5][4];
      sched_fence(zero);
      attn_core(qA, qB, kA, kB, vA, vB, pv, pv + 2, noprev, lane, o);
      attn_store(o, 0, sbase, frag);
      attn_store(o, 1, sbase, frag);
      request_store(sbase + B_STREQ);
      bar_sync(NB_CONS, 256);
      PROF(10, tid == 0);
      m_step(a0, sbase, wgoff, r);
      sched_fence(zero);
      attn_send(wB, 1, xch, warp, halo_out + 8 * 256, mb < 15);
      m_step(a0, sbase, wgoff, r);
      sched_fence(zero);
      transpose8(wA);
      #pragma unroll 1
      for (int i = 9; i < 15; i++) m_step(a0, sbase, wgoff, r);
      attn_recv<2>(wP, 2, xch, wg, warp, halo_in + 8 * 256, mb > 0);
      m_step(a0, sbase, wgoff, r);
    }
    {
      undef_regs(a1);
      {
        const uint32_t slot = m_wait(sbase, r);
        mma_step(a1, slot + wgoff, slot + 16384, true, m_prev(sbase, r), [&] {
          fence_regs(a0);
          pack_half(kB, a0, 32, 1);
          attn_send(kB, 0, xch, warp, halo_out + 8 * 256, mb < 15);
        });
        m_next(r);
      }
      PROF(14, tid == 0);
      sched_fence(zero);
      pack_half(kA, a0, 32, 0); pack_half(qA, a0, 0, 0); pack_half(qB, a0, 0, 1);
      m_step(a1, sbase, wgoff, r);
      attn_check<2>(wP, 2, warp, halo_in + 8 * 256, dl);
      uint4 kP[2];
      attn_recv<2>(kP, 0, xch, wg, warp, halo_in + 8 * 256, mb > 0);
      m_step(a1, sbase, wgoff, r);
      attn_check<2>(kP, 0, warp, halo_in + 8 * 256, dl);
      wgmma_wait<0>();
      PROF(15, tid == 0);
      float o[2][5][4];
      mbar_wait(sbase + B_STFREE, 0, dl);
      attn_core(qA, qB, kA, kB, wA, wB, kP, wP, noprev, lane, o);
      attn_store(o, 0, sbase, frag);
      attn_store(o, 1, sbase, frag);
      request_store(sbase + B_STREQ);
      bar_sync(NB_CONS, 256);
      PROF(16, tid == 0);
      auto residual = [&] {
        const uint32_t xs = m_wait(sbase, r), xe = sbase + B_EM + 8 * r.st;
        ring_next(r);
        #pragma unroll
        for (int t = 0; t < 2; t++) {
          #pragma unroll
          for (int jj = 4 * t; jj < 4 * t + 4; jj++) ldmatrix_x4(xs + t * 16384 + frag.o[jj & 3], x2[4 * jj], x2[4 * jj + 1], x2[4 * jj + 2], x2[4 * jj + 3]);
          if (t == 1) {
            uint32_t dep = 0;
            #pragma unroll
            for (int jj = 0; jj < 8; jj++) dep |= x2[4 * jj];
            mbar_arrive_e(xe + (dep & zero));
          }
          m_step(a1, sbase, wgoff, r);
        }
      };
      m_step(a1, sbase, wgoff, r);
      residual();
      #pragma unroll 1
      for (int i = 6; i < 8; i++) m_step(a1, sbase, wgoff, r);
      mma_step(a1, sbase + SM_STG + wgoff, m_wait(sbase, r) + 16384, false, m_prev(sbase, r));
      m_next(r);
      PROF(17, tid == 0);
      #pragma unroll 1
      for (int i = 0; i < 7; i++) { m_step(a1, sbase, wgoff, r); PROF(42, tid == 0 && i == 0); }
      PROF(45, tid == 0);
      mbar_wait(sbase + B_VEC, 0, dl);
      mbar_wait(sbase + B_STFREE, 1, dl);
      const uint32_t vec = sbase + SM_VEC + qd * 16;
      uint4 ga[4];
      #pragma unroll
      for (int q = 0; q < 4; q++) ga[q] = lds128(vec + q * 64);
      wgmma_wait<0>();
      mbar_arrive_e(m_prev(sbase, r));
      fence_regs(a1);
      PROF(18, tid == 0);
      float gl[4] = {0.f, 0.f, 0.f, 0.f}, gh[4] = {0.f, 0.f, 0.f, 0.f};
      #pragma unroll
      for (int jj = 0; jj < 8; jj++) {
        uint32_t* v = &x2[4 * jj];
        const uint32_t wl = (jj & 1) ? ga[jj >> 1].z : ga[jj >> 1].x, wh = (jj & 1) ? ga[jj >> 1].w : ga[jj >> 1].y;
        #pragma unroll
        for (int e = 0; e < 4; e++) v[e] = fma_bf2(e & 2 ? wh : wl, pack_bf16(a1[8 * jj + 2 * e], a1[8 * jj + 2 * e + 1]), v[e]);
        mma16(gl, v[0], 0x3F803F80u, v[2], 0x3F803F80u, v[0], v[2]);
        mma16(gh, v[1], 0x3F803F80u, v[3], 0x3F803F80u, v[1], v[3]);
      }
      uint4* const sm = mail0->st2 + (mb * 8 + wid) * 64 + g;
      st_rlx_v4(sm + j * 8, __float_as_uint(g & 1 ? gl[3] : gl[2]), __float_as_uint(g & 1 ? gl[1] : gl[0]),
                __float_as_uint(g & 1 ? gh[3] : gh[2]), __float_as_uint(g & 1 ? gh[1] : gh[0]), qd == (g >> 1));
      float s[2], q2[2];
      PROF(19, tid == 0);
      uint4 sb[4], cb[4];
      #pragma unroll
      for (int q = 0; q < 4; q++) { sb[q] = lds128(vec + 256 + q * 64); cb[q] = lds128(vec + 512 + q * 64); }
      uint4 p0, p1;
      while (true) {
        p0 = ld_rlx_v4(sm + qd * 16); p1 = ld_rlx_v4(sm + qd * 16 + 8);
        if (poll_done(max(max(max(p0.x, p0.y), max(p0.z, p0.w)), max(max(p1.x, p1.y), max(p1.z, p1.w))) != ~0u, dl)) break;
      }
      PROF(20, tid == 0);
      s[0] = __uint_as_float(p0.x) + __uint_as_float(p1.x); q2[0] = __uint_as_float(p0.y) + __uint_as_float(p1.y);
      s[1] = __uint_as_float(p0.z) + __uint_as_float(p1.z); q2[1] = __uint_as_float(p0.w) + __uint_as_float(p1.w);
      #pragma unroll
      for (int o2 = 1; o2 <= 2; o2 <<= 1)
        #pragma unroll
        for (int h = 0; h < 2; h++) { s[h] += __shfl_xor_sync(0xffffffffu, s[h], o2); q2[h] += __shfl_xor_sync(0xffffffffu, q2[h], o2); }
      #pragma unroll
      for (int h = 0; h < 2; h++) {
        const float m = s[h] * (1.f / D_);
        ln_row(ln, h, m, fast_rsqrt(fmaxf(q2[h] * (1.f / D_) - m * m, 0.f) + 1e-5f));
      }
      #pragma unroll
      for (int jj = 0; jj < 8; jj++) {
        const uint32_t cl = (jj & 1) ? cb[jj >> 1].z : cb[jj >> 1].x, ch = (jj & 1) ? cb[jj >> 1].w : cb[jj >> 1].y;
        const uint32_t sl = (jj & 1) ? sb[jj >> 1].z : sb[jj >> 1].x, sh = (jj & 1) ? sb[jj >> 1].w : sb[jj >> 1].y;
        stmatrix_x4(sbase + SM_STG + (jj >> 2) * 16384 + frag.o[jj & 3], ln_mod(x2[4 * jj], ln, 0, cl, sl), ln_mod(x2[4 * jj + 1], ln, 1, cl, sl),
                    ln_mod(x2[4 * jj + 2], ln, 0, ch, sh), ln_mod(x2[4 * jj + 3], ln, 1, ch, sh));
        if (jj == 3) { request_store(sbase + B_STH); sched_fence(zero); }
      }
      request_store(sbase + B_STREQ);
      bar_sync(NB_WG + wg, 128);
      PROF(21, tid == 0);
    }

    undef_regs(a0);
    #pragma unroll
    for (int t = 0; t < 2; t++) {
      const uint32_t slot = m_wait(sbase, r);
      if (t == 0) mma_step<false>(a0, sbase + SM_STG + wgoff, slot, true, 0);
      else mma_step(a0, sbase + SM_STG + 16384 + wgoff, slot, false, m_prev(sbase, r));
      mma_step<false>(a1, sbase + SM_STG + t * 16384 + wgoff, slot + 16384, t == 0, 0);
      m_next(r);
    }
    PROF(22, tid == 0);
    #pragma unroll 1
    for (int t = 0; t < 7; t += 2) {
      g_switch(a1, a0, t == 0 ? 14 : 11, t > 0, 5 + t, sbase, wgoff, frag, r);
      if (t == 6) break;
      g_switch(a0, a1, t == 0 ? 9 : 11, true, 6 + t, sbase, wgoff, frag, r);
    }
    #pragma unroll 1
    for (int i = 5; i < 56 - DTAIL; i++) m_step(a1, sbase, wgoff, r);
    if (DTAIL) {
      if (wg == 1) { wgmma_wait<0>(); mbar_arrive_e(m_prev(sbase, r)); bar_sync(NB_ORD, 256); }
      #pragma unroll
      for (int i = 0; i < DTAIL; i++) {
        const uint32_t slot = m_wait(sbase, r);
        const uint32_t alo = ((slot + wgoff) >> 4) + (1u << 16), blo = ((slot + 16384) >> 4) + (512u << 16);
        wgmma_fence();
        #pragma unroll
        for (int k = 0; k < 4; k++) wgmma_m64n128k16_ss(a1, desc_from_lo(alo + k * 2), desc_from_lo(blo + k * 128), true);
        wgmma_commit();
        ring_next(r);
      }
      if (wg == 0) bar_arrive(NB_ORD, 256);
    }
    {
      mbar_wait(sbase + B_STFREE, 1, dl);
      mbar_wait(sbase + B_VEC + 8, 0, dl);
      uint4 gb[4];
      #pragma unroll
      for (int q = 0; q < 4; q++) gb[q] = lds128(sbase + SM_VEC + 768 + qd * 16 + q * 64);
      wgmma_wait<0>();
      fence_regs(a1);
      PROF(50, tid == 128);
      #pragma unroll
      for (int t = 0; t < 2; t++) {
        #pragma unroll
        for (int jj = 4 * t; jj < 4 * t + 4; jj++) {
          const uint32_t gl = (jj & 1) ? gb[jj >> 1].z : gb[jj >> 1].x, gh = (jj & 1) ? gb[jj >> 1].w : gb[jj >> 1].y;
          const int i = 8 * jj;
          stmatrix_x4(sbase + SM_STG + t * 16384 + frag.o[jj & 3],
                      fma_bf2(gl, pack_bf16(a1[i], a1[i + 1]), x2[4 * jj]), fma_bf2(gl, pack_bf16(a1[i + 2], a1[i + 3]), x2[4 * jj + 1]),
                      fma_bf2(gh, pack_bf16(a1[i + 4], a1[i + 5]), x2[4 * jj + 2]), fma_bf2(gh, pack_bf16(a1[i + 6], a1[i + 7]), x2[4 * jj + 3]));
        }
        fence_proxy_async_smem();
        tma_store_3d(&maps.out, slab + t * 16384, j * 128 + t * 64, mb * 64 + warp * 16, wg);
      }
      bulk_commit();
      st_rlx(tid == 0 ? flags + FO_EPOCH : &mail0->flags[FL_EPOCH], e1, j == 0 && (tid == 0 || (tid == 1 && mb == 0)));
      bulk_wait_read0();
      PROFN(51, tid == 128);
    }
  }
}

typedef CUresult (*PFN_encodeTiled)(CUtensorMap*, CUtensorMapDataType, cuuint32_t, void*, const cuuint64_t*, const cuuint64_t*,
                                    const cuuint32_t*, const cuuint32_t*, CUtensorMapInterleave, CUtensorMapSwizzle,
                                    CUtensorMapL2promotion, CUtensorMapFloatOOBfill);

void encode(PFN_encodeTiled fn, CUtensorMap* m, const void* ptr, int rank, const cuuint64_t* dims, const cuuint64_t* strides,
            const cuuint32_t* box) {
  const cuuint32_t es[5] = {1, 1, 1, 1, 1};
  fn(m, CU_TENSOR_MAP_DATA_TYPE_BFLOAT16, rank, const_cast<void*>(ptr), dims, strides, box, es, CU_TENSOR_MAP_INTERLEAVE_NONE,
     CU_TENSOR_MAP_SWIZZLE_128B, CU_TENSOR_MAP_L2_PROMOTION_L2_256B, CU_TENSOR_MAP_FLOAT_OOB_FILL_NONE);
}
void map2d(PFN_encodeTiled fn, CUtensorMap* m, const void* ptr, int cols, int rows, int boxrows) {
  const cuuint64_t dims[2] = {(cuuint64_t)cols, (cuuint64_t)rows}, strides[1] = {(cuuint64_t)cols * 2};
  const cuuint32_t box[2] = {64, (cuuint32_t)boxrows};
  encode(fn, m, ptr, 2, dims, strides, box);
}
void map_w2chunk(PFN_encodeTiled fn, CUtensorMap* m, const void* ptr, int cols, int rows) {
  const cuuint64_t dims[3] = {64, (cuuint64_t)rows, (cuuint64_t)cols / 64}, strides[2] = {(cuuint64_t)cols * 2, 128};
  const cuuint32_t box[3] = {64, 64, 2};
  encode(fn, m, ptr, 3, dims, strides, box);
}
void map_parity(PFN_encodeTiled fn, CUtensorMap* m, const void* ptr, int boxpairs, int boxpar) {
  const cuuint64_t dims[3] = {D_, S_ / 2, 2}, strides[2] = {D_ * 4, D_ * 2};
  const cuuint32_t box[3] = {64, (cuuint32_t)boxpairs, (cuuint32_t)boxpar};
  encode(fn, m, ptr, 3, dims, strides, box);
}

}

extern "C" void kernel_launch(void* const* d_in, const int* in_sizes, int n_in, void* d_out, int out_size) {
  (void)in_sizes; (void)n_in; (void)out_size;
  const bf16* x = (const bf16*)d_in[0];
  const bf16* wqkv = (const bf16*)d_in[1];
  const bf16* wo = (const bf16*)d_in[2];
  const bf16* w1 = (const bf16*)d_in[4];
  const bf16* w3 = (const bf16*)d_in[5];
  const bf16* w2 = (const bf16*)d_in[6];
  const bf16* cvec = (const bf16*)d_in[7];
  const bf16* w_mod = (const bf16*)d_in[8];

  static PFN_encodeTiled fn = nullptr;
  static Maps maps;
  static const void* cached[8] = {};
  static int sms = 0;
  static void* mail = nullptr;
  if (!fn) {
    void* p = nullptr; cudaDriverEntryPointQueryResult st;
    cudaGetDriverEntryPoint("cuTensorMapEncodeTiled", &p, cudaEnableDefault, &st);
    fn = (PFN_encodeTiled)p;
    cudaFuncSetAttribute(fused_block_kernel<0>, cudaFuncAttributeMaxDynamicSharedMemorySize, SM_TOTAL + SM_PROF);
    cudaFuncSetAttribute(fused_block_kernel<1>, cudaFuncAttributeMaxDynamicSharedMemorySize, SM_TOTAL + SM_PROF);
    cudaFuncSetAttribute(fused_block_kernel<2>, cudaFuncAttributeMaxDynamicSharedMemorySize, SM_TOTAL + SM_PROF);
    cudaGetSymbolAddress(&mail, g_mail);
    int dev = 0;
    cudaGetDevice(&dev);
    cudaDeviceGetAttribute(&sms, cudaDevAttrMultiProcessorCount, dev);
  }
  const void* cur[8] = {x, wqkv, wo, w1, w3, w2, d_out, w_mod};
  bool same = true;
  for (int i = 0; i < 8; i++) same = same && cached[i] == cur[i];
  if (!same) {
    void *o, *h2, *hh;
    cudaGetSymbolAddress(&hh, g_hh); cudaGetSymbolAddress(&o, g_o);
    h2 = o;
    map_parity(fn, &maps.x, x, 64, 2); map_parity(fn, &maps.out, d_out, 16, 1);
    map2d(fn, &maps.o, o, D_, S_, 128); map2d(fn, &maps.h2, h2, D_, S_, 128);
    {
      const cuuint64_t dims[3] = {512, (cuuint64_t)S_, 7}, strides[2] = {1024, (cuuint64_t)S_ * 1024};
      const cuuint32_t box[3] = {64, 128, 1};
      encode(fn, &maps.hh, hh, 3, dims, strides, box);
    }
    {
      const cuuint64_t dims[4] = {64, 1024, 16, 2}, strides[3] = {3072 * 2, 128, 2048};
      const cuuint64_t dimv[4] = {64, 1024, 8, 2}, stridev[3] = {3072 * 2, 128, 1024};
      const cuuint32_t box[4] = {64, 64, 1, 2};
      encode(fn, &maps.wqk, wqkv, 4, dims, strides, box);
      encode(fn, &maps.wvv, wqkv + 2048, 4, dimv, stridev, box);
      const cuuint64_t dim1[4] = {1024, 128, 8, 2}, stride1[3] = {3072 * 2, 128 * 3072 * 2, 2048};
      const cuuint32_t box1[4] = {64, 16, 4, 2};
      encode(fn, &maps.wq1, wqkv, 4, dim1, stride1, box1);
    }
    map_w2chunk(fn, &maps.wo, wo, D_, D_); map_w2chunk(fn, &maps.w2, w2, D_, F_);
    map2d(fn, &maps.w1, w1, F_, D_, 64); map2d(fn, &maps.w3, w3, F_, D_, 64);
    map2d(fn, &maps.wmod, w_mod, 6 * D_, D_, 256);
    for (int i = 0; i < 8; i++) cached[i] = cur[i];
  }
  if (sms == NCTA + NAUX) {
    fused_block_kernel<0><<<NCTA + NAUX, 384, SM_TOTAL + SM_PROF>>>(x, cvec, w_mod, (Mail*)mail, 0, maps);
  } else {
    fused_block_kernel<1><<<NAUX, 384, SM_TOTAL + SM_PROF>>>(x, cvec, w_mod, (Mail*)mail, 0, maps);
    fused_block_kernel<2><<<NCTA, 384, SM_TOTAL + SM_PROF>>>(x, cvec, w_mod, (Mail*)mail, 0, maps);
  }
}
```

```cpp
#include <cuda.h>
#include <cuda_runtime.h>
#include <cuda_bf16.h>
#include <stdint.h>

namespace {

typedef __nv_bfloat16 bf16;

constexpr int S_ = 2048, D_ = 1024, F_ = 3584;
constexpr int NCTA = 128, NAUX = 4;

__device__ __align__(1024) bf16 g_o[S_ * D_];
__device__ __align__(1024) bf16 g_hh[S_ * F_];
constexpr int FO_EPOCH = 0, FO_O = 1, FO_H2 = 3, FO_H1 = 11;
constexpr int FL_EPOCH = 16 * 32, FL_LN1 = FL_EPOCH + 2, FL_H2 = FL_EPOCH + 3, FL_O = FL_EPOCH + 4;
struct Mail {
  unsigned flags[32 * 32];
  float mod[8 * 6 * D_];
  uint2 ln1[16 * 8 * 16];
  uint4 halo[2][16 * 16 * 2 * 4 * 32];
  uint4 st2[2][16 * 8 * 8 * 8];
};
__device__ __align__(1024) Mail g_mail;

template <int mode>
__device__ __forceinline__ int cta_role() {
  if (mode) return mode == 1 ? NCTA + (blockIdx.x & 3) : blockIdx.x & 127;
  uint32_t sm;
  asm("mov.u32 %0, %%smid;" : "=r"(sm));
  sm = (sm & ~3u) == 12 ? sm + 108 : (sm & ~3u) == 120 ? sm - 108 : sm;
  const int t = sm >> 1;
  int r;
  if (t < 32) r = (t & 7) * 16 + (t >> 3) * 2 + (sm & 1);
  else if (t < 60) r = (1 + (t - 32) % 7) * 16 + 8 + ((t - 32) / 7) * 2 + (sm & 1);
  else if (t < 62) r = NCTA + sm - 120;
  else r = sm - 116;
  return r;
}
#define PROF(slot, on) do {} while (0)
#define PROFN(slot, on) do {} while (0)
#define PROF_OUT(role, t) do {} while (0)
constexpr uint32_t SM_PROF = 0;

__device__ __forceinline__ uint32_t smem_u32(const void* p) { return (uint32_t)__cvta_generic_to_shared(p); }
#define ELECT "{\n.reg .pred p;\nelect.sync _|p, 0xffffffff;\n@p "
__device__ __forceinline__ void mbar_init_e(uint32_t bar, uint32_t count) {
  asm volatile(ELECT "mbarrier.init.shared::cta.b64 [%0], %1;\n}" :: "r"(bar), "r"(count) : "memory");
}
__device__ __forceinline__ void mbar_expect_tx_e(uint32_t bar, uint32_t bytes) {
  asm volatile(ELECT "mbarrier.arrive.expect_tx.shared::cta.b64 _, [%0], %1;\n}" :: "r"(bar), "r"(bytes) : "memory");
}
__device__ __forceinline__ void mbar_arrive_e(uint32_t bar) {
  asm volatile(ELECT "mbarrier.arrive.shared::cta.b64 _, [%0];\n}" :: "r"(bar) : "memory");
}
__device__ __forceinline__ uint32_t clock32() { uint32_t t; asm volatile("mov.u32 %0, %%clock;" : "=r"(t)); return t; }
__device__ __forceinline__ void mbar_wait(uint32_t bar, uint32_t parity, uint32_t dl) {
  asm volatile("{\n.reg .pred p, q;\n.reg .b32 t;\n"
               "mbarrier.try_wait.parity.shared::cta.b64 p, [%0], %1;\n"
               "@p bra LAB_DONE;\n"
               "LAB_WAIT:\n"
               "mbarrier.try_wait.parity.shared::cta.b64 p, [%0], %1;\n"
               "mov.u32 t, %%clock;\n"
               "sub.s32 t, t, %2;\n"
               "setp.lt.and.s32 q, t, 0, !p;\n"
               "@q bra LAB_WAIT;\n"
               "LAB_DONE:\n}" :: "r"(bar), "r"(parity), "r"(dl) : "memory");
}
__device__ __forceinline__ void mbar_sleep(uint32_t bar, uint32_t parity, uint32_t dl) {
  asm volatile("{\n.reg .pred p;\n.reg .b32 t;\n"
               "LAB_WAIT:\n"
               "mbarrier.try_wait.parity.shared::cta.b64 p, [%0], %1, 20000;\n"
               "@p bra LAB_DONE;\n"
               "mov.u32 t, %%clock;\n"
               "sub.s32 t, t, %2;\n"
               "setp.lt.s32 p, t, 0;\n"
               "@p bra LAB_WAIT;\n"
               "LAB_DONE:\n}" :: "r"(bar), "r"(parity), "r"(dl) : "memory");
}
__device__ __forceinline__ bool poll_done(bool ok, uint32_t dl) {
  return __all_sync(0xffffffffu, ok || (int)(clock32() - dl) >= 0);
}
__device__ __forceinline__ unsigned ld_relaxed(const unsigned* p) {
  unsigned v; asm volatile("ld.relaxed.gpu.global.u32 %0, [%1];" : "=r"(v) : "l"(p) : "memory"); return v;
}
__device__ __forceinline__ void red_add_e(unsigned* p, unsigned v) {
  asm volatile(ELECT "red.relaxed.gpu.global.add.u32 [%0], %1;\n}" :: "l"(p), "r"(v) : "memory");
}
__device__ __forceinline__ void wait_flag(const unsigned* p, unsigned target, uint32_t dl) {
  asm volatile("{\n.reg .pred p;\n.reg .b32 t;\n"
               "LAB_WAIT:\n"
               "ld.relaxed.gpu.global.u32 t, [%0];\n"
               "sub.s32 t, t, %1;\n"
               "setp.ge.s32 p, t, 0;\n"
               "@p bra LAB_DONE;\n"
               "mov.u32 t, %%clock;\n"
               "sub.s32 t, t, %2;\n"
               "setp.lt.s32 p, t, 0;\n"
               "@p bra LAB_WAIT;\n"
               "LAB_DONE:\n}" :: "l"(p), "r"(target), "r"(dl) : "memory");
}
__device__ __forceinline__ void wait_until(uint32_t t) { while ((int)(clock32() - t) < 0) {} }
__device__ __forceinline__ void fence_proxy_async_smem() { asm volatile("fence.proxy.async.shared::cta;" ::: "memory"); }

constexpr uint64_t EVICT_FIRST = 0x12F0000000000000ull;
template <bool STREAM = false>
__device__ __forceinline__ void tma_load_2d(uint32_t dst, const CUtensorMap* m, uint32_t bar, int c0, int c1) {
  if (STREAM)
    asm volatile(ELECT "cp.async.bulk.tensor.2d.shared::cluster.global.mbarrier::complete_tx::bytes.L2::cache_hint [%0], [%1, {%3, %4}], [%2], %5;\n}"
                 :: "r"(dst), "l"(m), "r"(bar), "r"(c0), "r"(c1), "l"(EVICT_FIRST) : "memory");
  else
    asm volatile(ELECT "cp.async.bulk.tensor.2d.shared::cluster.global.mbarrier::complete_tx::bytes [%0], [%1, {%3, %4}], [%2];\n}"
                 :: "r"(dst), "l"(m), "r"(bar), "r"(c0), "r"(c1) : "memory");
}
template <bool STREAM = false>
__device__ __forceinline__ void tma_load_3d(uint32_t dst, const CUtensorMap* m, uint32_t bar, int c0, int c1, int c2) {
  if (STREAM)
    asm volatile(ELECT "cp.async.bulk.tensor.3d.shared::cluster.global.mbarrier::complete_tx::bytes.L2::cache_hint [%0], [%1, {%3, %4, %5}], [%2], %6;\n}"
                 :: "r"(dst), "l"(m), "r"(bar), "r"(c0), "r"(c1), "r"(c2), "l"(EVICT_FIRST) : "memory");
  else
    asm volatile(ELECT "cp.async.bulk.tensor.3d.shared::cluster.global.mbarrier::complete_tx::bytes [%0], [%1, {%3, %4, %5}], [%2];\n}"
                 :: "r"(dst), "l"(m), "r"(bar), "r"(c0), "r"(c1), "r"(c2) : "memory");
}
template <bool STREAM = false>
__device__ __forceinline__ void tma_load_4d(uint32_t dst, const CUtensorMap* m, uint32_t bar, int c0, int c1, int c2, int c3) {
  if (STREAM)
    asm volatile(ELECT "cp.async.bulk.tensor.4d.shared::cluster.global.mbarrier::complete_tx::bytes.L2::cache_hint [%0], [%1, {%3, %4, %5, %6}], [%2], %7;\n}"
                 :: "r"(dst), "l"(m), "r"(bar), "r"(c0), "r"(c1), "r"(c2), "r"(c3), "l"(EVICT_FIRST) : "memory");
  else
    asm volatile(ELECT "cp.async.bulk.tensor.4d.shared::cluster.global.mbarrier::complete_tx::bytes [%0], [%1, {%3, %4, %5, %6}], [%2];\n}"
                 :: "r"(dst), "l"(m), "r"(bar), "r"(c0), "r"(c1), "r"(c2), "r"(c3) : "memory");
}
__device__ __forceinline__ void tma_store_2d(const CUtensorMap* m, uint32_t src, int c0, int c1) {
  asm volatile(ELECT "cp.async.bulk.tensor.2d.global.shared::cta.bulk_group [%0, {%2, %3}], [%1];\n}"
               :: "l"(m), "r"(src), "r"(c0), "r"(c1) : "memory");
}
__device__ __forceinline__ void tma_store_3d(const CUtensorMap* m, uint32_t src, int c0, int c1, int c2) {
  asm volatile(ELECT "cp.async.bulk.tensor.3d.global.shared::cta.bulk_group [%0, {%2, %3, %4}], [%1];\n}"
               :: "l"(m), "r"(src), "r"(c0), "r"(c1), "r"(c2) : "memory");
}
__device__ __forceinline__ void bulk_load(uint32_t dst, const void* src, uint32_t bytes, uint32_t bar) {
  asm volatile(ELECT "cp.async.bulk.shared::cluster.global.mbarrier::complete_tx::bytes [%0], [%1], %2, [%3];\n}"
               :: "r"(dst), "l"(src), "r"(bytes), "r"(bar) : "memory");
}
__device__ __forceinline__ void bulk_prefetch(const void* src, uint32_t bytes) {
  asm volatile(ELECT "cp.async.bulk.prefetch.L2.global [%0], %1;\n}" :: "l"(src), "r"(bytes) : "memory");
}
__device__ __forceinline__ void bulk_commit() { asm volatile("cp.async.bulk.commit_group;" ::: "memory"); }
__device__ __forceinline__ void bulk_wait0() { asm volatile("cp.async.bulk.wait_group 0;" ::: "memory"); }
__device__ __forceinline__ void bulk_wait_read0() { asm volatile("cp.async.bulk.wait_group.read 0;" ::: "memory"); }
__device__ __forceinline__ void prefetch_tmap(const CUtensorMap* m) { asm volatile(ELECT "prefetch.tensormap [%0];\n}" :: "l"(m) : "memory"); }
__device__ __forceinline__ void wgmma_fence() { asm volatile("wgmma.fence.sync.aligned;" ::: "memory"); }
__device__ __forceinline__ void wgmma_commit() { asm volatile("wgmma.commit_group.sync.aligned;" ::: "memory"); }
template <int N> __device__ __forceinline__ void wgmma_wait() { asm volatile("wgmma.wait_group.sync.aligned %0;" :: "n"(N) : "memory"); }
template <int R> __device__ __forceinline__ void reg_alloc() { asm volatile("setmaxnreg.inc.sync.aligned.u32 %0;" :: "n"(R)); }
template <int R> __device__ __forceinline__ void reg_dealloc() { asm volatile("setmaxnreg.dec.sync.aligned.u32 %0;" :: "n"(R)); }
__device__ __forceinline__ void bar_sync(int id, int n) { asm volatile("bar.sync %0, %1;" :: "r"(id), "r"(n) : "memory"); }
__device__ __forceinline__ void bar_arrive(int id, int n) { asm volatile("bar.arrive %0, %1;" :: "r"(id), "r"(n) : "memory"); }
__device__ __forceinline__ void sched_fence(int zero) {
  asm volatile("{\n.reg .pred p;\n.reg .b32 t;\nsetp.eq.s32 p, %0, 0;\n@p bra.uni LAB_S;\n"
               "LAB_F:\nmov.u32 t, %%clock;\nsetp.eq.u32 p, t, 0;\n@p bra LAB_F;\nLAB_S:\n}" :: "r"(zero) : "memory");
}
template <int N> __device__ __forceinline__ void fence_regs(float (&a)[N]) {
  #pragma unroll
  for (int i = 0; i < N; i++) asm volatile("" : "+f"(a[i]) :: "memory");
}
template <int N> __device__ __forceinline__ void undef_regs(float (&a)[N]) {
  #pragma unroll
  for (int i = 0; i < N; i++) asm volatile("" : "=f"(a[i]));
}

__device__ __forceinline__ uint64_t desc_from_lo(uint32_t lo) { return (uint64_t)lo | ((uint64_t)0x40000040u << 32); }
__device__ __forceinline__ uint32_t pack_bf16(float lo, float hi) {
  uint32_t r; asm("cvt.rn.bf16x2.f32 %0, %1, %2;" : "=r"(r) : "f"(hi), "f"(lo)); return r;
}
__device__ __forceinline__ uint32_t fma_bf2(uint32_t a, uint32_t b, uint32_t c) {
  uint32_t d; asm("fma.rn.bf16x2 %0, %1, %2, %3;" : "=r"(d) : "r"(a), "r"(b), "r"(c)); return d;
}
__device__ __forceinline__ float bf_lo(uint32_t v) { return __uint_as_float(v << 16); }
__device__ __forceinline__ float bf_hi(uint32_t v) { return __uint_as_float(v & 0xFFFF0000u); }
__device__ __forceinline__ float bf16_round(float x) { return bf_lo(pack_bf16(x, 0.f)); }
__device__ __forceinline__ void stmatrix_x4(uint32_t addr, uint32_t r0, uint32_t r1, uint32_t r2, uint32_t r3) {
  asm volatile("stmatrix.sync.aligned.m8n8.x4.shared.b16 [%0], {%1, %2, %3, %4};" :: "r"(addr), "r"(r0), "r"(r1), "r"(r2), "r"(r3) : "memory");
}
__device__ __forceinline__ void stmatrix_x4_t(uint32_t addr, uint32_t r0, uint32_t r1, uint32_t r2, uint32_t r3) {
  asm volatile("stmatrix.sync.aligned.m8n8.x4.trans.shared.b16 [%0], {%1, %2, %3, %4};" :: "r"(addr), "r"(r0), "r"(r1), "r"(r2), "r"(r3) : "memory");
}
__device__ __forceinline__ void stmatrix_x4_if(uint32_t addr, uint32_t r0, uint32_t r1, uint32_t r2, uint32_t r3, bool on) {
  asm volatile("{\n.reg .pred p;\nsetp.ne.b32 p, %5, 0;\n@p stmatrix.sync.aligned.m8n8.x4.shared.b16 [%0], {%1, %2, %3, %4};\n}"
               :: "r"(addr), "r"(r0), "r"(r1), "r"(r2), "r"(r3), "r"((int)on) : "memory");
}
__device__ __forceinline__ void ldmatrix_x4(uint32_t addr, uint32_t& r0, uint32_t& r1, uint32_t& r2, uint32_t& r3) {
  asm volatile("ldmatrix.sync.aligned.m8n8.x4.shared.b16 {%0, %1, %2, %3}, [%4];" : "=r"(r0), "=r"(r1), "=r"(r2), "=r"(r3) : "r"(addr) : "memory");
}
__device__ __forceinline__ void ldmatrix_x4_t(uint32_t addr, uint32_t (&r)[4]) {
  asm volatile("ldmatrix.sync.aligned.m8n8.x4.trans.shared.b16 {%0, %1, %2, %3}, [%4];" : "=r"(r[0]), "=r"(r[1]), "=r"(r[2]), "=r"(r[3]) : "r"(addr) : "memory");
}
__device__ __forceinline__ uint32_t tagf(float v, unsigned par) { return (__float_as_uint(v) & ~1u) | par; }
__device__ __forceinline__ void st_rlx(void* p, uint32_t a, bool on) {
  asm volatile("{\n.reg .pred p;\nsetp.ne.b32 p, %2, 0;\n@p st.relaxed.gpu.global.u32 [%0], %1;\n}" :: "l"(p), "r"(a), "r"((int)on) : "memory");
}
__device__ __forceinline__ void st_rlx_v2(void* p, uint32_t a, uint32_t b, bool on) {
  asm volatile("{\n.reg .pred p;\nsetp.ne.b32 p, %3, 0;\n@p st.relaxed.gpu.global.v2.u32 [%0], {%1, %2};\n}" :: "l"(p), "r"(a), "r"(b), "r"((int)on) : "memory");
}
__device__ __forceinline__ uint2 ld_rlx_v2(const void* p) {
  uint2 v; asm volatile("ld.relaxed.gpu.global.v2.u32 {%0,%1}, [%2];" : "=r"(v.x), "=r"(v.y) : "l"(p) : "memory"); return v;
}
__device__ __forceinline__ void st_rlx_v4(void* p, uint32_t a, uint32_t b, uint32_t c, uint32_t d, bool on) {
  asm volatile("{\n.reg .pred p;\nsetp.ne.b32 p, %5, 0;\n@p st.relaxed.gpu.global.v4.u32 [%0], {%1, %2, %3, %4};\n}"
               :: "l"(p), "r"(a), "r"(b), "r"(c), "r"(d), "r"((int)on) : "memory");
}
__device__ __forceinline__ void st_nonzero_v4(void* p, uint32_t a, uint32_t b, uint32_t c, uint32_t d, bool on) {
  st_rlx_v4(p, max(a, 1u), max(b, 1u), max(c, 1u), max(d, 1u), on);
}
__device__ __forceinline__ uint32_t min4(const uint4& v) { return min(min(v.x, v.y), min(v.z, v.w)); }
__device__ __forceinline__ uint4 ld_rlx_v4(const void* p) {
  uint4 v; asm volatile("ld.relaxed.gpu.global.v4.u32 {%0,%1,%2,%3}, [%4];" : "=r"(v.x), "=r"(v.y), "=r"(v.z), "=r"(v.w) : "l"(p) : "memory"); return v;
}
__device__ __forceinline__ uint32_t movmatrix_t(uint32_t a) {
  uint32_t d; asm volatile("movmatrix.sync.aligned.m8n8.trans.b16 %0, %1;" : "=r"(d) : "r"(a)); return d;
}
__device__ __forceinline__ void mma16(float (&c)[4], uint32_t a0, uint32_t a1, uint32_t a2, uint32_t a3, uint32_t b0, uint32_t b1) {
  asm volatile("mma.sync.aligned.m16n8k16.row.col.f32.bf16.bf16.f32 {%0,%1,%2,%3}, {%4,%5,%6,%7}, {%8,%9}, {%0,%1,%2,%3};"
               : "+f"(c[0]), "+f"(c[1]), "+f"(c[2]), "+f"(c[3]) : "r"(a0), "r"(a1), "r"(a2), "r"(a3), "r"(b0), "r"(b1));
}
__device__ __forceinline__ void sts128(uint32_t addr, uint32_t a, uint32_t b, uint32_t c, uint32_t d) {
  asm volatile("st.shared.v4.b32 [%0], {%1,%2,%3,%4};" :: "r"(addr), "r"(a), "r"(b), "r"(c), "r"(d) : "memory");
}
__device__ __forceinline__ uint4 lds128(uint32_t addr) {
  uint4 v; asm volatile("ld.shared.v4.b32 {%0,%1,%2,%3}, [%4];" : "=r"(v.x), "=r"(v.y), "=r"(v.z), "=r"(v.w) : "r"(addr) : "memory"); return v;
}
__device__ __forceinline__ uint32_t lds32(uint32_t addr) {
  uint32_t v; asm volatile("ld.shared.b32 %0, [%1];" : "=r"(v) : "r"(addr) : "memory"); return v;
}
__device__ __forceinline__ float2 lds64f(uint32_t addr) {
  float2 v; asm volatile("ld.shared.v2.f32 {%0,%1}, [%2];" : "=f"(v.x), "=f"(v.y) : "r"(addr) : "memory"); return v;
}
__device__ __forceinline__ void sts64(uint32_t addr, uint32_t a, uint32_t b) {
  asm volatile("st.shared.v2.b32 [%0], {%1, %2};" :: "r"(addr), "r"(a), "r"(b) : "memory");
}
__device__ __forceinline__ float fast_ex2(float x) { float y; asm("ex2.approx.ftz.f32 %0, %1;" : "=f"(y) : "f"(x)); return y; }
__device__ __forceinline__ float fast_rcp(float x) { float y; asm("rcp.approx.ftz.f32 %0, %1;" : "=f"(y) : "f"(x)); return y; }
__device__ __forceinline__ float fast_rsqrt(float x) { float y; asm("rsqrt.approx.ftz.f32 %0, %1;" : "=f"(y) : "f"(x)); return y; }
__device__ __forceinline__ float silu_f(float g) { return g * fast_rcp(1.f + fast_ex2(g * -1.4426950408889634f)); }
__device__ __forceinline__ float swiglu(float g, float u) {
  const float h = 0.5f * g;
  float t; asm("tanh.approx.f32 %0, %1;" : "=f"(t) : "f"(h));
  return fmaf(h, t, h) * u;
}

__device__ __forceinline__ void wgmma_m64n128k16_ss(float (&d)[64], uint64_t descA, uint64_t descB, int scaleD) {
  asm volatile("{\n.reg .pred p;\nsetp.ne.b32 p, %66, 0;\n"
    "wgmma.mma_async.sync.aligned.m64n128k16.f32.bf16.bf16 "
    "{%0, %1, %2, %3, %4, %5, %6, %7, %8, %9, %10, %11, %12, %13, %14, %15, "
    "%16, %17, %18, %19, %20, %21, %22, %23, %24, %25, %26, %27, %28, %29, %30, %31, "
    "%32, %33, %34, %35, %36, %37, %38, %39, %40, %41, %42, %43, %44, %45, %46, %47, "
    "%48, %49, %50, %51, %52, %53, %54, %55, %56, %57, %58, %59, %60, %61, %62, %63}, "
    "%64, %65, p, 1, 1, 0, 1;\n}\n"
    : "+f"(d[0]), "+f"(d[1]), "+f"(d[2]), "+f"(d[3]), "+f"(d[4]), "+f"(d[5]), "+f"(d[6]), "+f"(d[7]),
      "+f"(d[8]), "+f"(d[9]), "+f"(d[10]), "+f"(d[11]), "+f"(d[12]), "+f"(d[13]), "+f"(d[14]), "+f"(d[15]),
      "+f"(d[16]), "+f"(d[17]), "+f"(d[18]), "+f"(d[19]), "+f"(d[20]), "+f"(d[21]), "+f"(d[22]), "+f"(d[23]),
      "+f"(d[24]), "+f"(d[25]), "+f"(d[26]), "+f"(d[27]), "+f"(d[28]), "+f"(d[29]), "+f"(d[30]), "+f"(d[31]),
      "+f"(d[32]), "+f"(d[33]), "+f"(d[34]), "+f"(d[35]), "+f"(d[36]), "+f"(d[37]), "+f"(d[38]), "+f"(d[39]),
      "+f"(d[40]), "+f"(d[41]), "+f"(d[42]), "+f"(d[43]), "+f"(d[44]), "+f"(d[45]), "+f"(d[46]), "+f"(d[47]),
      "+f"(d[48]), "+f"(d[49]), "+f"(d[50]), "+f"(d[51]), "+f"(d[52]), "+f"(d[53]), "+f"(d[54]), "+f"(d[55]),
      "+f"(d[56]), "+f"(d[57]), "+f"(d[58]), "+f"(d[59]), "+f"(d[60]), "+f"(d[61]), "+f"(d[62]), "+f"(d[63])
    : "l"(descA), "l"(descB), "r"(scaleD));
}
__device__ __forceinline__ void wgmma_m64n256k16_rs(float (&d)[128], uint32_t a0, uint32_t a1, uint32_t a2, uint32_t a3, uint64_t descB, int scaleD) {
  asm volatile("{\n.reg .pred p;\nsetp.ne.b32 p, %133, 0;\n"
    "wgmma.mma_async.sync.aligned.m64n256k16.f32.bf16.bf16 "
    "{%0, %1, %2, %3, %4, %5, %6, %7, %8, %9, %10, %11, %12, %13, %14, %15, "
    "%16, %17, %18, %19, %20, %21, %22, %23, %24, %25, %26, %27, %28, %29, %30, %31, "
    "%32, %33, %34, %35, %36, %37, %38, %39, %40, %41, %42, %43, %44, %45, %46, %47, "
    "%48, %49, %50, %51, %52, %53, %54, %55, %56, %57, %58, %59, %60, %61, %62, %63, "
    "%64, %65, %66, %67, %68, %69, %70, %71, %72, %73, %74, %75, %76, %77, %78, %79, "
    "%80, %81, %82, %83, %84, %85, %86, %87, %88, %89, %90, %91, %92, %93, %94, %95, "
    "%96, %97, %98, %99, %100, %101, %102, %103, %104, %105, %106, %107, %108, %109, %110, %111, "
    "%112, %113, %114, %115, %116, %117, %118, %119, %120, %121, %122, %123, %124, %125, %126, %127}, "
    "{%128, %129, %130, %131}, %132, p, 1, 1, 1;\n}\n"
    : "+f"(d[0]), "+f"(d[1]), "+f"(d[2]), "+f"(d[3]), "+f"(d[4]), "+f"(d[5]), "+f"(d[6]), "+f"(d[7]),
      "+f"(d[8]), "+f"(d[9]), "+f"(d[10]), "+f"(d[11]), "+f"(d[12]), "+f"(d[13]), "+f"(d[14]), "+f"(d[15]),
      "+f"(d[16]), "+f"(d[17]), "+f"(d[18]), "+f"(d[19]), "+f"(d[20]), "+f"(d[21]), "+f"(d[22]), "+f"(d[23]),
      "+f"(d[24]), "+f"(d[25]), "+f"(d[26]), "+f"(d[27]), "+f"(d[28]), "+f"(d[29]), "+f"(d[30]), "+f"(d[31]),
      "+f"(d[32]), "+f"(d[33]), "+f"(d[34]), "+f"(d[35]), "+f"(d[36]), "+f"(d[37]), "+f"(d[38]), "+f"(d[39]),
      "+f"(d[40]), "+f"(d[41]), "+f"(d[42]), "+f"(d[43]), "+f"(d[44]), "+f"(d[45]), "+f"(d[46]), "+f"(d[47]),
      "+f"(d[48]), "+f"(d[49]), "+f"(d[50]), "+f"(d[51]), "+f"(d[52]), "+f"(d[53]), "+f"(d[54]), "+f"(d[55]),
      "+f"(d[56]), "+f"(d[57]), "+f"(d[58]), "+f"(d[59]), "+f"(d[60]), "+f"(d[61]), "+f"(d[62]), "+f"(d[63]),
      "+f"(d[64]), "+f"(d[65]), "+f"(d[66]), "+f"(d[67]), "+f"(d[68]), "+f"(d[69]), "+f"(d[70]), "+f"(d[71]),
      "+f"(d[72]), "+f"(d[73]), "+f"(d[74]), "+f"(d[75]), "+f"(d[76]), "+f"(d[77]), "+f"(d[78]), "+f"(d[79]),
      "+f"(d[80]), "+f"(d[81]), "+f"(d[82]), "+f"(d[83]), "+f"(d[84]), "+f"(d[85]), "+f"(d[86]), "+f"(d[87]),
      "+f"(d[88]), "+f"(d[89]), "+f"(d[90]), "+f"(d[91]), "+f"(d[92]), "+f"(d[93]), "+f"(d[94]), "+f"(d[95]),
      "+f"(d[96]), "+f"(d[97]), "+f"(d[98]), "+f"(d[99]), "+f"(d[100]), "+f"(d[101]), "+f"(d[102]), "+f"(d[103]),
      "+f"(d[104]), "+f"(d[105]), "+f"(d[106]), "+f"(d[107]), "+f"(d[108]), "+f"(d[109]), "+f"(d[110]), "+f"(d[111]),
      "+f"(d[112]), "+f"(d[113]), "+f"(d[114]), "+f"(d[115]), "+f"(d[116]), "+f"(d[117]), "+f"(d[118]), "+f"(d[119]),
      "+f"(d[120]), "+f"(d[121]), "+f"(d[122]), "+f"(d[123]), "+f"(d[124]), "+f"(d[125]), "+f"(d[126]), "+f"(d[127])
    : "r"(a0), "r"(a1), "r"(a2), "r"(a3), "l"(descB), "r"(scaleD));
}

constexpr uint32_t MSLOT = 32768, QSLOT = 49152;
constexpr int NM = 6;
constexpr uint32_t SM_X0 = 3 * QSLOT;
constexpr uint32_t SM_XR = SM_X0 + 16384;
constexpr uint32_t SM_STG = 196608;
constexpr uint32_t SM_XCH = SM_STG + 16384;
constexpr uint32_t SM_BAR = SM_STG + 32768;
constexpr uint32_t SM_VEC = SM_BAR + 512;
constexpr uint32_t SM_MODT = SM_VEC;
constexpr uint32_t SM_TOTAL = SM_VEC + 2048;
constexpr uint32_t B_X = SM_BAR  , B_EQ = B_X + 64, B_EM = B_EQ + 32, B_STREQ = B_EM + 48, B_STH = B_STREQ + 8, B_LN = B_STH + 8,
                   B_FQ = B_LN + 8, B_FM = B_FQ + 32, B_MOD = B_FM + 48  , B_GATE = B_MOD + 64, B_STFREE = B_GATE + 8, B_VEC = B_STFREE + 8  ,
                   B_FLG = B_VEC + 16  , B_H2A = B_FLG + 88, B_END = B_H2A + 8;
constexpr int NB_WG = 1  , NB_CONS = 3, NB_ORD = 4  ;
#define PF_BYTES 256
#define X_S1 7
#define X_POLL 3
#define SVC_WAIT mbar_sleep
#define PRD_WAIT mbar_wait
#define WPRE 2
#define QPOS 3
#define AUX_SLOW 84
#define AUX_GAP 500
#define DTAIL 4
#define EF 7
#define TRG_WAIT mbar_wait
#define ST_SPIN0 1
#define AUX_HOLD 3200
#define MSEP 6
#define AUX_URG 4
#define GPRE 5
#define X_UP 1
#define X_GAP 250

struct Maps {
  CUtensorMap x, out;
  CUtensorMap o, h2, hh;
  CUtensorMap wqk, wvv, wq1, wo, w1, w3, w2;
  CUtensorMap wmod;
};

struct Ring { int st; uint32_t ph; int prev; uint32_t dl;
};
__device__ __forceinline__ void ring_next(Ring& r) { if (++r.st == NM) { r.st = 0; r.ph ^= 1; } }

__device__ __forceinline__ void retire_prev(uint32_t rel, bool on) {
  wgmma_commit();
  wgmma_wait<1>();
  if (on) mbar_arrive_e(rel);
}
struct Nop { __device__ __forceinline__ void operator()() const {} };
template <bool REL = true, class F = Nop>
__device__ __forceinline__ void mma_step(float (&acc)[64], uint32_t a, uint32_t b, bool first, uint32_t rel, F urgent = F()) {
  const uint32_t alo = (a >> 4) + (1u << 16), blo = (b >> 4) + (512u << 16);
  wgmma_fence();
  #pragma unroll
  for (int k = 0; k < 4; k++) {
    wgmma_m64n128k16_ss(acc, desc_from_lo(alo + k * 2), desc_from_lo(blo + k * 128), k > 0 || !first);
    if (k == 0) { retire_prev(rel, REL); urgent(); }
  }
  wgmma_commit();
}
__device__ __forceinline__ uint32_t m_wait(uint32_t sbase, const Ring& r) {
  mbar_wait(sbase + B_FM + 8 * r.st, r.ph, r.dl);
  return sbase + r.st * MSLOT;
}
__device__ __forceinline__ uint32_t m_prev(uint32_t sbase, const Ring& r) { return sbase + B_EM + 8 * r.prev; }
__device__ __forceinline__ void m_next(Ring& r) {
  r.prev = r.st; ring_next(r);
}
__device__ __forceinline__ void m_step(float (&acc)[64], uint32_t sbase, uint32_t wgoff, Ring& r, bool first = false) {
  const uint32_t slot = m_wait(sbase, r);
  mma_step(acc, slot + wgoff, slot + 16384, first, m_prev(sbase, r));
  m_next(r);
}

struct LnRow { uint32_t rs[2], nb[2]; };
__device__ __forceinline__ void ln_row(LnRow& l, int h, float mean, float rstd) {
  l.rs[h] = pack_bf16(rstd, rstd);
  const float nb = -mean * bf_lo(l.rs[h]);
  l.nb[h] = pack_bf16(nb, nb);
}
__device__ __forceinline__ uint32_t ln_mod(uint32_t x, const LnRow& l, int h, uint32_t c1, uint32_t s) {
  return fma_bf2(fma_bf2(x, l.rs[h], l.nb[h]), c1, s);
}

__device__ __forceinline__ uint32_t q_wait(int u, uint32_t sbase, uint32_t dl) {
  mbar_wait(sbase + B_FQ + 8 * (u & 3), (u >> 2) & 1, dl);
  return sbase + (u & 3) * QSLOT;
}
__device__ __forceinline__ uint32_t q_empty(int u, uint32_t sbase) { return sbase + B_EQ + 8 * (u & 3); }
struct Frag4 { uint32_t o[4]; };
__device__ __forceinline__ void q_load(uint32_t (&A)[16], uint4 (&p)[4], int kk, uint32_t tile, const Frag4& f, uint32_t t) {
  ldmatrix_x4(tile + f.o[kk], A[4 * kk], A[4 * kk + 1], A[4 * kk + 2], A[4 * kk + 3]);
  p[kk] = lds128(t + kk * 64);
}
__device__ __forceinline__ void q_norm(uint32_t (&A)[16], const uint4 (&p)[4], int kk, const LnRow& l) {
  A[4 * kk + 0] = ln_mod(A[4 * kk + 0], l, 0, p[kk].x, p[kk].z); A[4 * kk + 1] = ln_mod(A[4 * kk + 1], l, 1, p[kk].x, p[kk].z);
  A[4 * kk + 2] = ln_mod(A[4 * kk + 2], l, 0, p[kk].y, p[kk].w); A[4 * kk + 3] = ln_mod(A[4 * kk + 3], l, 1, p[kk].y, p[kk].w);
}
template <bool NEXT>
__device__ __forceinline__ void q_step_rs(float (&acc)[128], uint32_t (&A)[16], uint32_t (&N)[16], uint4 (&p)[4], int u, uint32_t sbase,
                                          const Frag4& f, uint32_t tab, const LnRow& l, uint32_t rot, bool keep, bool first, uint32_t dl, int wg, int zero) {
  const uint32_t slot = first ? sbase : q_wait(u, sbase, dl);
  const uint32_t blo = ((slot + 16384) >> 4) + (512u << 16) + rot * 128 + (zero << (u >> 2)), t = tab + ((u + 1) & 7) * 256;
  #pragma unroll
  for (int kk = 0; kk < 4; kk++) q_norm(A, p, kk, l);
  #pragma unroll
  for (int i = 0; i < 16; i++) asm volatile("" : "+r"(A[i]));
  if (!first) sched_fence(zero);
  if (first) {
    mbar_wait(sbase + B_GATE, 0, dl);
    PROF(6, threadIdx.x == 0);
  }
  if (!(first && wg == 0)) bar_sync(NB_ORD + wg, 256);
  wgmma_fence();
  #pragma unroll
  for (int kk = 0; kk < 4; kk++) {
    wgmma_m64n256k16_rs(acc, A[4 * kk], A[4 * kk + 1], A[4 * kk + 2], A[4 * kk + 3], desc_from_lo(blo ^ (kk * 128)), kk > 0 || !first);
    if (kk == 0) retire_prev(q_empty(u - 1, sbase), !first);
    if (NEXT && kk == 1) {
      if ((u & 1) && u < MSEP) mbar_wait(sbase + B_MOD + 4 * (u + 1), 0, dl);
      #pragma unroll
      for (int q = 0; q < 4; q++) q_load(N, p, q, slot, f, t);
    }
    if (kk == QPOS && (NEXT || wg == 0)) bar_arrive(NB_ORD + (wg ^ 1), 256);
    if (kk == 1) stmatrix_x4_if(sbase + SM_STG + (u >> 3) * 16384 + (f.o[0] ^ (((u >> 1 & 3) ^ rot) << 5)), A[0], A[1], A[2], A[3], keep);
  }
  wgmma_commit();
}

typedef uint32_t Frag8[8];
template <int N> __device__ __forceinline__ void pack_half(Frag8& f, const float (&acc)[N], int off, int half) {
  #pragma unroll
  for (int e = 0; e < 8; e++) { f[e] = pack_bf16(acc[off + 4 * e + 2 * half], acc[off + 4 * e + 2 * half + 1]); asm volatile("" : "+r"(f[e])); }
}
__device__ __forceinline__ void transpose8(Frag8& f) {
  #pragma unroll
  for (int e = 0; e < 8; e++) f[e] = movmatrix_t(f[e]);
}
__device__ __forceinline__ void attn_send(const Frag8& f, int kv, uint32_t xch, int warp, uint4* halo_out, bool has_next) {
  if (warp == 3) {
    st_nonzero_v4(halo_out + kv * 64, f[0], f[1], f[2], f[3], has_next); st_nonzero_v4(halo_out + kv * 64 + 32, f[4], f[5], f[6], f[7], has_next);
  } else {
    sts128(xch + 2048 + kv * 1024, f[0], f[1], f[2], f[3]); sts128(xch + 2048 + kv * 1024 + 512, f[4], f[5], f[6], f[7]);
  }
}
template <int N>
__device__ __forceinline__ void attn_recv(uint4* p, int first, uint32_t xch, int wg, int warp, const uint4* halo_in, bool has_prev) {
  bar_sync(NB_WG + wg, 128);
  #pragma unroll
  for (int e = 0; e < N; e++)
    asm volatile("{\n.reg .pred p, q;\nsetp.ne.b32 p, %6, 0;\nsetp.ne.b32 q, %7, 0;\n"
                 "mov.b32 %0, 0;\nmov.b32 %1, 0;\nmov.b32 %2, 0;\nmov.b32 %3, 0;\n"
                 "@p ld.shared.v4.b32 {%0,%1,%2,%3}, [%4];\n@q ld.relaxed.gpu.global.v4.u32 {%0,%1,%2,%3}, [%5];\n}"
                 : "=&r"(p[e].x), "=&r"(p[e].y), "=&r"(p[e].z), "=&r"(p[e].w)
                 : "r"(xch + (first + e) * 512), "l"(halo_in + (first + e) * 32), "r"((int)(warp > 0)), "r"((int)(warp == 0 && has_prev)) : "memory");
}
template <int N>
__device__ __forceinline__ void attn_check(uint4* p, int first, bool remote, const uint4* halo_in, uint32_t dl) {
  if (remote) {
    while (true) {
      uint32_t m = ~0u;
      #pragma unroll
      for (int e = 0; e < N; e++) m = min(m, min4(p[e]));
      if (poll_done(m != 0, dl)) break;
      #pragma unroll
      for (int e = 0; e < N; e++) p[e] = ld_rlx_v4(halo_in + (first + e) * 32);
    }
  }
}
__device__ __forceinline__ void attn_core(const Frag8& qA, const Frag8& qB, const Frag8& kA, const Frag8& kB, const Frag8& vA, const Frag8& vB,
                                          const uint4* kP, const uint4* vP, bool noprev, int lane, float (&o)[2][5][4]) {
  const int g = lane >> 2, qd = lane & 3;
  const bool s0 = 2 * qd > g, s1 = 2 * qd + 1 > g;
  const uint32_t msk = (s0 ? 0xFFFFu : 0u) | (s1 ? 0xFFFF0000u : 0u);
  constexpr float SC = 0.17677669529663687f * 1.4426950408889634f;
  float s[2][3][4];
  #pragma unroll
  for (int h = 0; h < 2; h++) {
    #pragma unroll
    for (int nb = 0; nb < 3; nb++) s[h][nb][0] = s[h][nb][1] = s[h][nb][2] = s[h][nb][3] = 0.f;
    #pragma unroll
    for (int kk = 0; kk < 2; kk++) {
      const int e = 4 * h + 2 * kk;
      mma16(s[h][1], qA[e], qB[e], qA[e + 1], qB[e + 1], kA[e], kA[e + 1]);
      mma16(s[h][2], qA[e], qB[e], qA[e + 1], qB[e + 1], kB[e], kB[e + 1]);
      mma16(s[h][0], qA[e], qB[e], qA[e + 1], qB[e + 1], kk ? kP[h].z : kP[h].x, kk ? kP[h].w : kP[h].y);
    }
  }
  #pragma unroll
  for (int h = 0; h < 2; h++) {
    float l[4], m[2];
    l[0] = s0 ? (noprev ? -INFINITY : s[h][0][0]) : s[h][1][0];
    l[1] = s1 ? (noprev ? -INFINITY : s[h][0][1]) : s[h][1][1];
    l[2] = s0 ? s[h][1][2] : s[h][2][2];
    l[3] = s1 ? s[h][1][3] : s[h][2][3];
    m[0] = fmaxf(l[0], l[1]); m[1] = fmaxf(l[2], l[3]);
    #pragma unroll
    for (int x = 1; x <= 2; x <<= 1)
      #pragma unroll
      for (int e = 0; e < 2; e++) m[e] = fmaxf(m[e], __shfl_xor_sync(0xffffffffu, m[e], x));
    #pragma unroll
    for (int e = 0; e < 4; e++) l[e] = fast_ex2((l[e] - m[e >> 1]) * SC);
    const uint32_t plo = pack_bf16(l[0], l[1]), phi = pack_bf16(l[2], l[3]);
    const uint32_t vp[4] = {vP[h].x, vP[h].y, vP[h].z, vP[h].w};
    #pragma unroll
    for (int d = 0; d < 5; d++) o[h][d][0] = o[h][d][1] = o[h][d][2] = o[h][d][3] = 0.f;
    mma16(o[h][4], 0x3F803F80u, 0u, 0u, 0x3F803F80u, plo, phi);
    #pragma unroll
    for (int m2 = 0; m2 < 2; m2++) {
      const int e = 4 * h + 2 * m2;
      mma16(o[h][2 * m2], vp[2 * m2], vp[2 * m2 + 1], vA[e], vA[e + 1], plo & msk, plo & ~msk);
      mma16(o[h][2 * m2 + 1], vA[e], vA[e + 1], vB[e], vB[e + 1], phi & msk, phi & ~msk);
    }
  }
}
__device__ __forceinline__ void attn_store(const float (&o)[2][5][4], int h, uint32_t sbase, const Frag4& f) {
  float r[4];
  #pragma unroll
  for (int e = 0; e < 4; e++) r[e] = fast_rcp(o[h][4][e]);
  #pragma unroll
  for (int m = 0; m < 2; m++) {
    const float (&lo)[4] = o[h][2 * m], (&hi)[4] = o[h][2 * m + 1];
    stmatrix_x4_t(sbase + SM_STG + f.o[2 * h + m], pack_bf16(lo[0] * r[0], lo[1] * r[1]), pack_bf16(hi[0] * r[2], hi[1] * r[3]),
                  pack_bf16(lo[2] * r[0], lo[3] * r[1]), pack_bf16(hi[2] * r[2], hi[3] * r[3]));
  }
}

__device__ __forceinline__ void request_store(uint32_t bar) {
  fence_proxy_async_smem();
  mbar_arrive_e(bar);
}

__device__ __forceinline__ void g_switch(float (&cur)[64], float (&prv)[64], int nrest, bool first, int n, uint32_t sbase, uint32_t wgoff,
                                         const Frag4& f, Ring& r) {
  #pragma unroll 1
  for (int i = 1; i < nrest; i++) m_step(prv, sbase, wgoff, r);
  m_step(prv, sbase, wgoff, r);
  m_step(cur, sbase, wgoff, r, first);
  mbar_wait(sbase + B_STFREE, (n - 1) & 1, r.dl);
  fence_regs(prv);
  PROF(28 + n, threadIdx.x == 0);
  #pragma unroll
  for (int jj = 0; jj < 4; jj++) {
    uint32_t p[4];
    #pragma unroll
    for (int e = 0; e < 4; e++) {
      const int i = jj * 8 + e * 2;
      p[e] = pack_bf16(swiglu(prv[i], prv[i + 32]), swiglu(prv[i + 1], prv[i + 33]));
    }
    stmatrix_x4(sbase + SM_STG + f.o[jj], p[0], p[1], p[2], p[3]);
    m_step(cur, sbase, wgoff, r);
  }
  request_store(sbase + B_STREQ);
}

__device__ __forceinline__ uint32_t bad2(uint32_t a, uint32_t b, unsigned par) {
  uint32_t d; asm("lop3.b32 %0, %1, %2, %3, 0x7E;" : "=r"(d) : "r"(a), "r"(b), "r"(par)); return d;
}
__device__ __forceinline__ uint32_t bad4(const uint4& v, unsigned par) { return bad2(v.x, v.y, par) | bad2(v.z, v.w, par); }
__device__ __forceinline__ uint32_t hi_halves(uint32_t lo, uint32_t hi) { return __byte_perm(lo, hi, 0x7632); }

__device__ __forceinline__ void gather_table(const float* src, uint32_t dst, uint32_t bar, unsigned par, uint32_t dl) {
  asm volatile("{\n.reg .pred p, e;\n.reg .b32 s<4>, c<4>, t<4>, w<4>;\n"
               "elect.sync _|e, 0xffffffff;\n"
               "LAB_POLL:\n"
               "ld.relaxed.gpu.global.v4.u32 {s0, s1, s2, s3}, [%0];\n"
               "ld.relaxed.gpu.global.v4.u32 {c0, c1, c2, c3}, [%0 + 4096];\n"
               "prmt.b32 w0, c0, c1, 0x7632;\nprmt.b32 w1, c2, c3, 0x7632;\nprmt.b32 w2, s0, s1, 0x7632;\nprmt.b32 w3, s2, s3, 0x7632;\n"
               "st.shared.v4.b32 [%1], {w0, w1, w2, w3};\n"
               "lop3.b32 t0, s0, s1, %3, 0x7E;\nlop3.b32 t1, s2, s3, %3, 0x7E;\nlop3.b32 t2, c0, c1, %3, 0x7E;\nlop3.b32 t3, c2, c3, %3, 0x7E;\n"
               "lop3.b32 t0, t0, t1, 1, 0xA8;\nlop3.b32 t2, t2, t3, 1, 0xA8;\n"
               "or.b32 t0, t0, t2;\n"
               "setp.eq.u32 p, t0, 0;\n"
               "vote.sync.all.pred p, p, 0xffffffff;\n"
               "@p bra.uni LAB_OK;\n"
               "mov.u32 t0, %%clock;\nsub.s32 t0, t0, %4;\nsetp.lt.s32 p, t0, 0;\n"
               "vote.sync.all.pred p, p, 0xffffffff;\n"
               "@p bra.uni LAB_POLL;\n"
               "LAB_OK:\n"
               "@e mbarrier.arrive.shared::cta.b64 _, [%2];\n}"
               :: "l"(src), "r"(dst), "r"(bar), "r"(par), "r"(dl) : "memory");
}

__device__ __forceinline__ int other_slot(int i, int j) { return i < 4 ? (~j & 4) + i : (j & 4) + i - 4 + (i - 4 >= (j & 3)); }

__device__ __forceinline__ int aux_col(int a, int u) { return u < 8 ? (a & 1) * 1024 + (2 * u + (a >> 1)) * 64 : 2048 + ((u - 8) * 4 + a) * 64; }
constexpr int NA = 7;
constexpr uint32_t A_FULL = SM_BAR, A_EMPTY = SM_BAR + 64, A_SUM = SM_BAR + 128, A_FREE = SM_BAR + 136, SM_RED = SM_VEC;
__device__ __forceinline__ void aux_role(const Maps& maps, const bf16* __restrict__ cvec, Mail* mail0, int zero, int a, uint32_t sbase, int wid) {
  const int tid = threadIdx.x, lane = tid & 31;
  const uint32_t dl = clock32() + 800000000u;
  int st = 0; uint32_t ph = 0;
  if (wid == 8) {
    prefetch_tmap(&maps.wmod);
    #pragma unroll
    for (int i = 0; i < 18; i++) mbar_init_e(sbase + A_FULL + 8 * i, i < 8 ? 1 : i < 17 ? 8 : 2);
    fence_proxy_async_smem();
    bar_arrive(0, 352);
    PROF(39, lane == 0);
    #pragma unroll
    for (int i = 0; i < NA; i++) {
      mbar_expect_tx_e(sbase + A_FULL + 8 * i, 32768);
      tma_load_2d(sbase + i * MSLOT, &maps.wmod, sbase + A_FULL + 8 * i, aux_col(a, i >> 2), (i & 3) * 256);
    }
    PROF(40, lane == 0);
    #pragma unroll 1
    for (int i = NA; i < 96; i++) {
      if (i >= AUX_SLOW) wait_until(clock32() + AUX_GAP);
      if (i == 8) wait_until(dl - 800000000u + AUX_HOLD);
      mbar_wait(sbase + A_EMPTY + 8 * st, ph, dl);
      mbar_expect_tx_e(sbase + A_FULL + 8 * st, 32768);
      tma_load_2d<(EF & 1) != 0>(sbase + st * MSLOT, &maps.wmod, sbase + A_FULL + 8 * st, aux_col(a, i >> 2), (i & 3) * 256);
      if (++st == NA) { st = 0; ph ^= 1; }
    }
  } else if (wid < 8) {
    const int g = lane >> 2, qd = lane & 3;
    uint32_t sc[16];
    const uint2 c = *reinterpret_cast<const uint2*>(cvec + tid * 4);
    sts64(sbase + SM_RED + tid * 8, pack_bf16(silu_f(bf_lo(c.x)), silu_f(bf_hi(c.x))), pack_bf16(silu_f(bf_lo(c.y)), silu_f(bf_hi(c.y))));
    bar_sync(0, 352);
    #pragma unroll
    for (int i = 0; i < 16; i++) sc[i] = lds32(sbase + SM_RED + ((i >> 2) * 256 + wid * 32 + (i & 3) * 8 + qd * 2) * 2);
    bar_sync(NB_CONS, 256);
    PROF(38, tid == 0);
    const uint32_t aoff = (wid * 32 + (lane & 7) + (lane >> 4) * 8) * 128 + ((((lane >> 3) & 1) ^ (lane & 7)) << 4);
    uint32_t w[2][8][4];
    auto fetch = [&](uint32_t (&f)[8][4]) {
      mbar_wait(sbase + A_FULL + 8 * st, ph, dl);
      #pragma unroll
      for (int e = 0; e < 8; e++) ldmatrix_x4_t((sbase + st * MSLOT + aoff + (e >> 2) * 2048) ^ ((e & 3) << 5), f[e]);
      if (++st == NA) { st = 0; ph ^= 1; }
    };
    #pragma unroll 1
    for (int u = 0; u < 24; u++) {
      float acc[4][4];
      #pragma unroll
      for (int m = 0; m < 4; m++) acc[m][0] = acc[m][1] = acc[m][2] = acc[m][3] = 0.f;
      fetch(w[0]);
      #pragma unroll
      for (int q = 0; q < 4; q++) {
        PROF(30 + (u & 1) * 4 + q, u < 2 && tid == 0);
        const uint32_t rel = sbase + A_EMPTY + 8 * (st == 0 ? NA - 1 : st - 1);
        if (q < 3) fetch(w[(q + 1) & 1]);
        uint32_t dep = 0;
        #pragma unroll
        for (int e = 0; e < 8; e++) dep |= w[q & 1][e][0];
        mbar_arrive_e(rel + (dep & zero));
        if (q == 1) mbar_wait(sbase + A_FREE, (u & 1) ^ 1, dl);
        #pragma unroll
        for (int e = 0; e < 8; e++) {
          const uint32_t (&f)[4] = w[q & 1][e];
          mma16(acc[e & 3], f[0], f[1], f[2], f[3], sc[4 * q + 2 * (e >> 2)], sc[4 * q + 2 * (e >> 2) + 1]);
        }
      }
      const float v0 = qd & 2 ? (qd & 1 ? acc[3][0] : acc[2][0]) : (qd & 1 ? acc[1][0] : acc[0][0]);
      const float v1 = qd & 2 ? (qd & 1 ? acc[3][2] : acc[2][2]) : (qd & 1 ? acc[1][2] : acc[0][2]);
      sts64(sbase + SM_RED + wid * 256 + (qd * 8 + g) * 8, __float_as_uint(v0), __float_as_uint(v1));
      mbar_arrive_e(sbase + A_SUM);
      if (u < AUX_URG) mbar_wait(sbase + A_FREE, u & 1, dl);
    }
  } else if (wid < 11) {
    float* const mail = &mail0->mod[(wid - 9) * 4 * 6 * D_ + 2 * lane];
    unsigned par = ld_relaxed(&mail0->flags[FL_EPOCH + (lane >> 5)]);
    bar_sync(0, 352);
    par = (par + 1) & 1;
    #pragma unroll 1
    for (int u = -2; u < 24; u++) {
      if (u >= 0) {
        const int col = aux_col(a, u);
        const float add = (col >> 10) == 1 || (col >> 10) == 4 ? 1.f : 0.f;
        mbar_wait(sbase + A_SUM, u & 1, dl);
        float2 v[8];
        #pragma unroll
        for (int w = 0; w < 8; w++) v[w] = lds64f(sbase + SM_RED + w * 256 + lane * 8);
        const float t0 = ((v[0].x + v[1].x) + (v[2].x + v[3].x)) + ((v[4].x + v[5].x) + (v[6].x + v[7].x));
        const float t1 = ((v[0].y + v[1].y) + (v[2].y + v[3].y)) + ((v[4].y + v[5].y) + (v[6].y + v[7].y));
        mbar_arrive_e(sbase + A_FREE + (__float_as_uint(t0 + t1) & zero));
        const uint32_t w = pack_bf16(add + bf16_round(t0), add + bf16_round(t1)), o = __shfl_xor_sync(0xffffffffu, w, 1);
        const uint32_t m0 = (lane & 1) ? (o & 0xFFFF0000u) : (w << 16), m1 = (lane & 1) ? (w & 0xFFFF0000u) : (o << 16);
        #pragma unroll
        for (int c = 0; c < 4; c++) st_rlx_v2(mail + c * 6 * D_ + col, m0 | par, m1 | par, true);
        PROF(1 + u, tid == 288);
      }
      #pragma unroll 1
      for (int v = 2 * (u + 2); v < 2 * (u + 3) && v < 24; v++)
        #pragma unroll
        for (int c = 0; c < 4; c++) st_rlx_v2(mail + c * 6 * D_ + aux_col(a, v), par ^ 1, par ^ 1, true);
    }
    const int t = a * 64 + tid - 288;
    #pragma unroll 4
    for (int i = t; i < 16 * 16 * 256; i += 256) mail0->halo[par ^ 1][i] = make_uint4(0, 0, 0, 0);
    #pragma unroll 4
    for (int i = t; i < 16 * 8 * 64; i += 256) mail0->st2[par ^ 1][i] = make_uint4(0, 0, 0, 0);
  }
}

template <int MODE>
__global__ void __launch_bounds__(384, 1)
fused_block_kernel(const bf16* __restrict__ x, const bf16* __restrict__ cvec, const bf16* __restrict__ wmod, Mail* mail0, int zero,
                   const __grid_constant__ Maps maps) {
  extern __shared__ __align__(1024) uint8_t smem_raw[];
  const uint32_t sbase = smem_u32(smem_raw);
  const int tid = threadIdx.x, lane = tid & 31;
  PROFN(0, tid == 0);
  const int wid = __shfl_sync(0xffffffffu, tid >> 5, 0);
  const int b = cta_role<MODE>();
  if (b >= NCTA) { aux_role(maps, cvec, mail0, zero, b - NCTA, sbase, wid); return; }
  const int jg = b >> 6, mb = jg ? 31 - (b >> 2) : (b >> 2), j = 4 * jg + (b & 3);
  const uint32_t dl = clock32() + 800000000u;
  unsigned* const flags = &mail0->flags[mb * 32];
  const int row0 = mb * 128;

  if (wid >= 8) {
    if (wid == 8) {
      #pragma unroll
      for (int i = 0; i < 8; i++) mbar_init_e(sbase + B_X + 8 * i, 1);
      fence_proxy_async_smem();
      #pragma unroll
      for (int q = 0; q < X_UP; q++) {
        mbar_expect_tx_e(sbase + B_X + 8 * q, 4096);
        bulk_load(sbase + SM_XR + q * 4096, x + (size_t)(row0 + j * 16 + 2 * q) * D_, 4096, sbase + B_X + 8 * q);
      }
    } else if (wid == 11) {
      #pragma unroll
      for (int i = 0; i < 12; i++) prefetch_tmap(&maps.x + i);
    } else if (wid == 9) {
      #pragma unroll
      for (uint32_t bar = B_EQ; bar < B_FM; bar += 8) mbar_init_e(sbase + bar, bar < B_FQ ? 8 : bar == B_FQ + 8 || bar == B_FQ + 24 ? 2 : 1);
      fence_proxy_async_smem();
    } else {
      #pragma unroll
      for (uint32_t bar = B_FM; bar < B_END; bar += 8) mbar_init_e(sbase + bar, 1);
      fence_proxy_async_smem();
    }
    bar_sync(0, 384);
    reg_dealloc<40>();
    PROF(92, tid == 256);
    if (wid == 8) {
      uint32_t tnext = clock32();
      #pragma unroll 1
      for (int q = X_UP; q < 8; q++) {
        wait_until(tnext);
        mbar_expect_tx_e(sbase + B_X + 8 * q, 4096);
        bulk_load(sbase + SM_XR + q * 4096, x + (size_t)(row0 + j * 16 + 2 * q) * D_, 4096, sbase + B_X + 8 * q);
        tnext += X_GAP;
      }
      #pragma unroll 1
      for (int u = 0; u < 16; u++) {
        const int st = u & 3;
        if (u == 1) PRD_WAIT(X_S1 < 8 ? sbase + B_X + 8 * X_S1 : sbase + B_MOD, 0, dl);
        if (u == 2) { PRD_WAIT(sbase + B_GATE, 0, dl); PROFN(60, lane == 0); }
        if (u == 3) PRD_WAIT(sbase + B_EQ, 0, dl);
        PRD_WAIT(sbase + B_EQ + 8 * st, ((u >> 2) & 1) ^ 1, dl);
        const uint32_t slot = sbase + st * QSLOT, fb = sbase + B_FQ + 8 * st;
        mbar_expect_tx_e(fb, u == 0 ? 65536 : u == 15 ? 32768 : 49152);
        if ((u & 1) && (u < MSEP || u == 15)) mbar_arrive_e(fb);
        if (u == 0) tma_load_3d(sbase + SM_X0, &maps.x, fb, 0, mb * 64, 0);
        tma_load_4d<(EF & 2) != 0>(slot + 16384, &maps.wqk, fb, 0, u * 64, j, 0);
        tma_load_4d<(EF & 2) != 0>(slot + 32768, &maps.wvv, fb, 0, u * 64, j, 0);
        if (u < 15) tma_load_3d(slot, &maps.x, fb, u * 64 + 64, mb * 64, 0);
      }
      const unsigned e1 = 1 + ld_relaxed(flags + FO_EPOCH);
      Ring r{0, 1, 0, dl};
      uint32_t slot, fb;
      auto acquire = [&](uint32_t bytes) {
        PRD_WAIT(sbase + B_EM + 8 * r.st, r.ph, dl);
        slot = sbase + r.st * MSLOT; fb = sbase + B_FM + 8 * r.st;
        mbar_expect_tx_e(fb, bytes);
        ring_next(r);
      };
      #pragma unroll 1
      for (int kt = 0; kt < 16; kt++) {
        if (kt < 5) PRD_WAIT(sbase + B_EQ + 8 * (kt - (kt >= 2)), 1, dl);
        if ((kt & 7) == 0) { PROF(46, lane == 0 && kt == 8); PRD_WAIT(sbase + B_FLG + kt, 0, dl); PROF(47, lane == 0 && kt == 8); }
        acquire(32768);
        tma_load_4d<(EF & 2) != 0>(slot + 16384, &maps.wq1, fb, (j + 8) * 64, (kt & 1) * 64 + (kt & 6) * 8, (kt >> 3) * 4, 0);
        tma_load_3d(slot, &maps.hh, fb, (kt & 7) * 64, row0, kt >> 3);
      }
      PROF(82, lane == 0);
      PRD_WAIT(sbase + B_FLG + 16, 0, dl);
      PROF(83, lane == 0);
      #pragma unroll 1
      for (int kt = 0; kt < 8; kt++) {
        if (kt == 4) {
          acquire(32768);
          tma_load_3d(slot, &maps.x, fb, j * 128, mb * 64, 0);
          tma_load_3d(slot + 16384, &maps.x, fb, j * 128 + 64, mb * 64, 0);
        }
        acquire(32768);
        tma_load_3d<(EF & 2) != 0>(slot + 16384, &maps.wo, fb, 0, kt * 64, 2 * j);
        tma_load_2d(slot, &maps.o, fb, kt * 64, row0);
      }
      acquire(16384);
      tma_load_3d<(EF & 2) != 0>(slot + 16384, &maps.wo, fb, 0, (8 + j) * 64, 2 * j);
      {
        constexpr int NPRE = WPRE;
        Ring ra = r;
        #pragma unroll 1
        for (int i = 0; i < 7; i++) {
          const int kt = 8 + other_slot(i, j);
          acquire(32768);
          tma_load_3d<(EF & 2) != 0>(slot + 16384, &maps.wo, fb, 0, kt * 64, 2 * j);
          if (i == NPRE - 1) {
            wait_flag(&mail0->flags[FL_O], e1 * NCTA, dl);
            PROFN(61, lane == 0);
            #pragma unroll 1
            for (int q = 0; q < NPRE - 1; q++) { tma_load_2d(sbase + ra.st * MSLOT, &maps.o, sbase + B_FM + 8 * ra.st, (8 + other_slot(q, j)) * 64, row0); ring_next(ra); }
          }
          if (i >= NPRE - 1) tma_load_2d(slot, &maps.o, fb, kt * 64, row0);
        }
      }
      #pragma unroll 1
      for (int t = 0; t < 2; t++) {
        acquire(32768);
        tma_load_2d<(EF & 4) != 0>(slot, &maps.w1, fb, j * 64, (2 * j + t) * 64);
        tma_load_2d<(EF & 4) != 0>(slot + 8192, &maps.w3, fb, j * 64, (2 * j + t) * 64);
        tma_load_2d<(EF & 4) != 0>(slot + 16384, &maps.w1, fb, (8 + j) * 64, (2 * j + t) * 64);
        tma_load_2d<(EF & 4) != 0>(slot + 24576, &maps.w3, fb, (8 + j) * 64, (2 * j + t) * 64);
      }
      {
        Ring ra = r;
        #pragma unroll 1
        for (int i = 0; i < GPRE; i++) {
          const int kt = 2 * other_slot(i, j);
          acquire(32768);
          tma_load_2d<(EF & 4) != 0>(slot + 16384, &maps.w1, fb, j * 64, kt * 64);
          tma_load_2d<(EF & 4) != 0>(slot + 24576, &maps.w3, fb, j * 64, kt * 64);
        }
        wait_flag(&mail0->flags[FL_H2], e1 * NCTA, dl);
        PROFN(62, lane == 0);
        mbar_arrive_e(sbase + B_H2A);
        #pragma unroll 1
        for (int i = 0; i < GPRE; i++) { tma_load_2d(sbase + ra.st * MSLOT, &maps.h2, sbase + B_FM + 8 * ra.st, other_slot(i, j) * 128, row0); ring_next(ra); }
      }
      #pragma unroll 1
      for (int gt = 0; gt < 7; gt++) {
        const int ncol = (8 * gt + j) * 64;
        #pragma unroll 1
        for (int i = (gt == 0 ? GPRE : 0); i < (gt < 2 ? 14 : 16); i++) {
          const int kt = gt >= 2 ? i : i < 7 ? 2 * other_slot(i, j) : 2 * other_slot(i - 7, j) + 1;
          if (gt == 0 && i == 7) PRD_WAIT(sbase + B_FLG + 24, 0, dl);
          acquire(32768);
          tma_load_2d<(EF & 4) != 0>(slot + 16384, &maps.w1, fb, ncol, kt * 64);
          tma_load_2d<(EF & 4) != 0>(slot + 24576, &maps.w3, fb, ncol, kt * 64);
          tma_load_2d(slot, &maps.h2, fb, kt * 64, row0);
        }
      }
      #pragma unroll 1
      for (int kt = 0; kt < 56; kt++) {
        if ((kt & 7) == 0) PRD_WAIT(sbase + B_FLG + 32 + kt, 0, dl);
        acquire(32768);
        tma_load_3d<(EF & 8) != 0>(slot + 16384, &maps.w2, fb, 0, kt * 64, 2 * j);
        tma_load_3d<(EF & 16) != 0>(slot, &maps.hh, fb, (kt & 7) * 64, row0, kt >> 3);
      }
    } else {
      const unsigned e1 = 1 + ld_relaxed(wid == 9 ? flags + FO_EPOCH : &mail0->flags[FL_EPOCH]), par = e1 & 1;
      if (wid == 9) {
        #pragma unroll 1
        for (int n = 0; n < 12; n++) {
          if (n == 4) {
            mbar_wait(sbase + B_STH, 0, dl);
            tma_store_2d(&maps.h2, sbase + SM_STG, j * 128, row0);
            bulk_commit();
            bulk_wait0();
            red_add_e(&mail0->flags[FL_H2], 1);
            PROF(84, lane == 0);
            mbar_wait(sbase + B_H2A, 0, dl);
          }
          if (n >= ST_SPIN0 && n <= 4) mbar_wait(sbase + B_STREQ, n & 1, dl); else SVC_WAIT(sbase + B_STREQ, n & 1, dl);
          if (n == 0) fence_proxy_async_smem();
          if (n == 2 || n == 3) tma_store_2d(&maps.o, sbase + SM_STG, (j + 8 * (n - 2)) * 64, row0);
          else if (n == 4) tma_store_2d(&maps.h2, sbase + SM_STG + 16384, j * 128 + 64, row0);
          else tma_store_3d(&maps.hh, sbase + SM_STG + (n == 1 ? 16384 : 0), j * 64, row0, n < 2 ? n : n - 5);
          bulk_commit();
          bulk_wait0();
          red_add_e(n == 3 ? &mail0->flags[FL_O] : flags + (n < 2 ? FO_H1 + n : n - 1), 1);
          mbar_arrive_e(sbase + B_STFREE);
          PROFN(70 + n, lane == 0 && n > 0); PROF(85, lane == 0 && n == 0);
        }
      } else {
        mbar_wait(sbase + B_X + 8 * X_POLL, 0, dl);
        const float* const mail = &mail0->mod[(b & 7) * 6 * D_ + lane * 4];
        if (wid == 10) {
          #pragma unroll 1
          for (int p = 0; p < 8; p++) {
            if (p >= 2) TRG_WAIT(p == 2 ? q_empty(0, sbase) : q_empty(2 * p - 5, sbase), p == 2 ? 0 : ((2 * p - 5) >> 2) & 1, dl);
            gather_table(mail + p * 128, sbase + SM_MODT + (p & 3) * 512 + ((lane * 16) ^ ((j >> 1) << 6)), 2 * p - 1 < MSEP ? sbase + B_MOD + 8 * p : sbase + B_FQ + 8 * ((2 * p - 1) & 3), par, dl);
            PROF(63 + p, lane == 0 && p < 7);
          }
          const uint32_t vdst = sbase + SM_VEC + (lane >> 3) * 64 + (lane & 3) * 16 + ((lane >> 2) & 1) * 8;
          #pragma unroll 1
          for (int v = 0; v < 2; v++) {
            SVC_WAIT(sbase + B_FLG + 16 + 16 * v, 0, dl);
            uint4 m[3];
            while (true) {
              #pragma unroll
              for (int e = 0; e < 3; e++) m[e] = ld_rlx_v4(mail + (2 + v + e) * 1024 + j * 128);
              if (poll_done(((bad4(m[0], par) | bad4(m[1], par) | bad4(m[2], par)) & 1) == 0, dl)) break;
              __nanosleep(200);
            }
            #pragma unroll
            for (int e = 0; e < 3; e++) sts64(vdst + (v + e) * 256, hi_halves(m[e].x, m[e].y), hi_halves(m[e].z, m[e].w));
            mbar_arrive_e(sbase + B_VEC + 8 * v);
            PROF(70, lane == 0 && v == 0);
          }
        } else {
          mbar_wait(sbase + B_LN, 0, dl);
          red_add_e(&mail0->flags[FL_LN1], 1);
          wait_flag(&mail0->flags[FL_LN1], e1 * NCTA, dl);
          mbar_arrive_e(sbase + B_GATE);
          PROF(41, lane == 0);
          #pragma unroll 1
          for (int i = 0; i < 11; i++) {
            const unsigned* f = flags + (i < 2 ? FO_H1 + i : i == 2 ? FO_O : FO_H2 + i - 3);
            if (i == 3) SVC_WAIT(sbase + B_H2A, 0, dl);
            while (!poll_done((int)(ld_relaxed(f) - e1 * 8) >= 0, dl)) { if (i > 3 || i == 0) __nanosleep(200); }
            mbar_arrive_e(sbase + B_FLG + 8 * i);
          }
        }
      }
    }
  } else {
    const int wg = wid >> 2, warp = wid & 3;
    const int g = lane >> 2, qd = lane & 3;
    bulk_prefetch(wmod + (size_t)(b * 8 + wid) * (6 * D_), PF_BYTES);
    bulk_prefetch(wmod + (size_t)(b * 8 + wid) * (6 * D_) + D_, PF_BYTES);
    bar_sync(0, 384);
    bulk_prefetch(wmod + (size_t)(b * 8 + wid) * (6 * D_) + PF_BYTES / 2, PF_BYTES);
    bulk_prefetch(wmod + (size_t)(b * 8 + wid) * (6 * D_) + PF_BYTES / 2 + D_, PF_BYTES);
    const unsigned e1 = 1 + ld_relaxed(flags + FO_EPOCH), par = e1 & 1;
    reg_alloc<232>();
    PROF(1, tid == 0);
    const uint32_t wgoff = wg * 8192;
    const uint32_t frag0 = wid * 2048 + (lane & 15) * 128 + (((lane >> 4) ^ (lane & 7)) << 4);
    const uint32_t slab = sbase + SM_STG + wid * 2048;

    LnRow ln;
    {
      uint2* const lmail = &mail0->ln1[(mb * 8 + (lane & 1) * 4 + (j >> 1)) * 16 + (j & 1) * 8 + wid];
      st_rlx_v2(lmail, par ^ 1, par ^ 1, lane < 2);
      mbar_wait(sbase + B_X + 8 * wid, 0, dl);
      PROF(3, tid == 224); PROF(93, tid == 0);
      float s[2][2] = {{0.f, 0.f}, {0.f, 0.f}}, q2[2][2] = {{0.f, 0.f}, {0.f, 0.f}};
      #pragma unroll
      for (int c = 0; c < 8; c++) {
        const uint4 v = lds128(sbase + SM_XR + wid * 4096 + c * 512 + lane * 16);
        const uint32_t vv[4] = {v.x, v.y, v.z, v.w};
        #pragma unroll
        for (int e = 0; e < 4; e++) {
          const float lo = bf_lo(vv[e]), hi = bf_hi(vv[e]);
          s[c >> 2][0] += lo; s[c >> 2][1] += hi; q2[c >> 2][0] = fmaf(lo, lo, q2[c >> 2][0]); q2[c >> 2][1] = fmaf(hi, hi, q2[c >> 2][1]);
        }
      }
      const bool odd = lane & 1;
      float sm = (s[0][0] + s[0][1]), so = (s[1][0] + s[1][1]), qm = (q2[0][0] + q2[0][1]), qo = (q2[1][0] + q2[1][1]);
      { const float a = odd ? so : sm, c = odd ? qo : qm;
        sm = a + __shfl_xor_sync(0xffffffffu, odd ? sm : so, 1); qm = c + __shfl_xor_sync(0xffffffffu, odd ? qm : qo, 1); }
      #pragma unroll
      for (int o = 2; o < 32; o <<= 1) { sm += __shfl_xor_sync(0xffffffffu, sm, o); qm += __shfl_xor_sync(0xffffffffu, qm, o); }
      sm *= (1.f / D_);
      st_rlx_v2(lmail, tagf(fast_rsqrt(fmaxf(qm * (1.f / D_) - sm * sm, 0.f) + 1e-5f), par), tagf(sm, par), lane < 2);
      mbar_arrive_e(sbase + B_LN);
      PROF(4, tid == 224);
    }

    uint4* const halo_out = mail0->halo[par] + ((mb * 16 + j) * 2 + wg) * 128 + lane;
    const uint4* const halo_in = halo_out - 16 * 256;
    const uint32_t xch = sbase + SM_XCH + (tid >> 5) * 2048 + lane * 16;
    const bool noprev = mb == 0 && warp == 0, remote = mb > 0 && warp == 0;
    float a0[64], a1[64];
    uint32_t x2[32];
    Ring r{zero, 0, 0, dl};
    Frag8 qA, qB, kA, kB, vA, vB, wA, wB;
    {
      float acc[128];
      uint32_t A0[16], A1[16];
      undef_regs(acc);
      const uint32_t tab = sbase + SM_MODT + qd * 16;
      uint4 p[4];
      const uint32_t rot = j >> 1;
      Frag4 fq;
      #pragma unroll
      for (int q = 0; q < 4; q++) fq.o[q] = frag0 ^ ((q ^ rot) << 5);
      mbar_wait(sbase + B_LN, 0, dl);
      const uint2* const lin = &mail0->ln1[(mb * 8 + wid) * 16 + g];
      uint2 v0, v1;
      do { v0 = ld_rlx_v2(lin); v1 = ld_rlx_v2(lin + 8); } while (!poll_done(((bad2(v0.x, v0.y, par) | bad2(v1.x, v1.y, par)) & 1) == 0, dl));
      ln_row(ln, 0, __uint_as_float(v0.y), __uint_as_float(v0.x));
      ln_row(ln, 1, __uint_as_float(v1.y), __uint_as_float(v1.x));
      q_wait(0, sbase, dl);
      mbar_wait(sbase + B_MOD, 0, dl);
      #pragma unroll
      for (int kk = 0; kk < 4; kk++) q_load(A0, p, kk, sbase + SM_X0, fq, tab);
      PROF(5, tid == 0);
      q_step_rs<true>(acc, A0, A1, p, 0, sbase, fq, tab, ln, rot, !(j & 1), true, dl, wg, zero);
      #pragma unroll
      for (int u = 1; u < 15; u += 2) {
        q_step_rs<true>(acc, A1, A0, p, u, sbase, fq, tab, ln, rot, j & 1, false, dl, wg, zero);
        q_step_rs<true>(acc, A0, A1, p, u + 1, sbase, fq, tab, ln, rot, !(j & 1), false, dl, wg, zero);
        if (u == 7) mbar_arrive_e(sbase + B_STREQ);
      }
      q_step_rs<false>(acc, A1, A0, p, 15, sbase, fq, tab, ln, rot, j & 1, false, dl, wg, zero);
      PROF(7, tid == 0);
      mbar_wait(sbase + B_STFREE, 0, dl);
      request_store(sbase + B_STREQ);
      wgmma_wait<0>();
      undef_regs(a0);
      { const uint32_t slot = m_wait(sbase, r); mma_step(a0, slot + wgoff, slot + 16384, true, q_empty(15, sbase)); m_next(r); }
      fence_regs(acc);
      PROF(8, tid == 0);
      sched_fence(zero);
      pack_half(vB, acc, 64, 1); transpose8(vB);
      m_step(a0, sbase, wgoff, r);
      sched_fence(zero);
      pack_half(kB, acc, 32, 1);
      attn_send(vB, 1, xch - 16384, warp, halo_out, mb < 15); attn_send(kB, 0, xch - 16384, warp, halo_out, mb < 15);
      m_step(a0, sbase, wgoff, r);
      sched_fence(zero);
      pack_half(qA, acc, 0, 0); pack_half(qB, acc, 0, 1); pack_half(kA, acc, 32, 0); pack_half(wB, acc, 96, 1); pack_half(wA, acc, 96, 0);
      m_step(a0, sbase, wgoff, r);
      sched_fence(zero);
      pack_half(vA, acc, 64, 0); transpose8(vA);
    }
    uint4 wP[2];
    Frag4 frag;
    #pragma unroll
    for (int q = 0; q < 4; q++) frag.o[q] = frag0 ^ (q << 5);
    {
      m_step(a0, sbase, wgoff, r);
      uint4 pv[4];
      attn_recv<4>(pv, 0, xch - 16384, wg, warp, halo_in, mb > 0);
      m_step(a0, sbase, wgoff, r);
      mbar_wait(sbase + B_STFREE, 1, dl);
      transpose8(wB);
      m_step(a0, sbase, wgoff, r);
      attn_check<4>(pv, 0, remote, halo_in, dl);
      wgmma_wait<0>();
      PROF(9, tid == 0);
      float o[2][5][4];
      sched_fence(zero);
      attn_core(qA, qB, kA, kB, vA, vB, pv, pv + 2, noprev, lane, o);
      attn_store(o, 0, sbase, frag);
      attn_store(o, 1, sbase, frag);
      request_store(sbase + B_STREQ);
      bar_sync(NB_CONS, 256);
      PROF(10, tid == 0);
      m_step(a0, sbase, wgoff, r);
      sched_fence(zero);
      attn_send(wB, 1, xch, warp, halo_out + 8 * 256, mb < 15);
      m_step(a0, sbase, wgoff, r);
      sched_fence(zero);
      transpose8(wA);
      #pragma unroll 1
      for (int i = 9; i < 15; i++) m_step(a0, sbase, wgoff, r);
      attn_recv<2>(wP, 2, xch, wg, warp, halo_in + 8 * 256, mb > 0);
      m_step(a0, sbase, wgoff, r);
    }
    {
      undef_regs(a1);
      {
        const uint32_t slot = m_wait(sbase, r);
        mma_step(a1, slot + wgoff, slot + 16384, true, m_prev(sbase, r), [&] {
          fence_regs(a0);
          pack_half(kB, a0, 32, 1);
          attn_send(kB, 0, xch, warp, halo_out + 8 * 256, mb < 15);
        });
        m_next(r);
      }
      PROF(14, tid == 0);
      sched_fence(zero);
      pack_half(kA, a0, 32, 0); pack_half(qA, a0, 0, 0); pack_half(qB, a0, 0, 1);
      m_step(a1, sbase, wgoff, r);
      attn_check<2>(wP, 2, remote, halo_in + 8 * 256, dl);
      uint4 kP[2];
      attn_recv<2>(kP, 0, xch, wg, warp, halo_in + 8 * 256, mb > 0);
      m_step(a1, sbase, wgoff, r);
      attn_check<2>(kP, 0, remote, halo_in + 8 * 256, dl);
      wgmma_wait<0>();
      PROF(15, tid == 0);
      float o[2][5][4];
      mbar_wait(sbase + B_STFREE, 0, dl);
      attn_core(qA, qB, kA, kB, wA, wB, kP, wP, noprev, lane, o);
      attn_store(o, 0, sbase, frag);
      attn_store(o, 1, sbase, frag);
      request_store(sbase + B_STREQ);
      bar_sync(NB_CONS, 256);
      PROF(16, tid == 0);
      auto residual = [&] {
        const uint32_t xs = m_wait(sbase, r), xe = sbase + B_EM + 8 * r.st;
        ring_next(r);
        #pragma unroll
        for (int t = 0; t < 2; t++) {
          #pragma unroll
          for (int jj = 4 * t; jj < 4 * t + 4; jj++) ldmatrix_x4(xs + t * 16384 + frag.o[jj & 3], x2[4 * jj], x2[4 * jj + 1], x2[4 * jj + 2], x2[4 * jj + 3]);
          if (t == 1) {
            uint32_t dep = 0;
            #pragma unroll
            for (int jj = 0; jj < 8; jj++) dep |= x2[4 * jj];
            mbar_arrive_e(xe + (dep & zero));
          }
          m_step(a1, sbase, wgoff, r);
        }
      };
      m_step(a1, sbase, wgoff, r);
      residual();
      #pragma unroll 1
      for (int i = 6; i < 8; i++) m_step(a1, sbase, wgoff, r);
      mma_step(a1, sbase + SM_STG + wgoff, m_wait(sbase, r) + 16384, false, m_prev(sbase, r));
      m_next(r);
      PROF(17, tid == 0);
      uint4* const sm = mail0->st2[par] + (mb * 8 + wid) * 64 + g;
      st_rlx_v4(sm + j * 8, 0, 0, 0, 0, qd == (g >> 1));
      #pragma unroll 1
      for (int i = 0; i < 7; i++) { m_step(a1, sbase, wgoff, r); PROF(42, tid == 0 && i == 0); }
      PROF(45, tid == 0);
      mbar_wait(sbase + B_VEC, 0, dl);
      mbar_wait(sbase + B_STFREE, 1, dl);
      const uint32_t vec = sbase + SM_VEC + qd * 16;
      uint4 ga[4];
      #pragma unroll
      for (int q = 0; q < 4; q++) ga[q] = lds128(vec + q * 64);
      wgmma_wait<0>();
      mbar_arrive_e(m_prev(sbase, r));
      fence_regs(a1);
      PROF(18, tid == 0);
      float gl[4] = {0.f, 0.f, 0.f, 0.f}, gh[4] = {0.f, 0.f, 0.f, 0.f};
      #pragma unroll
      for (int jj = 0; jj < 8; jj++) {
        uint32_t* v = &x2[4 * jj];
        const uint32_t wl = (jj & 1) ? ga[jj >> 1].z : ga[jj >> 1].x, wh = (jj & 1) ? ga[jj >> 1].w : ga[jj >> 1].y;
        #pragma unroll
        for (int e = 0; e < 4; e++) v[e] = fma_bf2(e & 2 ? wh : wl, pack_bf16(a1[8 * jj + 2 * e], a1[8 * jj + 2 * e + 1]), v[e]);
        mma16(gl, v[0], 0x3F803F80u, v[2], 0x3F803F80u, v[0], v[2]);
        mma16(gh, v[1], 0x3F803F80u, v[3], 0x3F803F80u, v[1], v[3]);
      }
      st_nonzero_v4(sm + j * 8, __float_as_uint(g & 1 ? gl[3] : gl[2]), __float_as_uint(g & 1 ? gl[1] : gl[0]),
                __float_as_uint(g & 1 ? gh[3] : gh[2]), __float_as_uint(g & 1 ? gh[1] : gh[0]), qd == (g >> 1));
      float s[2], q2[2];
      PROF(19, tid == 0);
      uint4 sb[4], cb[4];
      #pragma unroll
      for (int q = 0; q < 4; q++) { sb[q] = lds128(vec + 256 + q * 64); cb[q] = lds128(vec + 512 + q * 64); }
      uint4 p0, p1;
      while (true) {
        p0 = ld_rlx_v4(sm + qd * 16); p1 = ld_rlx_v4(sm + qd * 16 + 8);
        if (poll_done(min(min4(p0), min4(p1)) != 0, dl)) break;
      }
      PROF(20, tid == 0);
      s[0] = __uint_as_float(p0.x) + __uint_as_float(p1.x); q2[0] = __uint_as_float(p0.y) + __uint_as_float(p1.y);
      s[1] = __uint_as_float(p0.z) + __uint_as_float(p1.z); q2[1] = __uint_as_float(p0.w) + __uint_as_float(p1.w);
      #pragma unroll
      for (int o2 = 1; o2 <= 2; o2 <<= 1)
        #pragma unroll
        for (int h = 0; h < 2; h++) { s[h] += __shfl_xor_sync(0xffffffffu, s[h], o2); q2[h] += __shfl_xor_sync(0xffffffffu, q2[h], o2); }
      #pragma unroll
      for (int h = 0; h < 2; h++) {
        const float m = s[h] * (1.f / D_);
        ln_row(ln, h, m, fast_rsqrt(fmaxf(q2[h] * (1.f / D_) - m * m, 0.f) + 1e-5f));
      }
      #pragma unroll
      for (int jj = 0; jj < 8; jj++) {
        const uint32_t cl = (jj & 1) ? cb[jj >> 1].z : cb[jj >> 1].x, ch = (jj & 1) ? cb[jj >> 1].w : cb[jj >> 1].y;
        const uint32_t sl = (jj & 1) ? sb[jj >> 1].z : sb[jj >> 1].x, sh = (jj & 1) ? sb[jj >> 1].w : sb[jj >> 1].y;
        stmatrix_x4(sbase + SM_STG + (jj >> 2) * 16384 + frag.o[jj & 3], ln_mod(x2[4 * jj], ln, 0, cl, sl), ln_mod(x2[4 * jj + 1], ln, 1, cl, sl),
                    ln_mod(x2[4 * jj + 2], ln, 0, ch, sh), ln_mod(x2[4 * jj + 3], ln, 1, ch, sh));
        if (jj == 3) { request_store(sbase + B_STH); sched_fence(zero); }
      }
      request_store(sbase + B_STREQ);
      bar_sync(NB_WG + wg, 128);
      PROF(21, tid == 0);
    }

    undef_regs(a0);
    #pragma unroll
    for (int t = 0; t < 2; t++) {
      const uint32_t slot = m_wait(sbase, r);
      if (t == 0) mma_step<false>(a0, sbase + SM_STG + wgoff, slot, true, 0);
      else mma_step(a0, sbase + SM_STG + 16384 + wgoff, slot, false, m_prev(sbase, r));
      mma_step<false>(a1, sbase + SM_STG + t * 16384 + wgoff, slot + 16384, t == 0, 0);
      m_next(r);
    }
    PROF(22, tid == 0);
    #pragma unroll 1
    for (int t = 0; t < 7; t += 2) {
      g_switch(a1, a0, t == 0 ? 14 : 11, t > 0, 5 + t, sbase, wgoff, frag, r);
      if (t == 6) break;
      g_switch(a0, a1, t == 0 ? 9 : 11, true, 6 + t, sbase, wgoff, frag, r);
    }
    #pragma unroll 1
    for (int i = 5; i < 56 - DTAIL; i++) m_step(a1, sbase, wgoff, r);
    if (DTAIL) {
      if (wg == 1) { wgmma_wait<0>(); mbar_arrive_e(m_prev(sbase, r)); bar_sync(NB_ORD, 256); }
      #pragma unroll
      for (int i = 0; i < DTAIL; i++) {
        const uint32_t slot = m_wait(sbase, r);
        const uint32_t alo = ((slot + wgoff) >> 4) + (1u << 16), blo = ((slot + 16384) >> 4) + (512u << 16);
        wgmma_fence();
        #pragma unroll
        for (int k = 0; k < 4; k++) wgmma_m64n128k16_ss(a1, desc_from_lo(alo + k * 2), desc_from_lo(blo + k * 128), true);
        wgmma_commit();
        ring_next(r);
      }
      if (wg == 0) bar_arrive(NB_ORD, 256);
    }
    {
      mbar_wait(sbase + B_STFREE, 1, dl);
      mbar_wait(sbase + B_VEC + 8, 0, dl);
      uint4 gb[4];
      #pragma unroll
      for (int q = 0; q < 4; q++) gb[q] = lds128(sbase + SM_VEC + 768 + qd * 16 + q * 64);
      wgmma_wait<0>();
      fence_regs(a1);
      PROF(50, tid == 128);
      #pragma unroll
      for (int t = 0; t < 2; t++) {
        #pragma unroll
        for (int jj = 4 * t; jj < 4 * t + 4; jj++) {
          const uint32_t gl = (jj & 1) ? gb[jj >> 1].z : gb[jj >> 1].x, gh = (jj & 1) ? gb[jj >> 1].w : gb[jj >> 1].y;
          const int i = 8 * jj;
          stmatrix_x4(sbase + SM_STG + t * 16384 + frag.o[jj & 3],
                      fma_bf2(gl, pack_bf16(a1[i], a1[i + 1]), x2[4 * jj]), fma_bf2(gl, pack_bf16(a1[i + 2], a1[i + 3]), x2[4 * jj + 1]),
                      fma_bf2(gh, pack_bf16(a1[i + 4], a1[i + 5]), x2[4 * jj + 2]), fma_bf2(gh, pack_bf16(a1[i + 6], a1[i + 7]), x2[4 * jj + 3]));
        }
        fence_proxy_async_smem();
        tma_store_3d(&maps.out, slab + t * 16384, j * 128 + t * 64, mb * 64 + warp * 16, wg);
      }
      bulk_commit();
      st_rlx(tid == 0 ? flags + FO_EPOCH : &mail0->flags[FL_EPOCH], e1, j == 0 && (tid == 0 || (tid == 1 && mb == 0)));
      bulk_wait_read0();
      PROFN(51, tid == 128);
    }
  }
}

typedef CUresult (*PFN_encodeTiled)(CUtensorMap*, CUtensorMapDataType, cuuint32_t, void*, const cuuint64_t*, const cuuint64_t*,
                                    const cuuint32_t*, const cuuint32_t*, CUtensorMapInterleave, CUtensorMapSwizzle,
                                    CUtensorMapL2promotion, CUtensorMapFloatOOBfill);

void encode(PFN_encodeTiled fn, CUtensorMap* m, const void* ptr, int rank, const cuuint64_t* dims, const cuuint64_t* strides,
            const cuuint32_t* box) {
  const cuuint32_t es[5] = {1, 1, 1, 1, 1};
  fn(m, CU_TENSOR_MAP_DATA_TYPE_BFLOAT16, rank, const_cast<void*>(ptr), dims, strides, box, es, CU_TENSOR_MAP_INTERLEAVE_NONE,
     CU_TENSOR_MAP_SWIZZLE_128B, CU_TENSOR_MAP_L2_PROMOTION_L2_256B, CU_TENSOR_MAP_FLOAT_OOB_FILL_NONE);
}
void map2d(PFN_encodeTiled fn, CUtensorMap* m, const void* ptr, int cols, int rows, int boxrows) {
  const cuuint64_t dims[2] = {(cuuint64_t)cols, (cuuint64_t)rows}, strides[1] = {(cuuint64_t)cols * 2};
  const cuuint32_t box[2] = {64, (cuuint32_t)boxrows};
  encode(fn, m, ptr, 2, dims, strides, box);
}
void map_w2chunk(PFN_encodeTiled fn, CUtensorMap* m, const void* ptr, int cols, int rows) {
  const cuuint64_t dims[3] = {64, (cuuint64_t)rows, (cuuint64_t)cols / 64}, strides[2] = {(cuuint64_t)cols * 2, 128};
  const cuuint32_t box[3] = {64, 64, 2};
  encode(fn, m, ptr, 3, dims, strides, box);
}
void map_parity(PFN_encodeTiled fn, CUtensorMap* m, const void* ptr, int boxpairs, int boxpar) {
  const cuuint64_t dims[3] = {D_, S_ / 2, 2}, strides[2] = {D_ * 4, D_ * 2};
  const cuuint32_t box[3] = {64, (cuuint32_t)boxpairs, (cuuint32_t)boxpar};
  encode(fn, m, ptr, 3, dims, strides, box);
}

}

extern "C" void kernel_launch(void* const* d_in, const int* in_sizes, int n_in, void* d_out, int out_size) {
  (void)in_sizes; (void)n_in; (void)out_size;
  const bf16* x = (const bf16*)d_in[0];
  const bf16* wqkv = (const bf16*)d_in[1];
  const bf16* wo = (const bf16*)d_in[2];
  const bf16* w1 = (const bf16*)d_in[4];
  const bf16* w3 = (const bf16*)d_in[5];
  const bf16* w2 = (const bf16*)d_in[6];
  const bf16* cvec = (const bf16*)d_in[7];
  const bf16* w_mod = (const bf16*)d_in[8];

  static PFN_encodeTiled fn = nullptr;
  static Maps maps;
  static const void* cached[8] = {};
  static int sms = 0;
  static void* mail = nullptr;
  if (!fn) {
    void* p = nullptr; cudaDriverEntryPointQueryResult st;
    cudaGetDriverEntryPoint("cuTensorMapEncodeTiled", &p, cudaEnableDefault, &st);
    fn = (PFN_encodeTiled)p;
    cudaFuncSetAttribute(fused_block_kernel<0>, cudaFuncAttributeMaxDynamicSharedMemorySize, SM_TOTAL + SM_PROF);
    cudaFuncSetAttribute(fused_block_kernel<1>, cudaFuncAttributeMaxDynamicSharedMemorySize, SM_TOTAL + SM_PROF);
    cudaFuncSetAttribute(fused_block_kernel<2>, cudaFuncAttributeMaxDynamicSharedMemorySize, SM_TOTAL + SM_PROF);
    cudaGetSymbolAddress(&mail, g_mail);
    int dev = 0;
    cudaGetDevice(&dev);
    cudaDeviceGetAttribute(&sms, cudaDevAttrMultiProcessorCount, dev);
  }
  const void* cur[8] = {x, wqkv, wo, w1, w3, w2, d_out, w_mod};
  bool same = true;
  for (int i = 0; i < 8; i++) same = same && cached[i] == cur[i];
  if (!same) {
    void *o, *h2, *hh;
    cudaGetSymbolAddress(&hh, g_hh); cudaGetSymbolAddress(&o, g_o);
    h2 = o;
    map_parity(fn, &maps.x, x, 64, 2); map_parity(fn, &maps.out, d_out, 16, 1);
    map2d(fn, &maps.o, o, D_, S_, 128); map2d(fn, &maps.h2, h2, D_, S_, 128);
    {
      const cuuint64_t dims[3] = {512, (cuuint64_t)S_, 7}, strides[2] = {1024, (cuuint64_t)S_ * 1024};
      const cuuint32_t box[3] = {64, 128, 1};
      encode(fn, &maps.hh, hh, 3, dims, strides, box);
    }
    {
      const cuuint64_t dims[4] = {64, 1024, 16, 2}, strides[3] = {3072 * 2, 128, 2048};
      const cuuint64_t dimv[4] = {64, 1024, 8, 2}, stridev[3] = {3072 * 2, 128, 1024};
      const cuuint32_t box[4] = {64, 64, 1, 2};
      encode(fn, &maps.wqk, wqkv, 4, dims, strides, box);
      encode(fn, &maps.wvv, wqkv + 2048, 4, dimv, stridev, box);
      const cuuint64_t dim1[4] = {1024, 128, 8, 2}, stride1[3] = {3072 * 2, 128 * 3072 * 2, 2048};
      const cuuint32_t box1[4] = {64, 16, 4, 2};
      encode(fn, &maps.wq1, wqkv, 4, dim1, stride1, box1);
    }
    map_w2chunk(fn, &maps.wo, wo, D_, D_); map_w2chunk(fn, &maps.w2, w2, D_, F_);
    map2d(fn, &maps.w1, w1, F_, D_, 64); map2d(fn, &maps.w3, w3, F_, D_, 64);
    map2d(fn, &maps.wmod, w_mod, 6 * D_, D_, 256);
    for (int i = 0; i < 8; i++) cached[i] = cur[i];
  }
  if (sms == NCTA + NAUX) {
    fused_block_kernel<0><<<NCTA + NAUX, 384, SM_TOTAL + SM_PROF>>>(x, cvec, w_mod, (Mail*)mail, 0, maps);
  } else {
    fused_block_kernel<1><<<NAUX, 384, SM_TOTAL + SM_PROF>>>(x, cvec, w_mod, (Mail*)mail, 0, maps);
    fused_block_kernel<2><<<NCTA, 384, SM_TOTAL + SM_PROF>>>(x, cvec, w_mod, (Mail*)mail, 0, maps);
  }
}
```

```cpp
#include <cuda.h>
#include <cuda_runtime.h>
#include <cuda_bf16.h>
#include <stdint.h>

namespace {

typedef __nv_bfloat16 bf16;

constexpr int S_ = 2048, D_ = 1024, F_ = 3584;
constexpr int NCTA = 128, NAUX = 4;

__device__ __align__(1024) bf16 g_o[S_ * D_];
__device__ __align__(1024) bf16 g_hh[S_ * F_];
constexpr int FO_EPOCH = 0, FO_O = 1, FO_H2 = 3, FO_H1 = 11;
constexpr int FL_EPOCH = 16 * 32, FL_LN1 = FL_EPOCH + 2, FL_H2 = FL_EPOCH + 3, FL_O = FL_EPOCH + 4;
struct Mail {
  unsigned flags[32 * 32];
  float mod[8 * 6 * D_];
  uint2 ln1[16 * 8 * 16];
  uint4 halo[2][16 * 16 * 2 * 4 * 32];
  uint4 st2[2][16 * 8 * 8 * 8];
};
__device__ __align__(1024) Mail g_mail;

template <int mode>
__device__ __forceinline__ int cta_role() {
  if (mode) return mode == 1 ? NCTA + (blockIdx.x & 3) : blockIdx.x & 127;
  uint32_t sm;
  asm("mov.u32 %0, %%smid;" : "=r"(sm));
  sm = (sm & ~3u) == 12 ? sm + 108 : (sm & ~3u) == 120 ? sm - 108 : sm;
  const int t = sm >> 1;
  int r;
  if (t < 32) r = (t & 7) * 16 + (t >> 3) * 2 + (sm & 1);
  else if (t < 60) r = (1 + (t - 32) % 7) * 16 + 8 + ((t - 32) / 7) * 2 + (sm & 1);
  else if (t < 62) r = NCTA + sm - 120;
  else r = sm - 116;
  return r;
}
#define PROF(slot, on) do {} while (0)
#define PROFN(slot, on) do {} while (0)
#define PROF_OUT(role, t) do {} while (0)
constexpr uint32_t SM_PROF = 0;

__device__ __forceinline__ uint32_t smem_u32(const void* p) { return (uint32_t)__cvta_generic_to_shared(p); }
#define ELECT "{\n.reg .pred p;\nelect.sync _|p, 0xffffffff;\n@p "
__device__ __forceinline__ void mbar_init_e(uint32_t bar, uint32_t count) {
  asm volatile(ELECT "mbarrier.init.shared::cta.b64 [%0], %1;\n}" :: "r"(bar), "r"(count) : "memory");
}
__device__ __forceinline__ void mbar_expect_tx_e(uint32_t bar, uint32_t bytes) {
  asm volatile(ELECT "mbarrier.arrive.expect_tx.shared::cta.b64 _, [%0], %1;\n}" :: "r"(bar), "r"(bytes) : "memory");
}
__device__ __forceinline__ void mbar_arrive_e(uint32_t bar) {
  asm volatile(ELECT "mbarrier.arrive.shared::cta.b64 _, [%0];\n}" :: "r"(bar) : "memory");
}
__device__ __forceinline__ uint32_t clock32() { uint32_t t; asm volatile("mov.u32 %0, %%clock;" : "=r"(t)); return t; }
__device__ __forceinline__ void mbar_wait(uint32_t bar, uint32_t parity, uint32_t dl) {
  asm volatile("{\n.reg .pred p, q;\n.reg .b32 t;\n"
               "mbarrier.try_wait.parity.shared::cta.b64 p, [%0], %1;\n"
               "@p bra LAB_DONE;\n"
               "LAB_WAIT:\n"
               "mbarrier.try_wait.parity.shared::cta.b64 p, [%0], %1;\n"
               "mov.u32 t, %%clock;\n"
               "sub.s32 t, t, %2;\n"
               "setp.lt.and.s32 q, t, 0, !p;\n"
               "@q bra LAB_WAIT;\n"
               "LAB_DONE:\n}" :: "r"(bar), "r"(parity), "r"(dl) : "memory");
}
__device__ __forceinline__ void mbar_sleep(uint32_t bar, uint32_t parity, uint32_t dl) {
  asm volatile("{\n.reg .pred p;\n.reg .b32 t;\n"
               "LAB_WAIT:\n"
               "mbarrier.try_wait.parity.shared::cta.b64 p, [%0], %1, 20000;\n"
               "@p bra LAB_DONE;\n"
               "mov.u32 t, %%clock;\n"
               "sub.s32 t, t, %2;\n"
               "setp.lt.s32 p, t, 0;\n"
               "@p bra LAB_WAIT;\n"
               "LAB_DONE:\n}" :: "r"(bar), "r"(parity), "r"(dl) : "memory");
}
__device__ __forceinline__ bool poll_done(bool ok, uint32_t dl) {
  return __all_sync(0xffffffffu, ok || (int)(clock32() - dl) >= 0);
}
__device__ __forceinline__ unsigned ld_relaxed(const unsigned* p) {
  unsigned v; asm volatile("ld.relaxed.gpu.global.u32 %0, [%1];" : "=r"(v) : "l"(p) : "memory"); return v;
}
__device__ __forceinline__ void red_add_e(unsigned* p, unsigned v) {
  asm volatile(ELECT "red.relaxed.gpu.global.add.u32 [%0], %1;\n}" :: "l"(p), "r"(v) : "memory");
}
__device__ __forceinline__ void wait_flag(const unsigned* p, unsigned target, uint32_t dl) {
  asm volatile("{\n.reg .pred p;\n.reg .b32 t;\n"
               "LAB_WAIT:\n"
               "ld.relaxed.gpu.global.u32 t, [%0];\n"
               "sub.s32 t, t, %1;\n"
               "setp.ge.s32 p, t, 0;\n"
               "@p bra LAB_DONE;\n"
               "mov.u32 t, %%clock;\n"
               "sub.s32 t, t, %2;\n"
               "setp.lt.s32 p, t, 0;\n"
               "@p bra LAB_WAIT;\n"
               "LAB_DONE:\n}" :: "l"(p), "r"(target), "r"(dl) : "memory");
}
__device__ __forceinline__ void wait_until(uint32_t t) { while ((int)(clock32() - t) < 0) {} }
__device__ __forceinline__ void fence_proxy_async_smem() { asm volatile("fence.proxy.async.shared::cta;" ::: "memory"); }

constexpr uint64_t EVICT_FIRST = 0x12F0000000000000ull;
template <bool STREAM = false>
__device__ __forceinline__ void tma_load_2d(uint32_t dst, const CUtensorMap* m, uint32_t bar, int c0, int c1) {
  if (STREAM)
    asm volatile(ELECT "cp.async.bulk.tensor.2d.shared::cluster.global.mbarrier::complete_tx::bytes.L2::cache_hint [%0], [%1, {%3, %4}], [%2], %5;\n}"
                 :: "r"(dst), "l"(m), "r"(bar), "r"(c0), "r"(c1), "l"(EVICT_FIRST) : "memory");
  else
    asm volatile(ELECT "cp.async.bulk.tensor.2d.shared::cluster.global.mbarrier::complete_tx::bytes [%0], [%1, {%3, %4}], [%2];\n}"
                 :: "r"(dst), "l"(m), "r"(bar), "r"(c0), "r"(c1) : "memory");
}
template <bool STREAM = false>
__device__ __forceinline__ void tma_load_3d(uint32_t dst, const CUtensorMap* m, uint32_t bar, int c0, int c1, int c2) {
  if (STREAM)
    asm volatile(ELECT "cp.async.bulk.tensor.3d.shared::cluster.global.mbarrier::complete_tx::bytes.L2::cache_hint [%0], [%1, {%3, %4, %5}], [%2], %6;\n}"
                 :: "r"(dst), "l"(m), "r"(bar), "r"(c0), "r"(c1), "r"(c2), "l"(EVICT_FIRST) : "memory");
  else
    asm volatile(ELECT "cp.async.bulk.tensor.3d.shared::cluster.global.mbarrier::complete_tx::bytes [%0], [%1, {%3, %4, %5}], [%2];\n}"
                 :: "r"(dst), "l"(m), "r"(bar), "r"(c0), "r"(c1), "r"(c2) : "memory");
}
template <bool STREAM = false>
__device__ __forceinline__ void tma_load_4d(uint32_t dst, const CUtensorMap* m, uint32_t bar, int c0, int c1, int c2, int c3) {
  if (STREAM)
    asm volatile(ELECT "cp.async.bulk.tensor.4d.shared::cluster.global.mbarrier::complete_tx::bytes.L2::cache_hint [%0], [%1, {%3, %4, %5, %6}], [%2], %7;\n}"
                 :: "r"(dst), "l"(m), "r"(bar), "r"(c0), "r"(c1), "r"(c2), "r"(c3), "l"(EVICT_FIRST) : "memory");
  else
    asm volatile(ELECT "cp.async.bulk.tensor.4d.shared::cluster.global.mbarrier::complete_tx::bytes [%0], [%1, {%3, %4, %5, %6}], [%2];\n}"
                 :: "r"(dst), "l"(m), "r"(bar), "r"(c0), "r"(c1), "r"(c2), "r"(c3) : "memory");
}
__device__ __forceinline__ void tma_store_2d(const CUtensorMap* m, uint32_t src, int c0, int c1) {
  asm volatile(ELECT "cp.async.bulk.tensor.2d.global.shared::cta.bulk_group [%0, {%2, %3}], [%1];\n}"
               :: "l"(m), "r"(src), "r"(c0), "r"(c1) : "memory");
}
__device__ __forceinline__ void tma_store_3d(const CUtensorMap* m, uint32_t src, int c0, int c1, int c2) {
  asm volatile(ELECT "cp.async.bulk.tensor.3d.global.shared::cta.bulk_group [%0, {%2, %3, %4}], [%1];\n}"
               :: "l"(m), "r"(src), "r"(c0), "r"(c1), "r"(c2) : "memory");
}
__device__ __forceinline__ void bulk_load(uint32_t dst, const void* src, uint32_t bytes, uint32_t bar) {
  asm volatile(ELECT "cp.async.bulk.shared::cluster.global.mbarrier::complete_tx::bytes [%0], [%1], %2, [%3];\n}"
               :: "r"(dst), "l"(src), "r"(bytes), "r"(bar) : "memory");
}
__device__ __forceinline__ void bulk_prefetch(const void* src, uint32_t bytes) {
  asm volatile(ELECT "cp.async.bulk.prefetch.L2.global [%0], %1;\n}" :: "l"(src), "r"(bytes) : "memory");
}
__device__ __forceinline__ void bulk_commit() { asm volatile("cp.async.bulk.commit_group;" ::: "memory"); }
__device__ __forceinline__ void bulk_wait0() { asm volatile("cp.async.bulk.wait_group 0;" ::: "memory"); }
__device__ __forceinline__ void bulk_wait_read0() { asm volatile("cp.async.bulk.wait_group.read 0;" ::: "memory"); }
__device__ __forceinline__ void prefetch_tmap(const CUtensorMap* m) { asm volatile(ELECT "prefetch.tensormap [%0];\n}" :: "l"(m) : "memory"); }
__device__ __forceinline__ void wgmma_fence() { asm volatile("wgmma.fence.sync.aligned;" ::: "memory"); }
__device__ __forceinline__ void wgmma_commit() { asm volatile("wgmma.commit_group.sync.aligned;" ::: "memory"); }
template <int N> __device__ __forceinline__ void wgmma_wait() { asm volatile("wgmma.wait_group.sync.aligned %0;" :: "n"(N) : "memory"); }
template <int R> __device__ __forceinline__ void reg_alloc() { asm volatile("setmaxnreg.inc.sync.aligned.u32 %0;" :: "n"(R)); }
template <int R> __device__ __forceinline__ void reg_dealloc() { asm volatile("setmaxnreg.dec.sync.aligned.u32 %0;" :: "n"(R)); }
__device__ __forceinline__ void bar_sync(int id, int n) { asm volatile("bar.sync %0, %1;" :: "r"(id), "r"(n) : "memory"); }
__device__ __forceinline__ void bar_arrive(int id, int n) { asm volatile("bar.arrive %0, %1;" :: "r"(id), "r"(n) : "memory"); }
__device__ __forceinline__ void sched_fence(int zero) {
  asm volatile("{\n.reg .pred p;\n.reg .b32 t;\nsetp.eq.s32 p, %0, 0;\n@p bra.uni LAB_S;\n"
               "LAB_F:\nmov.u32 t, %%clock;\nsetp.eq.u32 p, t, 0;\n@p bra LAB_F;\nLAB_S:\n}" :: "r"(zero) : "memory");
}
template <int N> __device__ __forceinline__ void fence_regs(float (&a)[N]) {
  #pragma unroll
  for (int i = 0; i < N; i++) asm volatile("" : "+f"(a[i]) :: "memory");
}
template <int N> __device__ __forceinline__ void undef_regs(float (&a)[N]) {
  #pragma unroll
  for (int i = 0; i < N; i++) asm volatile("" : "=f"(a[i]));
}

__device__ __forceinline__ uint64_t desc_from_lo(uint32_t lo) { return (uint64_t)lo | ((uint64_t)0x40000040u << 32); }
__device__ __forceinline__ uint32_t pack_bf16(float lo, float hi) {
  uint32_t r; asm("cvt.rn.bf16x2.f32 %0, %1, %2;" : "=r"(r) : "f"(hi), "f"(lo)); return r;
}
__device__ __forceinline__ uint32_t fma_bf2(uint32_t a, uint32_t b, uint32_t c) {
  uint32_t d; asm("fma.rn.bf16x2 %0, %1, %2, %3;" : "=r"(d) : "r"(a), "r"(b), "r"(c)); return d;
}
__device__ __forceinline__ float bf_lo(uint32_t v) { return __uint_as_float(v << 16); }
__device__ __forceinline__ float bf_hi(uint32_t v) { return __uint_as_float(v & 0xFFFF0000u); }
__device__ __forceinline__ float bf16_round(float x) { return bf_lo(pack_bf16(x, 0.f)); }
__device__ __forceinline__ void stmatrix_x4(uint32_t addr, uint32_t r0, uint32_t r1, uint32_t r2, uint32_t r3) {
  asm volatile("stmatrix.sync.aligned.m8n8.x4.shared.b16 [%0], {%1, %2, %3, %4};" :: "r"(addr), "r"(r0), "r"(r1), "r"(r2), "r"(r3) : "memory");
}
__device__ __forceinline__ void stmatrix_x4_t(uint32_t addr, uint32_t r0, uint32_t r1, uint32_t r2, uint32_t r3) {
  asm volatile("stmatrix.sync.aligned.m8n8.x4.trans.shared.b16 [%0], {%1, %2, %3, %4};" :: "r"(addr), "r"(r0), "r"(r1), "r"(r2), "r"(r3) : "memory");
}
__device__ __forceinline__ void stmatrix_x4_if(uint32_t addr, uint32_t r0, uint32_t r1, uint32_t r2, uint32_t r3, bool on) {
  asm volatile("{\n.reg .pred p;\nsetp.ne.b32 p, %5, 0;\n@p stmatrix.sync.aligned.m8n8.x4.shared.b16 [%0], {%1, %2, %3, %4};\n}"
               :: "r"(addr), "r"(r0), "r"(r1), "r"(r2), "r"(r3), "r"((int)on) : "memory");
}
__device__ __forceinline__ void ldmatrix_x4(uint32_t addr, uint32_t& r0, uint32_t& r1, uint32_t& r2, uint32_t& r3) {
  asm volatile("ldmatrix.sync.aligned.m8n8.x4.shared.b16 {%0, %1, %2, %3}, [%4];" : "=r"(r0), "=r"(r1), "=r"(r2), "=r"(r3) : "r"(addr) : "memory");
}
__device__ __forceinline__ void ldmatrix_x4_t(uint32_t addr, uint32_t (&r)[4]) {
  asm volatile("ldmatrix.sync.aligned.m8n8.x4.trans.shared.b16 {%0, %1, %2, %3}, [%4];" : "=r"(r[0]), "=r"(r[1]), "=r"(r[2]), "=r"(r[3]) : "r"(addr) : "memory");
}
__device__ __forceinline__ void st_rlx(void* p, uint32_t a, bool on) {
  asm volatile("{\n.reg .pred p;\nsetp.ne.b32 p, %2, 0;\n@p st.relaxed.gpu.global.u32 [%0], %1;\n}" :: "l"(p), "r"(a), "r"((int)on) : "memory");
}
__device__ __forceinline__ void st_rlx_v2(void* p, uint32_t a, uint32_t b, bool on) {
  asm volatile("{\n.reg .pred p;\nsetp.ne.b32 p, %3, 0;\n@p st.relaxed.gpu.global.v2.u32 [%0], {%1, %2};\n}" :: "l"(p), "r"(a), "r"(b), "r"((int)on) : "memory");
}
__device__ __forceinline__ uint2 ld_rlx_v2(const void* p) {
  uint2 v; asm volatile("ld.relaxed.gpu.global.v2.u32 {%0,%1}, [%2];" : "=r"(v.x), "=r"(v.y) : "l"(p) : "memory"); return v;
}
__device__ __forceinline__ void st_rlx_v4(void* p, uint32_t a, uint32_t b, uint32_t c, uint32_t d, bool on) {
  asm volatile("{\n.reg .pred p;\nsetp.ne.b32 p, %5, 0;\n@p st.relaxed.gpu.global.v4.u32 [%0], {%1, %2, %3, %4};\n}"
               :: "l"(p), "r"(a), "r"(b), "r"(c), "r"(d), "r"((int)on) : "memory");
}
__device__ __forceinline__ void st_nonzero_v4(void* p, uint32_t a, uint32_t b, uint32_t c, uint32_t d, bool on) {
  st_rlx_v4(p, max(a, 1u), max(b, 1u), max(c, 1u), max(d, 1u), on);
}
__device__ __forceinline__ uint32_t min4(const uint4& v) { return min(min(v.x, v.y), min(v.z, v.w)); }
__device__ __forceinline__ uint4 ld_rlx_v4(const void* p) {
  uint4 v; asm volatile("ld.relaxed.gpu.global.v4.u32 {%0,%1,%2,%3}, [%4];" : "=r"(v.x), "=r"(v.y), "=r"(v.z), "=r"(v.w) : "l"(p) : "memory"); return v;
}
__device__ __forceinline__ uint32_t movmatrix_t(uint32_t a) {
  uint32_t d; asm volatile("movmatrix.sync.aligned.m8n8.trans.b16 %0, %1;" : "=r"(d) : "r"(a)); return d;
}
__device__ __forceinline__ void mma16(float (&c)[4], uint32_t a0, uint32_t a1, uint32_t a2, uint32_t a3, uint32_t b0, uint32_t b1) {
  asm volatile("mma.sync.aligned.m16n8k16.row.col.f32.bf16.bf16.f32 {%0,%1,%2,%3}, {%4,%5,%6,%7}, {%8,%9}, {%0,%1,%2,%3};"
               : "+f"(c[0]), "+f"(c[1]), "+f"(c[2]), "+f"(c[3]) : "r"(a0), "r"(a1), "r"(a2), "r"(a3), "r"(b0), "r"(b1));
}
__device__ __forceinline__ void sts128(uint32_t addr, uint32_t a, uint32_t b, uint32_t c, uint32_t d) {
  asm volatile("st.shared.v4.b32 [%0], {%1,%2,%3,%4};" :: "r"(addr), "r"(a), "r"(b), "r"(c), "r"(d) : "memory");
}
__device__ __forceinline__ uint4 lds128(uint32_t addr) {
  uint4 v; asm volatile("ld.shared.v4.b32 {%0,%1,%2,%3}, [%4];" : "=r"(v.x), "=r"(v.y), "=r"(v.z), "=r"(v.w) : "r"(addr) : "memory"); return v;
}
__device__ __forceinline__ uint32_t lds32(uint32_t addr) {
  uint32_t v; asm volatile("ld.shared.b32 %0, [%1];" : "=r"(v) : "r"(addr) : "memory"); return v;
}
__device__ __forceinline__ float2 lds64f(uint32_t addr) {
  float2 v; asm volatile("ld.shared.v2.f32 {%0,%1}, [%2];" : "=f"(v.x), "=f"(v.y) : "r"(addr) : "memory"); return v;
}
__device__ __forceinline__ void sts64(uint32_t addr, uint32_t a, uint32_t b) {
  asm volatile("st.shared.v2.b32 [%0], {%1, %2};" :: "r"(addr), "r"(a), "r"(b) : "memory");
}
__device__ __forceinline__ float fast_ex2(float x) { float y; asm("ex2.approx.ftz.f32 %0, %1;" : "=f"(y) : "f"(x)); return y; }
__device__ __forceinline__ float fast_rcp(float x) { float y; asm("rcp.approx.ftz.f32 %0, %1;" : "=f"(y) : "f"(x)); return y; }
__device__ __forceinline__ float fast_rsqrt(float x) { float y; asm("rsqrt.approx.ftz.f32 %0, %1;" : "=f"(y) : "f"(x)); return y; }
__device__ __forceinline__ float silu_f(float g) { return g * fast_rcp(1.f + fast_ex2(g * -1.4426950408889634f)); }
__device__ __forceinline__ float swiglu(float h, float v) {
  float t; asm("tanh.approx.f32 %0, %1;" : "=f"(t) : "f"(h));
  const float p = h * v;
  return fmaf(p, t, p);
}

__device__ __forceinline__ void wgmma_m64n128k16_ss(float (&d)[64], uint64_t descA, uint64_t descB, int scaleD) {
  asm volatile("{\n.reg .pred p;\nsetp.ne.b32 p, %66, 0;\n"
    "wgmma.mma_async.sync.aligned.m64n128k16.f32.bf16.bf16 "
    "{%0, %1, %2, %3, %4, %5, %6, %7, %8, %9, %10, %11, %12, %13, %14, %15, "
    "%16, %17, %18, %19, %20, %21, %22, %23, %24, %25, %26, %27, %28, %29, %30, %31, "
    "%32, %33, %34, %35, %36, %37, %38, %39, %40, %41, %42, %43, %44, %45, %46, %47, "
    "%48, %49, %50, %51, %52, %53, %54, %55, %56, %57, %58, %59, %60, %61, %62, %63}, "
    "%64, %65, p, 1, 1, 0, 1;\n}\n"
    : "+f"(d[0]), "+f"(d[1]), "+f"(d[2]), "+f"(d[3]), "+f"(d[4]), "+f"(d[5]), "+f"(d[6]), "+f"(d[7]),
      "+f"(d[8]), "+f"(d[9]), "+f"(d[10]), "+f"(d[11]), "+f"(d[12]), "+f"(d[13]), "+f"(d[14]), "+f"(d[15]),
      "+f"(d[16]), "+f"(d[17]), "+f"(d[18]), "+f"(d[19]), "+f"(d[20]), "+f"(d[21]), "+f"(d[22]), "+f"(d[23]),
      "+f"(d[24]), "+f"(d[25]), "+f"(d[26]), "+f"(d[27]), "+f"(d[28]), "+f"(d[29]), "+f"(d[30]), "+f"(d[31]),
      "+f"(d[32]), "+f"(d[33]), "+f"(d[34]), "+f"(d[35]), "+f"(d[36]), "+f"(d[37]), "+f"(d[38]), "+f"(d[39]),
      "+f"(d[40]), "+f"(d[41]), "+f"(d[42]), "+f"(d[43]), "+f"(d[44]), "+f"(d[45]), "+f"(d[46]), "+f"(d[47]),
      "+f"(d[48]), "+f"(d[49]), "+f"(d[50]), "+f"(d[51]), "+f"(d[52]), "+f"(d[53]), "+f"(d[54]), "+f"(d[55]),
      "+f"(d[56]), "+f"(d[57]), "+f"(d[58]), "+f"(d[59]), "+f"(d[60]), "+f"(d[61]), "+f"(d[62]), "+f"(d[63])
    : "l"(descA), "l"(descB), "r"(scaleD));
}
__device__ __forceinline__ void wgmma_m64n256k16_rs(float (&d)[128], uint32_t a0, uint32_t a1, uint32_t a2, uint32_t a3, uint64_t descB, int scaleD) {
  asm volatile("{\n.reg .pred p;\nsetp.ne.b32 p, %133, 0;\n"
    "wgmma.mma_async.sync.aligned.m64n256k16.f32.bf16.bf16 "
    "{%0, %1, %2, %3, %4, %5, %6, %7, %8, %9, %10, %11, %12, %13, %14, %15, "
    "%16, %17, %18, %19, %20, %21, %22, %23, %24, %25, %26, %27, %28, %29, %30, %31, "
    "%32, %33, %34, %35, %36, %37, %38, %39, %40, %41, %42, %43, %44, %45, %46, %47, "
    "%48, %49, %50, %51, %52, %53, %54, %55, %56, %57, %58, %59, %60, %61, %62, %63, "
    "%64, %65, %66, %67, %68, %69, %70, %71, %72, %73, %74, %75, %76, %77, %78, %79, "
    "%80, %81, %82, %83, %84, %85, %86, %87, %88, %89, %90, %91, %92, %93, %94, %95, "
    "%96, %97, %98, %99, %100, %101, %102, %103, %104, %105, %106, %107, %108, %109, %110, %111, "
    "%112, %113, %114, %115, %116, %117, %118, %119, %120, %121, %122, %123, %124, %125, %126, %127}, "
    "{%128, %129, %130, %131}, %132, p, 1, 1, 1;\n}\n"
    : "+f"(d[0]), "+f"(d[1]), "+f"(d[2]), "+f"(d[3]), "+f"(d[4]), "+f"(d[5]), "+f"(d[6]), "+f"(d[7]),
      "+f"(d[8]), "+f"(d[9]), "+f"(d[10]), "+f"(d[11]), "+f"(d[12]), "+f"(d[13]), "+f"(d[14]), "+f"(d[15]),
      "+f"(d[16]), "+f"(d[17]), "+f"(d[18]), "+f"(d[19]), "+f"(d[20]), "+f"(d[21]), "+f"(d[22]), "+f"(d[23]),
      "+f"(d[24]), "+f"(d[25]), "+f"(d[26]), "+f"(d[27]), "+f"(d[28]), "+f"(d[29]), "+f"(d[30]), "+f"(d[31]),
      "+f"(d[32]), "+f"(d[33]), "+f"(d[34]), "+f"(d[35]), "+f"(d[36]), "+f"(d[37]), "+f"(d[38]), "+f"(d[39]),
      "+f"(d[40]), "+f"(d[41]), "+f"(d[42]), "+f"(d[43]), "+f"(d[44]), "+f"(d[45]), "+f"(d[46]), "+f"(d[47]),
      "+f"(d[48]), "+f"(d[49]), "+f"(d[50]), "+f"(d[51]), "+f"(d[52]), "+f"(d[53]), "+f"(d[54]), "+f"(d[55]),
      "+f"(d[56]), "+f"(d[57]), "+f"(d[58]), "+f"(d[59]), "+f"(d[60]), "+f"(d[61]), "+f"(d[62]), "+f"(d[63]),
      "+f"(d[64]), "+f"(d[65]), "+f"(d[66]), "+f"(d[67]), "+f"(d[68]), "+f"(d[69]), "+f"(d[70]), "+f"(d[71]),
      "+f"(d[72]), "+f"(d[73]), "+f"(d[74]), "+f"(d[75]), "+f"(d[76]), "+f"(d[77]), "+f"(d[78]), "+f"(d[79]),
      "+f"(d[80]), "+f"(d[81]), "+f"(d[82]), "+f"(d[83]), "+f"(d[84]), "+f"(d[85]), "+f"(d[86]), "+f"(d[87]),
      "+f"(d[88]), "+f"(d[89]), "+f"(d[90]), "+f"(d[91]), "+f"(d[92]), "+f"(d[93]), "+f"(d[94]), "+f"(d[95]),
      "+f"(d[96]), "+f"(d[97]), "+f"(d[98]), "+f"(d[99]), "+f"(d[100]), "+f"(d[101]), "+f"(d[102]), "+f"(d[103]),
      "+f"(d[104]), "+f"(d[105]), "+f"(d[106]), "+f"(d[107]), "+f"(d[108]), "+f"(d[109]), "+f"(d[110]), "+f"(d[111]),
      "+f"(d[112]), "+f"(d[113]), "+f"(d[114]), "+f"(d[115]), "+f"(d[116]), "+f"(d[117]), "+f"(d[118]), "+f"(d[119]),
      "+f"(d[120]), "+f"(d[121]), "+f"(d[122]), "+f"(d[123]), "+f"(d[124]), "+f"(d[125]), "+f"(d[126]), "+f"(d[127])
    : "r"(a0), "r"(a1), "r"(a2), "r"(a3), "l"(descB), "r"(scaleD));
}

constexpr uint32_t MSLOT = 32768, QSLOT = 49152;
constexpr int NM = 6;
constexpr uint32_t SM_X0 = 3 * QSLOT;
constexpr uint32_t SM_XR = SM_X0 + 16384;
constexpr uint32_t SM_STG = 196608;
constexpr uint32_t SM_XCH = SM_STG + 16384;
constexpr uint32_t SM_BAR = SM_STG + 32768;
constexpr uint32_t SM_VEC = SM_BAR + 512;
constexpr uint32_t SM_MODT = SM_VEC;
constexpr uint32_t SM_TOTAL = SM_VEC + 2048;
constexpr uint32_t B_X = SM_BAR  , B_EQ = B_X + 64, B_EM = B_EQ + 32, B_STREQ = B_EM + 48, B_STH = B_STREQ + 8, B_LN = B_STH + 8,
                   B_FQ = B_LN + 8, B_FM = B_FQ + 32, B_MOD = B_FM + 48  , B_GATE = B_MOD + 64, B_STFREE = B_GATE + 8, B_VEC = B_STFREE + 8  ,
                   B_FLG = B_VEC + 16  , B_H2A = B_FLG + 88, B_END = B_H2A + 8;
constexpr int NB_WG = 1  , NB_CONS = 3, NB_ORD = 4  ;
#define PF_BYTES 256
#define X_S1 7
#define X_POLL 3
#define SVC_WAIT mbar_sleep
#define PRD_WAIT mbar_wait
#define WPRE 2
#define QPOS 3
#define AUX_SLOW 84
#define AUX_GAP 500
#define DTAIL 4
#define EF 7
#define TRG_WAIT mbar_wait
#define ST_SPIN0 1
#define AUX_HOLD 3200
#define MSEP 6
#define AUX_URG 4
#define GPRE 5
#define X_UP 1
#define X_GAP 250

struct Maps {
  CUtensorMap x, out;
  CUtensorMap o, h2, hh;
  CUtensorMap wqk, wvv, wq1, wo, w1, w3, w2;
  CUtensorMap wmod;
};

struct Ring { int st; uint32_t ph; int prev; uint32_t dl;
};
__device__ __forceinline__ void ring_next(Ring& r) { if (++r.st == NM) { r.st = 0; r.ph ^= 1; } }

__device__ __forceinline__ void retire_prev(uint32_t rel, bool on) {
  wgmma_commit();
  wgmma_wait<1>();
  if (on) mbar_arrive_e(rel);
}
struct Nop { __device__ __forceinline__ void operator()() const {} };
template <bool REL = true, class F = Nop>
__device__ __forceinline__ void mma_step(float (&acc)[64], uint32_t a, uint32_t b, bool first, uint32_t rel, F urgent = F()) {
  const uint32_t alo = (a >> 4) + (1u << 16), blo = (b >> 4) + (512u << 16);
  wgmma_fence();
  #pragma unroll
  for (int k = 0; k < 4; k++) {
    wgmma_m64n128k16_ss(acc, desc_from_lo(alo + k * 2), desc_from_lo(blo + k * 128), k > 0 || !first);
    if (k == 0) { retire_prev(rel, REL); urgent(); }
  }
  wgmma_commit();
}
__device__ __forceinline__ uint32_t m_wait(uint32_t sbase, const Ring& r) {
  mbar_wait(sbase + B_FM + 8 * r.st, r.ph, r.dl);
  return sbase + r.st * MSLOT;
}
__device__ __forceinline__ uint32_t m_prev(uint32_t sbase, const Ring& r) { return sbase + B_EM + 8 * r.prev; }
__device__ __forceinline__ void m_next(Ring& r) {
  r.prev = r.st; ring_next(r);
}
__device__ __forceinline__ void m_step(float (&acc)[64], uint32_t sbase, uint32_t wgoff, Ring& r, bool first = false) {
  const uint32_t slot = m_wait(sbase, r);
  mma_step(acc, slot + wgoff, slot + 16384, first, m_prev(sbase, r));
  m_next(r);
}

struct LnRow { uint32_t rs[2], nb[2]; };
__device__ __forceinline__ void ln_row(LnRow& l, int h, float mean, float rstd) {
  l.rs[h] = pack_bf16(rstd, rstd);
  const float nb = -mean * bf_lo(l.rs[h]);
  l.nb[h] = pack_bf16(nb, nb);
}
__device__ __forceinline__ uint32_t ln_mod(uint32_t x, const LnRow& l, int h, uint32_t c1, uint32_t s) {
  return fma_bf2(fma_bf2(x, l.rs[h], l.nb[h]), c1, s);
}

__device__ __forceinline__ uint32_t q_wait(int u, uint32_t sbase, uint32_t dl) {
  mbar_wait(sbase + B_FQ + 8 * (u & 3), (u >> 2) & 1, dl);
  return sbase + (u & 3) * QSLOT;
}
__device__ __forceinline__ uint32_t q_empty(int u, uint32_t sbase) { return sbase + B_EQ + 8 * (u & 3); }
struct Frag4 { uint32_t o[4]; };
__device__ __forceinline__ void q_load(uint32_t (&A)[16], uint4 (&p)[4], int kk, uint32_t tile, const Frag4& f, uint32_t t) {
  ldmatrix_x4(tile + f.o[kk], A[4 * kk], A[4 * kk + 1], A[4 * kk + 2], A[4 * kk + 3]);
  p[kk] = lds128(t + kk * 64);
}
__device__ __forceinline__ void q_norm(uint32_t (&A)[16], const uint4 (&p)[4], int kk, const LnRow& l) {
  A[4 * kk + 0] = ln_mod(A[4 * kk + 0], l, 0, p[kk].x, p[kk].z); A[4 * kk + 1] = ln_mod(A[4 * kk + 1], l, 1, p[kk].x, p[kk].z);
  A[4 * kk + 2] = ln_mod(A[4 * kk + 2], l, 0, p[kk].y, p[kk].w); A[4 * kk + 3] = ln_mod(A[4 * kk + 3], l, 1, p[kk].y, p[kk].w);
}
template <bool NEXT>
__device__ __forceinline__ void q_step_rs(float (&acc)[128], uint32_t (&A)[16], uint32_t (&N)[16], uint4 (&p)[4], int u, uint32_t sbase,
                                          const Frag4& f, uint32_t tab, const LnRow& l, uint32_t rot, bool keep, bool first, uint32_t dl, int wg, int zero) {
  const uint32_t slot = first ? sbase : q_wait(u, sbase, dl);
  const uint32_t blo = ((slot + 16384) >> 4) + (512u << 16) + rot * 128 + (zero << (u >> 2)), t = tab + ((u + 1) & 7) * 256;
  #pragma unroll
  for (int kk = 0; kk < 4; kk++) q_norm(A, p, kk, l);
  #pragma unroll
  for (int i = 0; i < 16; i++) asm volatile("" : "+r"(A[i]));
  if (!first) sched_fence(zero);
  if (first) {
    mbar_wait(sbase + B_GATE, 0, dl);
    PROF(6, threadIdx.x == 0);
  }
  if (!(first && wg == 0)) bar_sync(NB_ORD + wg, 256);
  wgmma_fence();
  #pragma unroll
  for (int kk = 0; kk < 4; kk++) {
    wgmma_m64n256k16_rs(acc, A[4 * kk], A[4 * kk + 1], A[4 * kk + 2], A[4 * kk + 3], desc_from_lo(blo ^ (kk * 128)), kk > 0 || !first);
    if (kk == 0) retire_prev(q_empty(u - 1, sbase), !first);
    if (NEXT && kk == 1) {
      if ((u & 1) && u < MSEP) mbar_wait(sbase + B_MOD + 4 * (u + 1), 0, dl);
      #pragma unroll
      for (int q = 0; q < 4; q++) q_load(N, p, q, slot, f, t);
    }
    if (kk == QPOS && (NEXT || wg == 0)) bar_arrive(NB_ORD + (wg ^ 1), 256);
    if (kk == 1) stmatrix_x4_if(sbase + SM_STG + (u >> 3) * 16384 + (f.o[0] ^ (((u >> 1 & 3) ^ rot) << 5)), A[0], A[1], A[2], A[3], keep);
  }
  wgmma_commit();
}

typedef uint32_t Frag8[8];
template <int N> __device__ __forceinline__ void pack_half(Frag8& f, const float (&acc)[N], int off, int half) {
  #pragma unroll
  for (int e = 0; e < 8; e++) { f[e] = pack_bf16(acc[off + 4 * e + 2 * half], acc[off + 4 * e + 2 * half + 1]); asm volatile("" : "+r"(f[e])); }
}
__device__ __forceinline__ void transpose8(Frag8& f) {
  #pragma unroll
  for (int e = 0; e < 8; e++) f[e] = movmatrix_t(f[e]);
}
__device__ __forceinline__ void attn_send(const Frag8& f, int kv, uint32_t xch, int warp, uint4* halo_out, bool has_next) {
  if (warp == 3) {
    st_nonzero_v4(halo_out + kv * 64, f[0], f[1], f[2], f[3], has_next); st_nonzero_v4(halo_out + kv * 64 + 32, f[4], f[5], f[6], f[7], has_next);
  } else {
    sts128(xch + 2048 + kv * 1024, f[0], f[1], f[2], f[3]); sts128(xch + 2048 + kv * 1024 + 512, f[4], f[5], f[6], f[7]);
  }
}
template <int N>
__device__ __forceinline__ void attn_recv(uint4* p, int first, uint32_t xch, int wg, int warp, const uint4* halo_in, bool has_prev) {
  bar_sync(NB_WG + wg, 128);
  #pragma unroll
  for (int e = 0; e < N; e++)
    asm volatile("{\n.reg .pred p, q;\nsetp.ne.b32 p, %6, 0;\nsetp.ne.b32 q, %7, 0;\n"
                 "mov.b32 %0, 0;\nmov.b32 %1, 0;\nmov.b32 %2, 0;\nmov.b32 %3, 0;\n"
                 "@p ld.shared.v4.b32 {%0,%1,%2,%3}, [%4];\n@q ld.relaxed.gpu.global.v4.u32 {%0,%1,%2,%3}, [%5];\n}"
                 : "=&r"(p[e].x), "=&r"(p[e].y), "=&r"(p[e].z), "=&r"(p[e].w)
                 : "r"(xch + (first + e) * 512), "l"(halo_in + (first + e) * 32), "r"((int)(warp > 0)), "r"((int)(warp == 0 && has_prev)) : "memory");
}
template <int N>
__device__ __forceinline__ void attn_check(uint4* p, int first, bool remote, const uint4* halo_in, uint32_t dl) {
  if (remote) {
    while (true) {
      uint32_t m = ~0u;
      #pragma unroll
      for (int e = 0; e < N; e++) m = min(m, min4(p[e]));
      if (poll_done(m != 0, dl)) break;
      #pragma unroll
      for (int e = 0; e < N; e++) p[e] = ld_rlx_v4(halo_in + (first + e) * 32);
    }
  }
}
__device__ __forceinline__ void attn_core(const Frag8& qA, const Frag8& qB, const Frag8& kA, const Frag8& kB, const Frag8& vA, const Frag8& vB,
                                          const uint4* kP, const uint4* vP, bool noprev, int lane, float (&o)[2][5][4]) {
  const int g = lane >> 2, qd = lane & 3;
  const bool s0 = 2 * qd > g, s1 = 2 * qd + 1 > g;
  const uint32_t msk = (s0 ? 0xFFFFu : 0u) | (s1 ? 0xFFFF0000u : 0u);
  constexpr float SC = 0.17677669529663687f * 1.4426950408889634f;
  float s[2][3][4];
  #pragma unroll
  for (int h = 0; h < 2; h++) {
    #pragma unroll
    for (int nb = 0; nb < 3; nb++) s[h][nb][0] = s[h][nb][1] = s[h][nb][2] = s[h][nb][3] = 0.f;
    #pragma unroll
    for (int kk = 0; kk < 2; kk++) {
      const int e = 4 * h + 2 * kk;
      mma16(s[h][1], qA[e], qB[e], qA[e + 1], qB[e + 1], kA[e], kA[e + 1]);
      mma16(s[h][2], qA[e], qB[e], qA[e + 1], qB[e + 1], kB[e], kB[e + 1]);
      mma16(s[h][0], qA[e], qB[e], qA[e + 1], qB[e + 1], kk ? kP[h].z : kP[h].x, kk ? kP[h].w : kP[h].y);
    }
  }
  #pragma unroll
  for (int h = 0; h < 2; h++) {
    float l[4], m[2];
    l[0] = s0 ? (noprev ? -INFINITY : s[h][0][0]) : s[h][1][0];
    l[1] = s1 ? (noprev ? -INFINITY : s[h][0][1]) : s[h][1][1];
    l[2] = s0 ? s[h][1][2] : s[h][2][2];
    l[3] = s1 ? s[h][1][3] : s[h][2][3];
    m[0] = fmaxf(l[0], l[1]); m[1] = fmaxf(l[2], l[3]);
    #pragma unroll
    for (int x = 1; x <= 2; x <<= 1)
      #pragma unroll
      for (int e = 0; e < 2; e++) m[e] = fmaxf(m[e], __shfl_xor_sync(0xffffffffu, m[e], x));
    #pragma unroll
    for (int e = 0; e < 4; e++) l[e] = fast_ex2((l[e] - m[e >> 1]) * SC);
    const uint32_t plo = pack_bf16(l[0], l[1]), phi = pack_bf16(l[2], l[3]);
    const uint32_t vp[4] = {vP[h].x, vP[h].y, vP[h].z, vP[h].w};
    #pragma unroll
    for (int d = 0; d < 5; d++) o[h][d][0] = o[h][d][1] = o[h][d][2] = o[h][d][3] = 0.f;
    mma16(o[h][4], 0x3F803F80u, 0u, 0u, 0x3F803F80u, plo, phi);
    #pragma unroll
    for (int m2 = 0; m2 < 2; m2++) {
      const int e = 4 * h + 2 * m2;
      mma16(o[h][2 * m2], vp[2 * m2], vp[2 * m2 + 1], vA[e], vA[e + 1], plo & msk, plo & ~msk);
      mma16(o[h][2 * m2 + 1], vA[e], vA[e + 1], vB[e], vB[e + 1], phi & msk, phi & ~msk);
    }
  }
}
__device__ __forceinline__ void attn_store(const float (&o)[2][5][4], int h, uint32_t sbase, const Frag4& f) {
  float r[4];
  #pragma unroll
  for (int e = 0; e < 4; e++) r[e] = fast_rcp(o[h][4][e]);
  #pragma unroll
  for (int m = 0; m < 2; m++) {
    const float (&lo)[4] = o[h][2 * m], (&hi)[4] = o[h][2 * m + 1];
    stmatrix_x4_t(sbase + SM_STG + f.o[2 * h + m], pack_bf16(lo[0] * r[0], lo[1] * r[1]), pack_bf16(hi[0] * r[2], hi[1] * r[3]),
                  pack_bf16(lo[2] * r[0], lo[3] * r[1]), pack_bf16(hi[2] * r[2], hi[3] * r[3]));
  }
}

__device__ __forceinline__ void request_store(uint32_t bar) {
  fence_proxy_async_smem();
  mbar_arrive_e(bar);
}

__device__ __forceinline__ void g_switch(float (&cur)[64], float (&prv)[64], int nrest, bool first, int n, uint32_t sbase, uint32_t wgoff,
                                         const Frag4& f, Ring& r) {
  #pragma unroll 1
  for (int i = 1; i < nrest; i++) m_step(prv, sbase, wgoff, r);
  m_step(prv, sbase, wgoff, r);
  m_step(cur, sbase, wgoff, r, first);
  mbar_wait(sbase + B_STFREE, (n - 1) & 1, r.dl);
  fence_regs(prv);
  PROF(28 + n, threadIdx.x == 0);
  #pragma unroll
  for (int jj = 0; jj < 4; jj++) {
    uint32_t p[4];
    #pragma unroll
    for (int e = 0; e < 4; e++) {
      const int i = jj * 8 + e * 2;
      p[e] = pack_bf16(swiglu(prv[i], prv[i + 32]), swiglu(prv[i + 1], prv[i + 33]));
    }
    stmatrix_x4(sbase + SM_STG + f.o[jj], p[0], p[1], p[2], p[3]);
    m_step(cur, sbase, wgoff, r);
  }
  request_store(sbase + B_STREQ);
}

__device__ __forceinline__ uint32_t bad2(uint32_t a, uint32_t b, unsigned par) {
  uint32_t d; asm("lop3.b32 %0, %1, %2, %3, 0x7E;" : "=r"(d) : "r"(a), "r"(b), "r"(par)); return d;
}
__device__ __forceinline__ uint32_t bad4(const uint4& v, unsigned par) { return bad2(v.x, v.y, par) | bad2(v.z, v.w, par); }
__device__ __forceinline__ uint32_t hi_halves(uint32_t lo, uint32_t hi) { return __byte_perm(lo, hi, 0x7632); }

__device__ __forceinline__ void gather_table(const float* src, uint32_t dst, uint32_t bar, unsigned par, uint32_t dl) {
  asm volatile("{\n.reg .pred p, e;\n.reg .b32 s<4>, c<4>, t<4>, w<4>;\n"
               "elect.sync _|e, 0xffffffff;\n"
               "LAB_POLL:\n"
               "ld.relaxed.gpu.global.v4.u32 {s0, s1, s2, s3}, [%0];\n"
               "ld.relaxed.gpu.global.v4.u32 {c0, c1, c2, c3}, [%0 + 4096];\n"
               "prmt.b32 w0, c0, c1, 0x7632;\nprmt.b32 w1, c2, c3, 0x7632;\nprmt.b32 w2, s0, s1, 0x7632;\nprmt.b32 w3, s2, s3, 0x7632;\n"
               "st.shared.v4.b32 [%1], {w0, w1, w2, w3};\n"
               "lop3.b32 t0, s0, s1, %3, 0x7E;\nlop3.b32 t1, s2, s3, %3, 0x7E;\nlop3.b32 t2, c0, c1, %3, 0x7E;\nlop3.b32 t3, c2, c3, %3, 0x7E;\n"
               "lop3.b32 t0, t0, t1, 1, 0xA8;\nlop3.b32 t2, t2, t3, 1, 0xA8;\n"
               "or.b32 t0, t0, t2;\n"
               "setp.eq.u32 p, t0, 0;\n"
               "vote.sync.all.pred p, p, 0xffffffff;\n"
               "@p bra.uni LAB_OK;\n"
               "mov.u32 t0, %%clock;\nsub.s32 t0, t0, %4;\nsetp.lt.s32 p, t0, 0;\n"
               "vote.sync.all.pred p, p, 0xffffffff;\n"
               "@p bra.uni LAB_POLL;\n"
               "LAB_OK:\n"
               "@e mbarrier.arrive.shared::cta.b64 _, [%2];\n}"
               :: "l"(src), "r"(dst), "r"(bar), "r"(par), "r"(dl) : "memory");
}

__device__ __forceinline__ int other_slot(int i, int j) { return i < 4 ? (~j & 4) + i : (j & 4) + i - 4 + (i - 4 >= (j & 3)); }

__device__ __forceinline__ int aux_col(int a, int u) { return u < 8 ? (a & 1) * 1024 + (2 * u + (a >> 1)) * 64 : 2048 + ((u - 8) * 4 + a) * 64; }
constexpr int NA = 7;
constexpr uint32_t A_FULL = SM_BAR, A_EMPTY = SM_BAR + 64, A_SUM = SM_BAR + 128, A_FREE = SM_BAR + 136, SM_RED = SM_VEC;
__device__ __forceinline__ void aux_role(const Maps& maps, const bf16* __restrict__ cvec, Mail* mail0, int zero, int a, uint32_t sbase, int wid) {
  const int tid = threadIdx.x, lane = tid & 31;
  const uint32_t dl = clock32() + 800000000u;
  int st = 0; uint32_t ph = 0;
  if (wid == 8) {
    prefetch_tmap(&maps.wmod);
    #pragma unroll
    for (int i = 0; i < 18; i++) mbar_init_e(sbase + A_FULL + 8 * i, i < 8 ? 1 : i < 17 ? 8 : 2);
    fence_proxy_async_smem();
    bar_arrive(0, 352);
    PROF(39, lane == 0);
    #pragma unroll
    for (int i = 0; i < NA; i++) {
      mbar_expect_tx_e(sbase + A_FULL + 8 * i, 32768);
      tma_load_2d(sbase + i * MSLOT, &maps.wmod, sbase + A_FULL + 8 * i, aux_col(a, i >> 2), (i & 3) * 256);
    }
    PROF(40, lane == 0);
    #pragma unroll 1
    for (int i = NA; i < 96; i++) {
      if (i >= AUX_SLOW) wait_until(clock32() + AUX_GAP);
      if (i == 8) wait_until(dl - 800000000u + AUX_HOLD);
      mbar_wait(sbase + A_EMPTY + 8 * st, ph, dl);
      mbar_expect_tx_e(sbase + A_FULL + 8 * st, 32768);
      tma_load_2d<(EF & 1) != 0>(sbase + st * MSLOT, &maps.wmod, sbase + A_FULL + 8 * st, aux_col(a, i >> 2), (i & 3) * 256);
      if (++st == NA) { st = 0; ph ^= 1; }
    }
  } else if (wid < 8) {
    const int g = lane >> 2, qd = lane & 3;
    uint32_t sc[16];
    const uint2 c = *reinterpret_cast<const uint2*>(cvec + tid * 4);
    sts64(sbase + SM_RED + tid * 8, pack_bf16(silu_f(bf_lo(c.x)), silu_f(bf_hi(c.x))), pack_bf16(silu_f(bf_lo(c.y)), silu_f(bf_hi(c.y))));
    bar_sync(0, 352);
    #pragma unroll
    for (int i = 0; i < 16; i++) sc[i] = lds32(sbase + SM_RED + ((i >> 2) * 256 + wid * 32 + (i & 3) * 8 + qd * 2) * 2);
    bar_sync(NB_CONS, 256);
    PROF(38, tid == 0);
    const uint32_t aoff = (wid * 32 + (lane & 7) + (lane >> 4) * 8) * 128 + ((((lane >> 3) & 1) ^ (lane & 7)) << 4);
    uint32_t w[2][8][4];
    auto fetch = [&](uint32_t (&f)[8][4]) {
      mbar_wait(sbase + A_FULL + 8 * st, ph, dl);
      #pragma unroll
      for (int e = 0; e < 8; e++) ldmatrix_x4_t((sbase + st * MSLOT + aoff + (e >> 2) * 2048) ^ ((e & 3) << 5), f[e]);
      if (++st == NA) { st = 0; ph ^= 1; }
    };
    #pragma unroll 1
    for (int u = 0; u < 24; u++) {
      float acc[4][4];
      #pragma unroll
      for (int m = 0; m < 4; m++) acc[m][0] = acc[m][1] = acc[m][2] = acc[m][3] = 0.f;
      fetch(w[0]);
      #pragma unroll
      for (int q = 0; q < 4; q++) {
        PROF(30 + (u & 1) * 4 + q, u < 2 && tid == 0);
        const uint32_t rel = sbase + A_EMPTY + 8 * (st == 0 ? NA - 1 : st - 1);
        if (q < 3) fetch(w[(q + 1) & 1]);
        uint32_t dep = 0;
        #pragma unroll
        for (int e = 0; e < 8; e++) dep |= w[q & 1][e][0];
        mbar_arrive_e(rel + (dep & zero));
        if (q == 1) mbar_wait(sbase + A_FREE, (u & 1) ^ 1, dl);
        #pragma unroll
        for (int e = 0; e < 8; e++) {
          const uint32_t (&f)[4] = w[q & 1][e];
          mma16(acc[e & 3], f[0], f[1], f[2], f[3], sc[4 * q + 2 * (e >> 2)], sc[4 * q + 2 * (e >> 2) + 1]);
        }
      }
      const float v0 = qd & 2 ? (qd & 1 ? acc[3][0] : acc[2][0]) : (qd & 1 ? acc[1][0] : acc[0][0]);
      const float v1 = qd & 2 ? (qd & 1 ? acc[3][2] : acc[2][2]) : (qd & 1 ? acc[1][2] : acc[0][2]);
      sts64(sbase + SM_RED + wid * 256 + (qd * 8 + g) * 8, __float_as_uint(v0), __float_as_uint(v1));
      mbar_arrive_e(sbase + A_SUM);
      if (u < AUX_URG) mbar_wait(sbase + A_FREE, u & 1, dl);
    }
  } else if (wid < 11) {
    float* const mail = &mail0->mod[(wid - 9) * 4 * 6 * D_ + 2 * lane];
    unsigned par = ld_relaxed(&mail0->flags[FL_EPOCH + (lane >> 5)]);
    bar_sync(0, 352);
    par = (par + 1) & 1;
    #pragma unroll 1
    for (int u = -2; u < 24; u++) {
      if (u >= 0) {
        const int col = aux_col(a, u);
        const float add = (col >> 10) == 1 || (col >> 10) == 4 ? 1.f : 0.f;
        const float mul = col < 3 * D_ ? 1.f : col < 5 * D_ ? 0.5f : 2.f;
        mbar_wait(sbase + A_SUM, u & 1, dl);
        float2 v[8];
        #pragma unroll
        for (int w = 0; w < 8; w++) v[w] = lds64f(sbase + SM_RED + w * 256 + lane * 8);
        const float t0 = ((v[0].x + v[1].x) + (v[2].x + v[3].x)) + ((v[4].x + v[5].x) + (v[6].x + v[7].x));
        const float t1 = ((v[0].y + v[1].y) + (v[2].y + v[3].y)) + ((v[4].y + v[5].y) + (v[6].y + v[7].y));
        mbar_arrive_e(sbase + A_FREE + (__float_as_uint(t0 + t1) & zero));
        const uint32_t w = pack_bf16((add + bf16_round(t0)) * mul, (add + bf16_round(t1)) * mul), o = __shfl_xor_sync(0xffffffffu, w, 1);
        const uint32_t m0 = (lane & 1) ? (o & 0xFFFF0000u) : (w << 16), m1 = (lane & 1) ? (w & 0xFFFF0000u) : (o << 16);
        #pragma unroll
        for (int c = 0; c < 4; c++) st_rlx_v2(mail + c * 6 * D_ + col, m0 | par, m1 | par, true);
        PROF(1 + u, tid == 288);
      }
      #pragma unroll 1
      for (int v = 2 * (u + 2); v < 2 * (u + 3) && v < 24; v++)
        #pragma unroll
        for (int c = 0; c < 4; c++) st_rlx_v2(mail + c * 6 * D_ + aux_col(a, v), par ^ 1, par ^ 1, true);
    }
    const int t = a * 64 + tid - 288;
    #pragma unroll 4
    for (int i = t; i < 16 * 16 * 256; i += 256) mail0->halo[par ^ 1][i] = make_uint4(0, 0, 0, 0);
    #pragma unroll 4
    for (int i = t; i < 16 * 8 * 64; i += 256) mail0->st2[par ^ 1][i] = make_uint4(0, 0, 0, 0);
  }
}

template <int MODE>
__global__ void __launch_bounds__(384, 1)
fused_block_kernel(const bf16* __restrict__ x, const bf16* __restrict__ cvec, const bf16* __restrict__ wmod, Mail* mail0, int zero,
                   const __grid_constant__ Maps maps) {
  extern __shared__ __align__(1024) uint8_t smem_raw[];
  const uint32_t sbase = smem_u32(smem_raw);
  const int tid = threadIdx.x, lane = tid & 31;
  PROFN(0, tid == 0);
  const int wid = __shfl_sync(0xffffffffu, tid >> 5, 0);
  const int b = cta_role<MODE>();
  if (b >= NCTA) { aux_role(maps, cvec, mail0, zero, b - NCTA, sbase, wid); return; }
  const int jg = b >> 6, mb = jg ? 31 - (b >> 2) : (b >> 2), j = 4 * jg + (b & 3);
  const uint32_t dl = clock32() + 800000000u;
  unsigned* const flags = &mail0->flags[mb * 32];
  const int row0 = mb * 128;

  if (wid >= 8) {
    if (wid == 8) {
      #pragma unroll
      for (int i = 0; i < 8; i++) mbar_init_e(sbase + B_X + 8 * i, 1);
      fence_proxy_async_smem();
      #pragma unroll
      for (int q = 0; q < X_UP; q++) {
        mbar_expect_tx_e(sbase + B_X + 8 * q, 4096);
        bulk_load(sbase + SM_XR + q * 4096, x + (size_t)(row0 + j * 16 + 2 * q) * D_, 4096, sbase + B_X + 8 * q);
      }
    } else if (wid == 11) {
      #pragma unroll
      for (int i = 0; i < 12; i++) prefetch_tmap(&maps.x + i);
    } else if (wid == 9) {
      #pragma unroll
      for (uint32_t bar = B_EQ; bar < B_FM; bar += 8) mbar_init_e(sbase + bar, bar < B_FQ ? 8 : bar == B_FQ + 8 || bar == B_FQ + 24 ? 2 : 1);
      fence_proxy_async_smem();
    } else {
      #pragma unroll
      for (uint32_t bar = B_FM; bar < B_END; bar += 8) mbar_init_e(sbase + bar, 1);
      fence_proxy_async_smem();
    }
    bar_sync(0, 384);
    reg_dealloc<40>();
    PROF(92, tid == 256);
    if (wid == 8) {
      uint32_t tnext = clock32();
      #pragma unroll 1
      for (int q = X_UP; q < 8; q++) {
        wait_until(tnext);
        mbar_expect_tx_e(sbase + B_X + 8 * q, 4096);
        bulk_load(sbase + SM_XR + q * 4096, x + (size_t)(row0 + j * 16 + 2 * q) * D_, 4096, sbase + B_X + 8 * q);
        tnext += X_GAP;
      }
      #pragma unroll 1
      for (int u = 0; u < 16; u++) {
        const int st = u & 3;
        if (u == 1) PRD_WAIT(X_S1 < 8 ? sbase + B_X + 8 * X_S1 : sbase + B_MOD, 0, dl);
        if (u == 2) { PRD_WAIT(sbase + B_GATE, 0, dl); PROFN(60, lane == 0); }
        if (u == 3) PRD_WAIT(sbase + B_EQ, 0, dl);
        PRD_WAIT(sbase + B_EQ + 8 * st, ((u >> 2) & 1) ^ 1, dl);
        const uint32_t slot = sbase + st * QSLOT, fb = sbase + B_FQ + 8 * st;
        mbar_expect_tx_e(fb, u == 0 ? 65536 : u == 15 ? 32768 : 49152);
        if ((u & 1) && (u < MSEP || u == 15)) mbar_arrive_e(fb);
        if (u == 0) tma_load_3d(sbase + SM_X0, &maps.x, fb, 0, mb * 64, 0);
        tma_load_4d<(EF & 2) != 0>(slot + 16384, &maps.wqk, fb, 0, u * 64, j, 0);
        tma_load_4d<(EF & 2) != 0>(slot + 32768, &maps.wvv, fb, 0, u * 64, j, 0);
        if (u < 15) tma_load_3d(slot, &maps.x, fb, u * 64 + 64, mb * 64, 0);
      }
      const unsigned e1 = 1 + ld_relaxed(flags + FO_EPOCH);
      Ring r{0, 1, 0, dl};
      uint32_t slot, fb;
      auto acquire = [&](uint32_t bytes) {
        PRD_WAIT(sbase + B_EM + 8 * r.st, r.ph, dl);
        slot = sbase + r.st * MSLOT; fb = sbase + B_FM + 8 * r.st;
        mbar_expect_tx_e(fb, bytes);
        ring_next(r);
      };
      #pragma unroll 1
      for (int kt = 0; kt < 16; kt++) {
        if (kt < 5) PRD_WAIT(sbase + B_EQ + 8 * (kt - (kt >= 2)), 1, dl);
        if ((kt & 7) == 0) { PROF(46, lane == 0 && kt == 8); PRD_WAIT(sbase + B_FLG + kt, 0, dl); PROF(47, lane == 0 && kt == 8); }
        acquire(32768);
        tma_load_4d<(EF & 2) != 0>(slot + 16384, &maps.wq1, fb, (j + 8) * 64, (kt & 1) * 64 + (kt & 6) * 8, (kt >> 3) * 4, 0);
        tma_load_3d(slot, &maps.hh, fb, (kt & 7) * 64, row0, kt >> 3);
      }
      PROF(82, lane == 0);
      PRD_WAIT(sbase + B_FLG + 16, 0, dl);
      PROF(83, lane == 0);
      #pragma unroll 1
      for (int kt = 0; kt < 8; kt++) {
        if (kt == 4) {
          acquire(32768);
          tma_load_3d(slot, &maps.x, fb, j * 128, mb * 64, 0);
          tma_load_3d(slot + 16384, &maps.x, fb, j * 128 + 64, mb * 64, 0);
        }
        acquire(32768);
        tma_load_3d<(EF & 2) != 0>(slot + 16384, &maps.wo, fb, 0, kt * 64, 2 * j);
        tma_load_2d(slot, &maps.o, fb, kt * 64, row0);
      }
      acquire(16384);
      tma_load_3d<(EF & 2) != 0>(slot + 16384, &maps.wo, fb, 0, (8 + j) * 64, 2 * j);
      {
        constexpr int NPRE = WPRE;
        Ring ra = r;
        #pragma unroll 1
        for (int i = 0; i < 7; i++) {
          const int kt = 8 + other_slot(i, j);
          acquire(32768);
          tma_load_3d<(EF & 2) != 0>(slot + 16384, &maps.wo, fb, 0, kt * 64, 2 * j);
          if (i == NPRE - 1) {
            wait_flag(&mail0->flags[FL_O], e1 * NCTA, dl);
            PROFN(61, lane == 0);
            #pragma unroll 1
            for (int q = 0; q < NPRE - 1; q++) { tma_load_2d(sbase + ra.st * MSLOT, &maps.o, sbase + B_FM + 8 * ra.st, (8 + other_slot(q, j)) * 64, row0); ring_next(ra); }
          }
          if (i >= NPRE - 1) tma_load_2d(slot, &maps.o, fb, kt * 64, row0);
        }
      }
      #pragma unroll 1
      for (int t = 0; t < 2; t++) {
        acquire(32768);
        tma_load_2d<(EF & 4) != 0>(slot, &maps.w1, fb, j * 64, (2 * j + t) * 64);
        tma_load_2d<(EF & 4) != 0>(slot + 8192, &maps.w3, fb, j * 64, (2 * j + t) * 64);
        tma_load_2d<(EF & 4) != 0>(slot + 16384, &maps.w1, fb, (8 + j) * 64, (2 * j + t) * 64);
        tma_load_2d<(EF & 4) != 0>(slot + 24576, &maps.w3, fb, (8 + j) * 64, (2 * j + t) * 64);
      }
      {
        Ring ra = r;
        #pragma unroll 1
        for (int i = 0; i < GPRE; i++) {
          const int kt = 2 * other_slot(i, j);
          acquire(32768);
          tma_load_2d<(EF & 4) != 0>(slot + 16384, &maps.w1, fb, j * 64, kt * 64);
          tma_load_2d<(EF & 4) != 0>(slot + 24576, &maps.w3, fb, j * 64, kt * 64);
        }
        wait_flag(&mail0->flags[FL_H2], e1 * NCTA, dl);
        PROFN(62, lane == 0);
        mbar_arrive_e(sbase + B_H2A);
        #pragma unroll 1
        for (int i = 0; i < GPRE; i++) { tma_load_2d(sbase + ra.st * MSLOT, &maps.h2, sbase + B_FM + 8 * ra.st, other_slot(i, j) * 128, row0); ring_next(ra); }
      }
      #pragma unroll 1
      for (int gt = 0; gt < 7; gt++) {
        const int ncol = (8 * gt + j) * 64;
        #pragma unroll 1
        for (int i = (gt == 0 ? GPRE : 0); i < (gt < 2 ? 14 : 16); i++) {
          const int kt = gt >= 2 ? i : i < 7 ? 2 * other_slot(i, j) : 2 * other_slot(i - 7, j) + 1;
          if (gt == 0 && i == 7) PRD_WAIT(sbase + B_FLG + 24, 0, dl);
          acquire(32768);
          tma_load_2d<(EF & 4) != 0>(slot + 16384, &maps.w1, fb, ncol, kt * 64);
          tma_load_2d<(EF & 4) != 0>(slot + 24576, &maps.w3, fb, ncol, kt * 64);
          tma_load_2d(slot, &maps.h2, fb, kt * 64, row0);
        }
      }
      #pragma unroll 1
      for (int kt = 0; kt < 56; kt++) {
        if ((kt & 7) == 0) PRD_WAIT(sbase + B_FLG + 32 + kt, 0, dl);
        acquire(32768);
        tma_load_3d<(EF & 8) != 0>(slot + 16384, &maps.w2, fb, 0, kt * 64, 2 * j);
        tma_load_3d<(EF & 16) != 0>(slot, &maps.hh, fb, (kt & 7) * 64, row0, kt >> 3);
      }
    } else {
      const unsigned e1 = 1 + ld_relaxed(wid == 9 ? flags + FO_EPOCH : &mail0->flags[FL_EPOCH]), par = e1 & 1;
      if (wid == 9) {
        #pragma unroll 1
        for (int n = 0; n < 12; n++) {
          if (n == 4) {
            mbar_wait(sbase + B_STH, 0, dl);
            tma_store_2d(&maps.h2, sbase + SM_STG, j * 128, row0);
            bulk_commit();
            bulk_wait0();
            red_add_e(&mail0->flags[FL_H2], 1);
            PROF(84, lane == 0);
            mbar_wait(sbase + B_H2A, 0, dl);
          }
          if (n >= ST_SPIN0 && n <= 4) mbar_wait(sbase + B_STREQ, n & 1, dl); else SVC_WAIT(sbase + B_STREQ, n & 1, dl);
          if (n == 0) fence_proxy_async_smem();
          if (n == 2 || n == 3) tma_store_2d(&maps.o, sbase + SM_STG, (j + 8 * (n - 2)) * 64, row0);
          else if (n == 4) tma_store_2d(&maps.h2, sbase + SM_STG + 16384, j * 128 + 64, row0);
          else tma_store_3d(&maps.hh, sbase + SM_STG + (n == 1 ? 16384 : 0), j * 64, row0, n < 2 ? n : n - 5);
          bulk_commit();
          bulk_wait0();
          red_add_e(n == 3 ? &mail0->flags[FL_O] : flags + (n < 2 ? FO_H1 + n : n - 1), 1);
          mbar_arrive_e(sbase + B_STFREE);
          PROFN(70 + n, lane == 0 && n > 0); PROF(85, lane == 0 && n == 0);
        }
      } else {
        mbar_wait(sbase + B_X + 8 * X_POLL, 0, dl);
        const float* const mail = &mail0->mod[(b & 7) * 6 * D_ + lane * 4];
        if (wid == 10) {
          #pragma unroll 1
          for (int p = 0; p < 8; p++) {
            if (p >= 2) TRG_WAIT(p == 2 ? q_empty(0, sbase) : q_empty(2 * p - 5, sbase), p == 2 ? 0 : ((2 * p - 5) >> 2) & 1, dl);
            gather_table(mail + p * 128, sbase + SM_MODT + (p & 3) * 512 + ((lane * 16) ^ ((j >> 1) << 6)), 2 * p - 1 < MSEP ? sbase + B_MOD + 8 * p : sbase + B_FQ + 8 * ((2 * p - 1) & 3), par, dl);
            PROF(63 + p, lane == 0 && p < 7);
          }
          const uint32_t vdst = sbase + SM_VEC + (lane >> 3) * 64 + (lane & 3) * 16 + ((lane >> 2) & 1) * 8;
          #pragma unroll 1
          for (int v = 0; v < 2; v++) {
            SVC_WAIT(sbase + B_FLG + 16 + 16 * v, 0, dl);
            uint4 m[3];
            while (true) {
              #pragma unroll
              for (int e = 0; e < 3; e++) m[e] = ld_rlx_v4(mail + (2 + v + e) * 1024 + j * 128);
              if (poll_done(((bad4(m[0], par) | bad4(m[1], par) | bad4(m[2], par)) & 1) == 0, dl)) break;
              __nanosleep(200);
            }
            #pragma unroll
            for (int e = 0; e < 3; e++) sts64(vdst + (v + e) * 256, hi_halves(m[e].x, m[e].y), hi_halves(m[e].z, m[e].w));
            mbar_arrive_e(sbase + B_VEC + 8 * v);
            PROF(70, lane == 0 && v == 0);
          }
        } else {
          mbar_wait(sbase + B_LN, 0, dl);
          red_add_e(&mail0->flags[FL_LN1], 1);
          wait_flag(&mail0->flags[FL_LN1], e1 * NCTA, dl);
          mbar_arrive_e(sbase + B_GATE);
          PROF(41, lane == 0);
          #pragma unroll 1
          for (int i = 0; i < 11; i++) {
            const unsigned* f = flags + (i < 2 ? FO_H1 + i : i == 2 ? FO_O : FO_H2 + i - 3);
            if (i == 3) SVC_WAIT(sbase + B_H2A, 0, dl);
            while (!poll_done((int)(ld_relaxed(f) - e1 * 8) >= 0, dl)) { if (i > 3 || i == 0) __nanosleep(200); }
            mbar_arrive_e(sbase + B_FLG + 8 * i);
          }
        }
      }
    }
  } else {
    const int wg = wid >> 2, warp = wid & 3;
    const int g = lane >> 2, qd = lane & 3;
    bulk_prefetch(wmod + (size_t)(b * 8 + wid) * (6 * D_), PF_BYTES);
    bulk_prefetch(wmod + (size_t)(b * 8 + wid) * (6 * D_) + D_, PF_BYTES);
    bar_sync(0, 384);
    bulk_prefetch(wmod + (size_t)(b * 8 + wid) * (6 * D_) + PF_BYTES / 2, PF_BYTES);
    bulk_prefetch(wmod + (size_t)(b * 8 + wid) * (6 * D_) + PF_BYTES / 2 + D_, PF_BYTES);
    const unsigned e1 = 1 + ld_relaxed(flags + FO_EPOCH), par = e1 & 1;
    reg_alloc<232>();
    PROF(1, tid == 0);
    const uint32_t wgoff = wg * 8192;
    const uint32_t frag0 = wid * 2048 + (lane & 15) * 128 + (((lane >> 4) ^ (lane & 7)) << 4);
    const uint32_t slab = sbase + SM_STG + wid * 2048;

    LnRow ln;
    {
      uint2* const lmail = &mail0->ln1[(mb * 8 + (lane & 1) * 4 + (j >> 1)) * 16 + (j & 1) * 8 + wid];
      st_rlx_v2(lmail, par ^ 1, par ^ 1, lane < 2);
      mbar_wait(sbase + B_X + 8 * wid, 0, dl);
      PROF(3, tid == 224); PROF(93, tid == 0);
      float s[2][2] = {{0.f, 0.f}, {0.f, 0.f}}, q2[2][2] = {{0.f, 0.f}, {0.f, 0.f}};
      #pragma unroll
      for (int c = 0; c < 8; c++) {
        const uint4 v = lds128(sbase + SM_XR + wid * 4096 + c * 512 + lane * 16);
        const uint32_t vv[4] = {v.x, v.y, v.z, v.w};
        #pragma unroll
        for (int e = 0; e < 4; e++) {
          const float lo = bf_lo(vv[e]), hi = bf_hi(vv[e]);
          s[c >> 2][0] += lo; s[c >> 2][1] += hi; q2[c >> 2][0] = fmaf(lo, lo, q2[c >> 2][0]); q2[c >> 2][1] = fmaf(hi, hi, q2[c >> 2][1]);
        }
      }
      const bool odd = lane & 1;
      float sm = (s[0][0] + s[0][1]), so = (s[1][0] + s[1][1]), qm = (q2[0][0] + q2[0][1]), qo = (q2[1][0] + q2[1][1]);
      { const float a = odd ? so : sm, c = odd ? qo : qm;
        sm = a + __shfl_xor_sync(0xffffffffu, odd ? sm : so, 1); qm = c + __shfl_xor_sync(0xffffffffu, odd ? qm : qo, 1); }
      #pragma unroll
      for (int o = 2; o < 32; o <<= 1) { sm += __shfl_xor_sync(0xffffffffu, sm, o); qm += __shfl_xor_sync(0xffffffffu, qm, o); }
      sm *= (1.f / D_);
      ln_row(ln, 0, sm, fast_rsqrt(fmaxf(qm * (1.f / D_) - sm * sm, 0.f) + 1e-5f));
      st_rlx_v2(lmail, (ln.rs[0] << 16) | par, (ln.nb[0] << 16) | par, lane < 2);
      mbar_arrive_e(sbase + B_LN);
      PROF(4, tid == 224);
    }

    uint4* const halo_out = mail0->halo[par] + ((mb * 16 + j) * 2 + wg) * 128 + lane;
    const uint4* const halo_in = halo_out - 16 * 256;
    const uint32_t xch = sbase + SM_XCH + (tid >> 5) * 2048 + lane * 16;
    const bool noprev = mb == 0 && warp == 0, remote = mb > 0 && warp == 0;
    float a0[64], a1[64];
    uint32_t x2[32];
    Ring r{zero, 0, 0, dl};
    Frag8 qA, qB, kA, kB, vA, vB, wA, wB;
    {
      float acc[128];
      uint32_t A0[16], A1[16];
      undef_regs(acc);
      const uint32_t tab = sbase + SM_MODT + qd * 16;
      uint4 p[4];
      const uint32_t rot = j >> 1;
      Frag4 fq;
      #pragma unroll
      for (int q = 0; q < 4; q++) fq.o[q] = frag0 ^ ((q ^ rot) << 5);
      mbar_wait(sbase + B_LN, 0, dl);
      const uint2* const lin = &mail0->ln1[(mb * 8 + wid) * 16 + g];
      uint2 v0, v1;
      do { v0 = ld_rlx_v2(lin); v1 = ld_rlx_v2(lin + 8); } while (!poll_done(((bad2(v0.x, v0.y, par) | bad2(v1.x, v1.y, par)) & 1) == 0, dl));
      ln.rs[0] = hi_halves(v0.x, v0.x); ln.nb[0] = hi_halves(v0.y, v0.y); ln.rs[1] = hi_halves(v1.x, v1.x); ln.nb[1] = hi_halves(v1.y, v1.y);
      q_wait(0, sbase, dl);
      mbar_wait(sbase + B_MOD, 0, dl);
      #pragma unroll
      for (int kk = 0; kk < 4; kk++) q_load(A0, p, kk, sbase + SM_X0, fq, tab);
      PROF(5, tid == 0);
      q_step_rs<true>(acc, A0, A1, p, 0, sbase, fq, tab, ln, rot, !(j & 1), true, dl, wg, zero);
      #pragma unroll
      for (int u = 1; u < 15; u += 2) {
        q_step_rs<true>(acc, A1, A0, p, u, sbase, fq, tab, ln, rot, j & 1, false, dl, wg, zero);
        q_step_rs<true>(acc, A0, A1, p, u + 1, sbase, fq, tab, ln, rot, !(j & 1), false, dl, wg, zero);
        if (u == 7) mbar_arrive_e(sbase + B_STREQ);
      }
      q_step_rs<false>(acc, A1, A0, p, 15, sbase, fq, tab, ln, rot, j & 1, false, dl, wg, zero);
      PROF(7, tid == 0);
      mbar_wait(sbase + B_STFREE, 0, dl);
      request_store(sbase + B_STREQ);
      wgmma_wait<0>();
      undef_regs(a0);
      { const uint32_t slot = m_wait(sbase, r); mma_step(a0, slot + wgoff, slot + 16384, true, q_empty(15, sbase)); m_next(r); }
      fence_regs(acc);
      PROF(8, tid == 0);
      sched_fence(zero);
      pack_half(vB, acc, 64, 1); transpose8(vB);
      m_step(a0, sbase, wgoff, r);
      sched_fence(zero);
      pack_half(kB, acc, 32, 1);
      attn_send(vB, 1, xch - 16384, warp, halo_out, mb < 15); attn_send(kB, 0, xch - 16384, warp, halo_out, mb < 15);
      m_step(a0, sbase, wgoff, r);
      sched_fence(zero);
      pack_half(qA, acc, 0, 0); pack_half(qB, acc, 0, 1); pack_half(kA, acc, 32, 0); pack_half(wB, acc, 96, 1); pack_half(wA, acc, 96, 0);
      m_step(a0, sbase, wgoff, r);
      sched_fence(zero);
      pack_half(vA, acc, 64, 0); transpose8(vA);
    }
    uint4 wP[2];
    Frag4 frag;
    #pragma unroll
    for (int q = 0; q < 4; q++) frag.o[q] = frag0 ^ (q << 5);
    {
      m_step(a0, sbase, wgoff, r);
      uint4 pv[4];
      attn_recv<4>(pv, 0, xch - 16384, wg, warp, halo_in, mb > 0);
      m_step(a0, sbase, wgoff, r);
      mbar_wait(sbase + B_STFREE, 1, dl);
      transpose8(wB);
      m_step(a0, sbase, wgoff, r);
      attn_check<4>(pv, 0, remote, halo_in, dl);
      wgmma_wait<0>();
      PROF(9, tid == 0);
      float o[2][5][4];
      sched_fence(zero);
      attn_core(qA, qB, kA, kB, vA, vB, pv, pv + 2, noprev, lane, o);
      attn_store(o, 0, sbase, frag);
      attn_store(o, 1, sbase, frag);
      request_store(sbase + B_STREQ);
      bar_sync(NB_CONS, 256);
      PROF(10, tid == 0);
      m_step(a0, sbase, wgoff, r);
      sched_fence(zero);
      attn_send(wB, 1, xch, warp, halo_out + 8 * 256, mb < 15);
      m_step(a0, sbase, wgoff, r);
      sched_fence(zero);
      transpose8(wA);
      #pragma unroll 1
      for (int i = 9; i < 15; i++) m_step(a0, sbase, wgoff, r);
      attn_recv<2>(wP, 2, xch, wg, warp, halo_in + 8 * 256, mb > 0);
      m_step(a0, sbase, wgoff, r);
    }
    {
      undef_regs(a1);
      {
        const uint32_t slot = m_wait(sbase, r);
        mma_step(a1, slot + wgoff, slot + 16384, true, m_prev(sbase, r), [&] {
          fence_regs(a0);
          pack_half(kB, a0, 32, 1);
          attn_send(kB, 0, xch, warp, halo_out + 8 * 256, mb < 15);
        });
        m_next(r);
      }
      PROF(14, tid == 0);
      sched_fence(zero);
      pack_half(kA, a0, 32, 0); pack_half(qA, a0, 0, 0); pack_half(qB, a0, 0, 1);
      m_step(a1, sbase, wgoff, r);
      attn_check<2>(wP, 2, remote, halo_in + 8 * 256, dl);
      uint4 kP[2];
      attn_recv<2>(kP, 0, xch, wg, warp, halo_in + 8 * 256, mb > 0);
      m_step(a1, sbase, wgoff, r);
      attn_check<2>(kP, 0, remote, halo_in + 8 * 256, dl);
      wgmma_wait<0>();
      PROF(15, tid == 0);
      float o[2][5][4];
      mbar_wait(sbase + B_STFREE, 0, dl);
      attn_core(qA, qB, kA, kB, wA, wB, kP, wP, noprev, lane, o);
      attn_store(o, 0, sbase, frag);
      attn_store(o, 1, sbase, frag);
      request_store(sbase + B_STREQ);
      bar_sync(NB_CONS, 256);
      PROF(16, tid == 0);
      auto residual = [&] {
        const uint32_t xs = m_wait(sbase, r), xe = sbase + B_EM + 8 * r.st;
        ring_next(r);
        #pragma unroll
        for (int t = 0; t < 2; t++) {
          #pragma unroll
          for (int jj = 4 * t; jj < 4 * t + 4; jj++) ldmatrix_x4(xs + t * 16384 + frag.o[jj & 3], x2[4 * jj], x2[4 * jj + 1], x2[4 * jj + 2], x2[4 * jj + 3]);
          if (t == 1) {
            uint32_t dep = 0;
            #pragma unroll
            for (int jj = 0; jj < 8; jj++) dep |= x2[4 * jj];
            mbar_arrive_e(xe + (dep & zero));
          }
          m_step(a1, sbase, wgoff, r);
        }
      };
      m_step(a1, sbase, wgoff, r);
      residual();
      #pragma unroll 1
      for (int i = 6; i < 8; i++) m_step(a1, sbase, wgoff, r);
      mma_step(a1, sbase + SM_STG + wgoff, m_wait(sbase, r) + 16384, false, m_prev(sbase, r));
      m_next(r);
      PROF(17, tid == 0);
      uint4* const sm = mail0->st2[par] + (mb * 8 + wid) * 64 + g;
      st_rlx_v4(sm + j * 8, 0, 0, 0, 0, qd == (g >> 1));
      #pragma unroll 1
      for (int i = 0; i < 7; i++) { m_step(a1, sbase, wgoff, r); PROF(42, tid == 0 && i == 0); }
      PROF(45, tid == 0);
      mbar_wait(sbase + B_VEC, 0, dl);
      mbar_wait(sbase + B_STFREE, 1, dl);
      const uint32_t vec = sbase + SM_VEC + qd * 16;
      uint4 ga[4];
      #pragma unroll
      for (int q = 0; q < 4; q++) ga[q] = lds128(vec + q * 64);
      wgmma_wait<0>();
      mbar_arrive_e(m_prev(sbase, r));
      fence_regs(a1);
      PROF(18, tid == 0);
      float gl[4] = {0.f, 0.f, 0.f, 0.f}, gh[4] = {0.f, 0.f, 0.f, 0.f};
      #pragma unroll
      for (int jj = 0; jj < 8; jj++) {
        uint32_t* v = &x2[4 * jj];
        const uint32_t wl = (jj & 1) ? ga[jj >> 1].z : ga[jj >> 1].x, wh = (jj & 1) ? ga[jj >> 1].w : ga[jj >> 1].y;
        #pragma unroll
        for (int e = 0; e < 4; e++) v[e] = fma_bf2(e & 2 ? wh : wl, pack_bf16(a1[8 * jj + 2 * e], a1[8 * jj + 2 * e + 1]), v[e]);
        mma16(gl, v[0], 0x3F803F80u, v[2], 0x3F803F80u, v[0], v[2]);
        mma16(gh, v[1], 0x3F803F80u, v[3], 0x3F803F80u, v[1], v[3]);
      }
      st_nonzero_v4(sm + j * 8, __float_as_uint(g & 1 ? gl[3] : gl[2]), __float_as_uint(g & 1 ? gl[1] : gl[0]),
                __float_as_uint(g & 1 ? gh[3] : gh[2]), __float_as_uint(g & 1 ? gh[1] : gh[0]), qd == (g >> 1));
      float s[2], q2[2];
      PROF(19, tid == 0);
      uint4 sb[4], cb[4];
      #pragma unroll
      for (int q = 0; q < 4; q++) { sb[q] = lds128(vec + 256 + q * 64); cb[q] = lds128(vec + 512 + q * 64); }
      uint4 p0, p1;
      while (true) {
        p0 = ld_rlx_v4(sm + qd * 16); p1 = ld_rlx_v4(sm + qd * 16 + 8);
        if (poll_done(min(min4(p0), min4(p1)) != 0, dl)) break;
      }
      PROF(20, tid == 0);
      s[0] = __uint_as_float(p0.x) + __uint_as_float(p1.x); q2[0] = __uint_as_float(p0.y) + __uint_as_float(p1.y);
      s[1] = __uint_as_float(p0.z) + __uint_as_float(p1.z); q2[1] = __uint_as_float(p0.w) + __uint_as_float(p1.w);
      #pragma unroll
      for (int o2 = 1; o2 <= 2; o2 <<= 1)
        #pragma unroll
        for (int h = 0; h < 2; h++) { s[h] += __shfl_xor_sync(0xffffffffu, s[h], o2); q2[h] += __shfl_xor_sync(0xffffffffu, q2[h], o2); }
      #pragma unroll
      for (int h = 0; h < 2; h++) {
        const float m = s[h] * (1.f / D_);
        ln_row(ln, h, m, fast_rsqrt(fmaxf(q2[h] * (1.f / D_) - m * m, 0.f) + 1e-5f));
      }
      #pragma unroll
      for (int jj = 0; jj < 8; jj++) {
        const uint32_t cl = (jj & 1) ? cb[jj >> 1].z : cb[jj >> 1].x, ch = (jj & 1) ? cb[jj >> 1].w : cb[jj >> 1].y;
        const uint32_t sl = (jj & 1) ? sb[jj >> 1].z : sb[jj >> 1].x, sh = (jj & 1) ? sb[jj >> 1].w : sb[jj >> 1].y;
        stmatrix_x4(sbase + SM_STG + (jj >> 2) * 16384 + frag.o[jj & 3], ln_mod(x2[4 * jj], ln, 0, cl, sl), ln_mod(x2[4 * jj + 1], ln, 1, cl, sl),
                    ln_mod(x2[4 * jj + 2], ln, 0, ch, sh), ln_mod(x2[4 * jj + 3], ln, 1, ch, sh));
        if (jj == 3) { request_store(sbase + B_STH); sched_fence(zero); }
      }
      request_store(sbase + B_STREQ);
      bar_sync(NB_WG + wg, 128);
      PROF(21, tid == 0);
    }

    undef_regs(a0);
    #pragma unroll
    for (int t = 0; t < 2; t++) {
      const uint32_t slot = m_wait(sbase, r);
      if (t == 0) mma_step<false>(a0, sbase + SM_STG + wgoff, slot, true, 0);
      else mma_step(a0, sbase + SM_STG + 16384 + wgoff, slot, false, m_prev(sbase, r));
      mma_step<false>(a1, sbase + SM_STG + t * 16384 + wgoff, slot + 16384, t == 0, 0);
      m_next(r);
    }
    PROF(22, tid == 0);
    #pragma unroll 1
    for (int t = 0; t < 7; t += 2) {
      g_switch(a1, a0, t == 0 ? 14 : 11, t > 0, 5 + t, sbase, wgoff, frag, r);
      if (t == 6) break;
      g_switch(a0, a1, t == 0 ? 9 : 11, true, 6 + t, sbase, wgoff, frag, r);
    }
    #pragma unroll 1
    for (int i = 5; i < 56 - DTAIL; i++) m_step(a1, sbase, wgoff, r);
    if (DTAIL) {
      if (wg == 1) { wgmma_wait<0>(); mbar_arrive_e(m_prev(sbase, r)); bar_sync(NB_ORD, 256); }
      #pragma unroll
      for (int i = 0; i < DTAIL; i++) {
        const uint32_t slot = m_wait(sbase, r);
        const uint32_t alo = ((slot + wgoff) >> 4) + (1u << 16), blo = ((slot + 16384) >> 4) + (512u << 16);
        wgmma_fence();
        #pragma unroll
        for (int k = 0; k < 4; k++) wgmma_m64n128k16_ss(a1, desc_from_lo(alo + k * 2), desc_from_lo(blo + k * 128), true);
        wgmma_commit();
        ring_next(r);
      }
      if (wg == 0) bar_arrive(NB_ORD, 256);
    }
    {
      mbar_wait(sbase + B_STFREE, 1, dl);
      mbar_wait(sbase + B_VEC + 8, 0, dl);
      uint4 gb[4];
      #pragma unroll
      for (int q = 0; q < 4; q++) gb[q] = lds128(sbase + SM_VEC + 768 + qd * 16 + q * 64);
      wgmma_wait<0>();
      fence_regs(a1);
      PROF(50, tid == 128);
      #pragma unroll
      for (int t = 0; t < 2; t++) {
        #pragma unroll
        for (int jj = 4 * t; jj < 4 * t + 4; jj++) {
          const uint32_t gl = (jj & 1) ? gb[jj >> 1].z : gb[jj >> 1].x, gh = (jj & 1) ? gb[jj >> 1].w : gb[jj >> 1].y;
          const int i = 8 * jj;
          stmatrix_x4(sbase + SM_STG + t * 16384 + frag.o[jj & 3],
                      fma_bf2(gl, pack_bf16(a1[i], a1[i + 1]), x2[4 * jj]), fma_bf2(gl, pack_bf16(a1[i + 2], a1[i + 3]), x2[4 * jj + 1]),
                      fma_bf2(gh, pack_bf16(a1[i + 4], a1[i + 5]), x2[4 * jj + 2]), fma_bf2(gh, pack_bf16(a1[i + 6], a1[i + 7]), x2[4 * jj + 3]));
        }
        fence_proxy_async_smem();
        tma_store_3d(&maps.out, slab + t * 16384, j * 128 + t * 64, mb * 64 + warp * 16, wg);
      }
      bulk_commit();
      st_rlx(tid == 0 ? flags + FO_EPOCH : &mail0->flags[FL_EPOCH], e1, j == 0 && (tid == 0 || (tid == 1 && mb == 0)));
      bulk_wait_read0();
      PROFN(51, tid == 128);
    }
  }
}

typedef CUresult (*PFN_encodeTiled)(CUtensorMap*, CUtensorMapDataType, cuuint32_t, void*, const cuuint64_t*, const cuuint64_t*,
                                    const cuuint32_t*, const cuuint32_t*, CUtensorMapInterleave, CUtensorMapSwizzle,
                                    CUtensorMapL2promotion, CUtensorMapFloatOOBfill);

void encode(PFN_encodeTiled fn, CUtensorMap* m, const void* ptr, int rank, const cuuint64_t* dims, const cuuint64_t* strides,
            const cuuint32_t* box) {
  const cuuint32_t es[5] = {1, 1, 1, 1, 1};
  fn(m, CU_TENSOR_MAP_DATA_TYPE_BFLOAT16, rank, const_cast<void*>(ptr), dims, strides, box, es, CU_TENSOR_MAP_INTERLEAVE_NONE,
     CU_TENSOR_MAP_SWIZZLE_128B, CU_TENSOR_MAP_L2_PROMOTION_L2_256B, CU_TENSOR_MAP_FLOAT_OOB_FILL_NONE);
}
void map2d(PFN_encodeTiled fn, CUtensorMap* m, const void* ptr, int cols, int rows, int boxrows) {
  const cuuint64_t dims[2] = {(cuuint64_t)cols, (cuuint64_t)rows}, strides[1] = {(cuuint64_t)cols * 2};
  const cuuint32_t box[2] = {64, (cuuint32_t)boxrows};
  encode(fn, m, ptr, 2, dims, strides, box);
}
void map_w2chunk(PFN_encodeTiled fn, CUtensorMap* m, const void* ptr, int cols, int rows) {
  const cuuint64_t dims[3] = {64, (cuuint64_t)rows, (cuuint64_t)cols / 64}, strides[2] = {(cuuint64_t)cols * 2, 128};
  const cuuint32_t box[3] = {64, 64, 2};
  encode(fn, m, ptr, 3, dims, strides, box);
}
void map_parity(PFN_encodeTiled fn, CUtensorMap* m, const void* ptr, int boxpairs, int boxpar) {
  const cuuint64_t dims[3] = {D_, S_ / 2, 2}, strides[2] = {D_ * 4, D_ * 2};
  const cuuint32_t box[3] = {64, (cuuint32_t)boxpairs, (cuuint32_t)boxpar};
  encode(fn, m, ptr, 3, dims, strides, box);
}

}

extern "C" void kernel_launch(void* const* d_in, const int* in_sizes, int n_in, void* d_out, int out_size) {
  (void)in_sizes; (void)n_in; (void)out_size;
  const bf16* x = (const bf16*)d_in[0];
  const bf16* wqkv = (const bf16*)d_in[1];
  const bf16* wo = (const bf16*)d_in[2];
  const bf16* w1 = (const bf16*)d_in[4];
  const bf16* w3 = (const bf16*)d_in[5];
  const bf16* w2 = (const bf16*)d_in[6];
  const bf16* cvec = (const bf16*)d_in[7];
  const bf16* w_mod = (const bf16*)d_in[8];

  static PFN_encodeTiled fn = nullptr;
  static Maps maps;
  static const void* cached[8] = {};
  static int sms = 0;
  static void* mail = nullptr;
  if (!fn) {
    void* p = nullptr; cudaDriverEntryPointQueryResult st;
    cudaGetDriverEntryPoint("cuTensorMapEncodeTiled", &p, cudaEnableDefault, &st);
    fn = (PFN_encodeTiled)p;
    cudaFuncSetAttribute(fused_block_kernel<0>, cudaFuncAttributeMaxDynamicSharedMemorySize, SM_TOTAL + SM_PROF);
    cudaFuncSetAttribute(fused_block_kernel<1>, cudaFuncAttributeMaxDynamicSharedMemorySize, SM_TOTAL + SM_PROF);
    cudaFuncSetAttribute(fused_block_kernel<2>, cudaFuncAttributeMaxDynamicSharedMemorySize, SM_TOTAL + SM_PROF);
    cudaGetSymbolAddress(&mail, g_mail);
    int dev = 0;
    cudaGetDevice(&dev);
    cudaDeviceGetAttribute(&sms, cudaDevAttrMultiProcessorCount, dev);
  }
  const void* cur[8] = {x, wqkv, wo, w1, w3, w2, d_out, w_mod};
  bool same = true;
  for (int i = 0; i < 8; i++) same = same && cached[i] == cur[i];
  if (!same) {
    void *o, *h2, *hh;
    cudaGetSymbolAddress(&hh, g_hh); cudaGetSymbolAddress(&o, g_o);
    h2 = o;
    map_parity(fn, &maps.x, x, 64, 2); map_parity(fn, &maps.out, d_out, 16, 1);
    map2d(fn, &maps.o, o, D_, S_, 128); map2d(fn, &maps.h2, h2, D_, S_, 128);
    {
      const cuuint64_t dims[3] = {512, (cuuint64_t)S_, 7}, strides[2] = {1024, (cuuint64_t)S_ * 1024};
      const cuuint32_t box[3] = {64, 128, 1};
      encode(fn, &maps.hh, hh, 3, dims, strides, box);
    }
    {
      const cuuint64_t dims[4] = {64, 1024, 16, 2}, strides[3] = {3072 * 2, 128, 2048};
      const cuuint64_t dimv[4] = {64, 1024, 8, 2}, stridev[3] = {3072 * 2, 128, 1024};
      const cuuint32_t box[4] = {64, 64, 1, 2};
      encode(fn, &maps.wqk, wqkv, 4, dims, strides, box);
      encode(fn, &maps.wvv, wqkv + 2048, 4, dimv, stridev, box);
      const cuuint64_t dim1[4] = {1024, 128, 8, 2}, stride1[3] = {3072 * 2, 128 * 3072 * 2, 2048};
      const cuuint32_t box1[4] = {64, 16, 4, 2};
      encode(fn, &maps.wq1, wqkv, 4, dim1, stride1, box1);
    }
    map_w2chunk(fn, &maps.wo, wo, D_, D_); map_w2chunk(fn, &maps.w2, w2, D_, F_);
    map2d(fn, &maps.w1, w1, F_, D_, 64); map2d(fn, &maps.w3, w3, F_, D_, 64);
    map2d(fn, &maps.wmod, w_mod, 6 * D_, D_, 256);
    for (int i = 0; i < 8; i++) cached[i] = cur[i];
  }
  if (sms == NCTA + NAUX) {
    fused_block_kernel<0><<<NCTA + NAUX, 384, SM_TOTAL + SM_PROF>>>(x, cvec, w_mod, (Mail*)mail, 0, maps);
  } else {
    fused_block_kernel<1><<<NAUX, 384, SM_TOTAL + SM_PROF>>>(x, cvec, w_mod, (Mail*)mail, 0, maps);
    fused_block_kernel<2><<<NCTA, 384, SM_TOTAL + SM_PROF>>>(x, cvec, w_mod, (Mail*)mail, 0, maps);
  }
}
```

```cpp
#include <cuda.h>
#include <cuda_runtime.h>
#include <cuda_bf16.h>
#include <stdint.h>

namespace {

typedef __nv_bfloat16 bf16;

constexpr int S_ = 2048, D_ = 1024, F_ = 3584;
constexpr int NCTA = 128, NAUX = 4;

__device__ __align__(1024) bf16 g_o[S_ * D_];
__device__ __align__(1024) bf16 g_hh[S_ * F_];
constexpr int FO_EPOCH = 0, FO_CNT = 1;
constexpr int FL_EPOCH = 16 * 32, FL_LN1 = FL_EPOCH + 2, FL_H2 = FL_EPOCH + 3, FL_O = FL_EPOCH + 4;
struct Mail {
  unsigned flags[32 * 32];
  float mod[8 * 6 * D_];
  uint2 ln1[16 * 8 * 16];
  uint4 halo[2][16 * 16 * 2 * 4 * 32];
  uint4 st2[2][16 * 8 * 8 * 8];
};
__device__ __align__(1024) Mail g_mail;

template <int mode>
__device__ __forceinline__ int cta_role() {
  if (mode) return mode == 1 ? NCTA + (blockIdx.x & 3) : blockIdx.x & 127;
  uint32_t sm;
  asm("mov.u32 %0, %%smid;" : "=r"(sm));
  sm = (sm & ~3u) == 12 ? sm + 108 : (sm & ~3u) == 120 ? sm - 108 : sm;
  const int t = sm >> 1;
  int r;
  if (t < 32) r = (t & 7) * 16 + (t >> 3) * 2 + (sm & 1);
  else if (t < 60) r = (1 + (t - 32) % 7) * 16 + 8 + ((t - 32) / 7) * 2 + (sm & 1);
  else if (t < 62) r = NCTA + sm - 120;
  else r = sm - 116;
  return r;
}
#define PROF(slot, on) do {} while (0)
#define PROFN(slot, on) do {} while (0)
#define PROF_OUT(role, t) do {} while (0)
constexpr uint32_t SM_PROF = 0;

__device__ __forceinline__ uint32_t smem_u32(const void* p) { return (uint32_t)__cvta_generic_to_shared(p); }
#define ELECT "{\n.reg .pred p;\nelect.sync _|p, 0xffffffff;\n@p "
__device__ __forceinline__ void mbar_init_e(uint32_t bar, uint32_t count) {
  asm volatile(ELECT "mbarrier.init.shared::cta.b64 [%0], %1;\n}" :: "r"(bar), "r"(count) : "memory");
}
__device__ __forceinline__ void mbar_expect_tx_e(uint32_t bar, uint32_t bytes) {
  asm volatile(ELECT "mbarrier.arrive.expect_tx.shared::cta.b64 _, [%0], %1;\n}" :: "r"(bar), "r"(bytes) : "memory");
}
__device__ __forceinline__ void mbar_arrive_e(uint32_t bar) {
  asm volatile(ELECT "mbarrier.arrive.shared::cta.b64 _, [%0];\n}" :: "r"(bar) : "memory");
}
__device__ __forceinline__ uint32_t clock32() { uint32_t t; asm volatile("mov.u32 %0, %%clock;" : "=r"(t)); return t; }
__device__ __forceinline__ void mbar_wait(uint32_t bar, uint32_t parity, uint32_t dl) {
  asm volatile("{\n.reg .pred p, q;\n.reg .b32 t;\n"
               "mbarrier.try_wait.parity.shared::cta.b64 p, [%0], %1;\n"
               "@p bra LAB_DONE;\n"
               "LAB_WAIT:\n"
               "mbarrier.try_wait.parity.shared::cta.b64 p, [%0], %1;\n"
               "mov.u32 t, %%clock;\n"
               "sub.s32 t, t, %2;\n"
               "setp.lt.and.s32 q, t, 0, !p;\n"
               "@q bra LAB_WAIT;\n"
               "LAB_DONE:\n}" :: "r"(bar), "r"(parity), "r"(dl) : "memory");
}
__device__ __forceinline__ void mbar_sleep(uint32_t bar, uint32_t parity, uint32_t dl) {
  asm volatile("{\n.reg .pred p;\n.reg .b32 t;\n"
               "LAB_WAIT:\n"
               "mbarrier.try_wait.parity.shared::cta.b64 p, [%0], %1, 20000;\n"
               "@p bra LAB_DONE;\n"
               "mov.u32 t, %%clock;\n"
               "sub.s32 t, t, %2;\n"
               "setp.lt.s32 p, t, 0;\n"
               "@p bra LAB_WAIT;\n"
               "LAB_DONE:\n}" :: "r"(bar), "r"(parity), "r"(dl) : "memory");
}
__device__ __forceinline__ bool poll_done(bool ok, uint32_t dl) {
  return __all_sync(0xffffffffu, ok || (int)(clock32() - dl) >= 0);
}
__device__ __forceinline__ unsigned ld_relaxed(const unsigned* p) {
  unsigned v; asm volatile("ld.relaxed.gpu.global.u32 %0, [%1];" : "=r"(v) : "l"(p) : "memory"); return v;
}
__device__ __forceinline__ void red_add_e(unsigned* p, unsigned v) {
  asm volatile(ELECT "red.relaxed.gpu.global.add.u32 [%0], %1;\n}" :: "l"(p), "r"(v) : "memory");
}
__device__ __forceinline__ void wait_flag(const unsigned* p, unsigned target, uint32_t dl) {
  asm volatile("{\n.reg .pred p;\n.reg .b32 t;\n"
               "LAB_WAIT:\n"
               "ld.relaxed.gpu.global.u32 t, [%0];\n"
               "sub.s32 t, t, %1;\n"
               "setp.ge.s32 p, t, 0;\n"
               "@p bra LAB_DONE;\n"
               "mov.u32 t, %%clock;\n"
               "sub.s32 t, t, %2;\n"
               "setp.lt.s32 p, t, 0;\n"
               "@p bra LAB_WAIT;\n"
               "LAB_DONE:\n}" :: "l"(p), "r"(target), "r"(dl) : "memory");
}
__device__ __forceinline__ void wait_until(uint32_t t) { while ((int)(clock32() - t) < 0) {} }
__device__ __forceinline__ void fence_proxy_async_smem() { asm volatile("fence.proxy.async.shared::cta;" ::: "memory"); }

constexpr uint64_t EVICT_FIRST = 0x12F0000000000000ull;
template <bool STREAM = false>
__device__ __forceinline__ void tma_load_2d(uint32_t dst, const CUtensorMap* m, uint32_t bar, int c0, int c1) {
  if (STREAM)
    asm volatile(ELECT "cp.async.bulk.tensor.2d.shared::cluster.global.mbarrier::complete_tx::bytes.L2::cache_hint [%0], [%1, {%3, %4}], [%2], %5;\n}"
                 :: "r"(dst), "l"(m), "r"(bar), "r"(c0), "r"(c1), "l"(EVICT_FIRST) : "memory");
  else
    asm volatile(ELECT "cp.async.bulk.tensor.2d.shared::cluster.global.mbarrier::complete_tx::bytes [%0], [%1, {%3, %4}], [%2];\n}"
                 :: "r"(dst), "l"(m), "r"(bar), "r"(c0), "r"(c1) : "memory");
}
template <bool STREAM = false>
__device__ __forceinline__ void tma_load_3d(uint32_t dst, const CUtensorMap* m, uint32_t bar, int c0, int c1, int c2) {
  if (STREAM)
    asm volatile(ELECT "cp.async.bulk.tensor.3d.shared::cluster.global.mbarrier::complete_tx::bytes.L2::cache_hint [%0], [%1, {%3, %4, %5}], [%2], %6;\n}"
                 :: "r"(dst), "l"(m), "r"(bar), "r"(c0), "r"(c1), "r"(c2), "l"(EVICT_FIRST) : "memory");
  else
    asm volatile(ELECT "cp.async.bulk.tensor.3d.shared::cluster.global.mbarrier::complete_tx::bytes [%0], [%1, {%3, %4, %5}], [%2];\n}"
                 :: "r"(dst), "l"(m), "r"(bar), "r"(c0), "r"(c1), "r"(c2) : "memory");
}
template <bool STREAM = false>
__device__ __forceinline__ void tma_load_4d(uint32_t dst, const CUtensorMap* m, uint32_t bar, int c0, int c1, int c2, int c3) {
  if (STREAM)
    asm volatile(ELECT "cp.async.bulk.tensor.4d.shared::cluster.global.mbarrier::complete_tx::bytes.L2::cache_hint [%0], [%1, {%3, %4, %5, %6}], [%2], %7;\n}"
                 :: "r"(dst), "l"(m), "r"(bar), "r"(c0), "r"(c1), "r"(c2), "r"(c3), "l"(EVICT_FIRST) : "memory");
  else
    asm volatile(ELECT "cp.async.bulk.tensor.4d.shared::cluster.global.mbarrier::complete_tx::bytes [%0], [%1, {%3, %4, %5, %6}], [%2];\n}"
                 :: "r"(dst), "l"(m), "r"(bar), "r"(c0), "r"(c1), "r"(c2), "r"(c3) : "memory");
}
__device__ __forceinline__ void tma_store_2d(const CUtensorMap* m, uint32_t src, int c0, int c1) {
  asm volatile(ELECT "cp.async.bulk.tensor.2d.global.shared::cta.bulk_group [%0, {%2, %3}], [%1];\n}"
               :: "l"(m), "r"(src), "r"(c0), "r"(c1) : "memory");
}
__device__ __forceinline__ void tma_store_3d(const CUtensorMap* m, uint32_t src, int c0, int c1, int c2) {
  asm volatile(ELECT "cp.async.bulk.tensor.3d.global.shared::cta.bulk_group [%0, {%2, %3, %4}], [%1];\n}"
               :: "l"(m), "r"(src), "r"(c0), "r"(c1), "r"(c2) : "memory");
}
__device__ __forceinline__ void bulk_load(uint32_t dst, const void* src, uint32_t bytes, uint32_t bar) {
  asm volatile(ELECT "cp.async.bulk.shared::cluster.global.mbarrier::complete_tx::bytes [%0], [%1], %2, [%3];\n}"
               :: "r"(dst), "l"(src), "r"(bytes), "r"(bar) : "memory");
}
__device__ __forceinline__ void bulk_prefetch(const void* src, uint32_t bytes) {
  asm volatile(ELECT "cp.async.bulk.prefetch.L2.global [%0], %1;\n}" :: "l"(src), "r"(bytes) : "memory");
}
__device__ __forceinline__ void bulk_commit() { asm volatile("cp.async.bulk.commit_group;" ::: "memory"); }
__device__ __forceinline__ void bulk_wait0() { asm volatile("cp.async.bulk.wait_group 0;" ::: "memory"); }
__device__ __forceinline__ void bulk_wait_read0() { asm volatile("cp.async.bulk.wait_group.read 0;" ::: "memory"); }
__device__ __forceinline__ void prefetch_tmap(const CUtensorMap* m) { asm volatile(ELECT "prefetch.tensormap [%0];\n}" :: "l"(m) : "memory"); }
__device__ __forceinline__ void wgmma_fence() { asm volatile("wgmma.fence.sync.aligned;" ::: "memory"); }
__device__ __forceinline__ void wgmma_commit() { asm volatile("wgmma.commit_group.sync.aligned;" ::: "memory"); }
template <int N> __device__ __forceinline__ void wgmma_wait() { asm volatile("wgmma.wait_group.sync.aligned %0;" :: "n"(N) : "memory"); }
template <int R> __device__ __forceinline__ void reg_alloc() { asm volatile("setmaxnreg.inc.sync.aligned.u32 %0;" :: "n"(R)); }
template <int R> __device__ __forceinline__ void reg_dealloc() { asm volatile("setmaxnreg.dec.sync.aligned.u32 %0;" :: "n"(R)); }
__device__ __forceinline__ void bar_sync(int id, int n) { asm volatile("bar.sync %0, %1;" :: "r"(id), "r"(n) : "memory"); }
__device__ __forceinline__ void bar_arrive(int id, int n) { asm volatile("bar.arrive %0, %1;" :: "r"(id), "r"(n) : "memory"); }
__device__ __forceinline__ void sched_fence(int zero) {
  asm volatile("{\n.reg .pred p;\n.reg .b32 t;\nsetp.eq.s32 p, %0, 0;\n@p bra.uni LAB_S;\n"
               "LAB_F:\nmov.u32 t, %%clock;\nsetp.eq.u32 p, t, 0;\n@p bra LAB_F;\nLAB_S:\n}" :: "r"(zero) : "memory");
}
template <int N> __device__ __forceinline__ void fence_regs(float (&a)[N]) {
  #pragma unroll
  for (int i = 0; i < N; i++) asm volatile("" : "+f"(a[i]) :: "memory");
}
template <int N> __device__ __forceinline__ void undef_regs(float (&a)[N]) {
  #pragma unroll
  for (int i = 0; i < N; i++) asm volatile("" : "=f"(a[i]));
}

__device__ __forceinline__ uint64_t desc_from_lo(uint32_t lo) { return (uint64_t)lo | ((uint64_t)0x40000040u << 32); }
__device__ __forceinline__ uint32_t pack_bf16(float lo, float hi) {
  uint32_t r; asm("cvt.rn.bf16x2.f32 %0, %1, %2;" : "=r"(r) : "f"(hi), "f"(lo)); return r;
}
__device__ __forceinline__ uint32_t fma_bf2(uint32_t a, uint32_t b, uint32_t c) {
  uint32_t d; asm("fma.rn.bf16x2 %0, %1, %2, %3;" : "=r"(d) : "r"(a), "r"(b), "r"(c)); return d;
}
__device__ __forceinline__ float bf_lo(uint32_t v) { return __uint_as_float(v << 16); }
__device__ __forceinline__ float bf_hi(uint32_t v) { return __uint_as_float(v & 0xFFFF0000u); }
__device__ __forceinline__ float bf16_round(float x) { return bf_lo(pack_bf16(x, 0.f)); }
__device__ __forceinline__ void stmatrix_x4(uint32_t addr, uint32_t r0, uint32_t r1, uint32_t r2, uint32_t r3) {
  asm volatile("stmatrix.sync.aligned.m8n8.x4.shared.b16 [%0], {%1, %2, %3, %4};" :: "r"(addr), "r"(r0), "r"(r1), "r"(r2), "r"(r3) : "memory");
}
__device__ __forceinline__ void stmatrix_x4_t(uint32_t addr, uint32_t r0, uint32_t r1, uint32_t r2, uint32_t r3) {
  asm volatile("stmatrix.sync.aligned.m8n8.x4.trans.shared.b16 [%0], {%1, %2, %3, %4};" :: "r"(addr), "r"(r0), "r"(r1), "r"(r2), "r"(r3) : "memory");
}
__device__ __forceinline__ void stmatrix_x4_if(uint32_t addr, uint32_t r0, uint32_t r1, uint32_t r2, uint32_t r3, bool on) {
  asm volatile("{\n.reg .pred p;\nsetp.ne.b32 p, %5, 0;\n@p stmatrix.sync.aligned.m8n8.x4.shared.b16 [%0], {%1, %2, %3, %4};\n}"
               :: "r"(addr), "r"(r0), "r"(r1), "r"(r2), "r"(r3), "r"((int)on) : "memory");
}
__device__ __forceinline__ void ldmatrix_x4(uint32_t addr, uint32_t& r0, uint32_t& r1, uint32_t& r2, uint32_t& r3) {
  asm volatile("ldmatrix.sync.aligned.m8n8.x4.shared.b16 {%0, %1, %2, %3}, [%4];" : "=r"(r0), "=r"(r1), "=r"(r2), "=r"(r3) : "r"(addr) : "memory");
}
__device__ __forceinline__ void ldmatrix_x4_t(uint32_t addr, uint32_t (&r)[4]) {
  asm volatile("ldmatrix.sync.aligned.m8n8.x4.trans.shared.b16 {%0, %1, %2, %3}, [%4];" : "=r"(r[0]), "=r"(r[1]), "=r"(r[2]), "=r"(r[3]) : "r"(addr) : "memory");
}
__device__ __forceinline__ void st_rlx(void* p, uint32_t a, bool on) {
  asm volatile("{\n.reg .pred p;\nsetp.ne.b32 p, %2, 0;\n@p st.relaxed.gpu.global.u32 [%0], %1;\n}" :: "l"(p), "r"(a), "r"((int)on) : "memory");
}
__device__ __forceinline__ void st_rlx_v2(void* p, uint32_t a, uint32_t b, bool on) {
  asm volatile("{\n.reg .pred p;\nsetp.ne.b32 p, %3, 0;\n@p st.relaxed.gpu.global.v2.u32 [%0], {%1, %2};\n}" :: "l"(p), "r"(a), "r"(b), "r"((int)on) : "memory");
}
__device__ __forceinline__ uint2 ld_rlx_v2(const void* p) {
  uint2 v; asm volatile("ld.relaxed.gpu.global.v2.u32 {%0,%1}, [%2];" : "=r"(v.x), "=r"(v.y) : "l"(p) : "memory"); return v;
}
__device__ __forceinline__ void st_rlx_v4(void* p, uint32_t a, uint32_t b, uint32_t c, uint32_t d, bool on) {
  asm volatile("{\n.reg .pred p;\nsetp.ne.b32 p, %5, 0;\n@p st.relaxed.gpu.global.v4.u32 [%0], {%1, %2, %3, %4};\n}"
               :: "l"(p), "r"(a), "r"(b), "r"(c), "r"(d), "r"((int)on) : "memory");
}
__device__ __forceinline__ void st_nonzero_v4(void* p, uint32_t a, uint32_t b, uint32_t c, uint32_t d, bool on) {
  st_rlx_v4(p, max(a, 1u), max(b, 1u), max(c, 1u), max(d, 1u), on);
}
__device__ __forceinline__ uint32_t min4(const uint4& v) { return min(min(v.x, v.y), min(v.z, v.w)); }
__device__ __forceinline__ uint4 ld_rlx_v4(const void* p) {
  uint4 v; asm volatile("ld.relaxed.gpu.global.v4.u32 {%0,%1,%2,%3}, [%4];" : "=r"(v.x), "=r"(v.y), "=r"(v.z), "=r"(v.w) : "l"(p) : "memory"); return v;
}
__device__ __forceinline__ uint32_t movmatrix_t(uint32_t a) {
  uint32_t d; asm volatile("movmatrix.sync.aligned.m8n8.trans.b16 %0, %1;" : "=r"(d) : "r"(a)); return d;
}
__device__ __forceinline__ void mma16(float (&c)[4], uint32_t a0, uint32_t a1, uint32_t a2, uint32_t a3, uint32_t b0, uint32_t b1) {
  asm volatile("mma.sync.aligned.m16n8k16.row.col.f32.bf16.bf16.f32 {%0,%1,%2,%3}, {%4,%5,%6,%7}, {%8,%9}, {%0,%1,%2,%3};"
               : "+f"(c[0]), "+f"(c[1]), "+f"(c[2]), "+f"(c[3]) : "r"(a0), "r"(a1), "r"(a2), "r"(a3), "r"(b0), "r"(b1));
}
__device__ __forceinline__ void sts128(uint32_t addr, uint32_t a, uint32_t b, uint32_t c, uint32_t d) {
  asm volatile("st.shared.v4.b32 [%0], {%1,%2,%3,%4};" :: "r"(addr), "r"(a), "r"(b), "r"(c), "r"(d) : "memory");
}
__device__ __forceinline__ uint4 lds128(uint32_t addr) {
  uint4 v; asm volatile("ld.shared.v4.b32 {%0,%1,%2,%3}, [%4];" : "=r"(v.x), "=r"(v.y), "=r"(v.z), "=r"(v.w) : "r"(addr) : "memory"); return v;
}
__device__ __forceinline__ uint32_t lds32(uint32_t addr) {
  uint32_t v; asm volatile("ld.shared.b32 %0, [%1];" : "=r"(v) : "r"(addr) : "memory"); return v;
}
__device__ __forceinline__ float2 lds64f(uint32_t addr) {
  float2 v; asm volatile("ld.shared.v2.f32 {%0,%1}, [%2];" : "=f"(v.x), "=f"(v.y) : "r"(addr) : "memory"); return v;
}
__device__ __forceinline__ void sts64(uint32_t addr, uint32_t a, uint32_t b) {
  asm volatile("st.shared.v2.b32 [%0], {%1, %2};" :: "r"(addr), "r"(a), "r"(b) : "memory");
}
__device__ __forceinline__ float fast_ex2(float x) { float y; asm("ex2.approx.ftz.f32 %0, %1;" : "=f"(y) : "f"(x)); return y; }
__device__ __forceinline__ float fast_rcp(float x) { float y; asm("rcp.approx.ftz.f32 %0, %1;" : "=f"(y) : "f"(x)); return y; }
__device__ __forceinline__ float fast_rsqrt(float x) { float y; asm("rsqrt.approx.ftz.f32 %0, %1;" : "=f"(y) : "f"(x)); return y; }
__device__ __forceinline__ float silu_f(float g) { return g * fast_rcp(1.f + fast_ex2(g * -1.4426950408889634f)); }
__device__ __forceinline__ float swiglu(float h, float v) {
  float t; asm("tanh.approx.f32 %0, %1;" : "=f"(t) : "f"(h));
  const float p = h * v;
  return fmaf(p, t, p);
}

__device__ __forceinline__ void wgmma_m64n128k16_ss(float (&d)[64], uint64_t descA, uint64_t descB, int scaleD) {
  asm volatile("{\n.reg .pred p;\nsetp.ne.b32 p, %66, 0;\n"
    "wgmma.mma_async.sync.aligned.m64n128k16.f32.bf16.bf16 "
    "{%0, %1, %2, %3, %4, %5, %6, %7, %8, %9, %10, %11, %12, %13, %14, %15, "
    "%16, %17, %18, %19, %20, %21, %22, %23, %24, %25, %26, %27, %28, %29, %30, %31, "
    "%32, %33, %34, %35, %36, %37, %38, %39, %40, %41, %42, %43, %44, %45, %46, %47, "
    "%48, %49, %50, %51, %52, %53, %54, %55, %56, %57, %58, %59, %60, %61, %62, %63}, "
    "%64, %65, p, 1, 1, 0, 1;\n}\n"
    : "+f"(d[0]), "+f"(d[1]), "+f"(d[2]), "+f"(d[3]), "+f"(d[4]), "+f"(d[5]), "+f"(d[6]), "+f"(d[7]),
      "+f"(d[8]), "+f"(d[9]), "+f"(d[10]), "+f"(d[11]), "+f"(d[12]), "+f"(d[13]), "+f"(d[14]), "+f"(d[15]),
      "+f"(d[16]), "+f"(d[17]), "+f"(d[18]), "+f"(d[19]), "+f"(d[20]), "+f"(d[21]), "+f"(d[22]), "+f"(d[23]),
      "+f"(d[24]), "+f"(d[25]), "+f"(d[26]), "+f"(d[27]), "+f"(d[28]), "+f"(d[29]), "+f"(d[30]), "+f"(d[31]),
      "+f"(d[32]), "+f"(d[33]), "+f"(d[34]), "+f"(d[35]), "+f"(d[36]), "+f"(d[37]), "+f"(d[38]), "+f"(d[39]),
      "+f"(d[40]), "+f"(d[41]), "+f"(d[42]), "+f"(d[43]), "+f"(d[44]), "+f"(d[45]), "+f"(d[46]), "+f"(d[47]),
      "+f"(d[48]), "+f"(d[49]), "+f"(d[50]), "+f"(d[51]), "+f"(d[52]), "+f"(d[53]), "+f"(d[54]), "+f"(d[55]),
      "+f"(d[56]), "+f"(d[57]), "+f"(d[58]), "+f"(d[59]), "+f"(d[60]), "+f"(d[61]), "+f"(d[62]), "+f"(d[63])
    : "l"(descA), "l"(descB), "r"(scaleD));
}
__device__ __forceinline__ void wgmma_m64n256k16_rs(float (&d)[128], uint32_t a0, uint32_t a1, uint32_t a2, uint32_t a3, uint64_t descB, int scaleD) {
  asm volatile("{\n.reg .pred p;\nsetp.ne.b32 p, %133, 0;\n"
    "wgmma.mma_async.sync.aligned.m64n256k16.f32.bf16.bf16 "
    "{%0, %1, %2, %3, %4, %5, %6, %7, %8, %9, %10, %11, %12, %13, %14, %15, "
    "%16, %17, %18, %19, %20, %21, %22, %23, %24, %25, %26, %27, %28, %29, %30, %31, "
    "%32, %33, %34, %35, %36, %37, %38, %39, %40, %41, %42, %43, %44, %45, %46, %47, "
    "%48, %49, %50, %51, %52, %53, %54, %55, %56, %57, %58, %59, %60, %61, %62, %63, "
    "%64, %65, %66, %67, %68, %69, %70, %71, %72, %73, %74, %75, %76, %77, %78, %79, "
    "%80, %81, %82, %83, %84, %85, %86, %87, %88, %89, %90, %91, %92, %93, %94, %95, "
    "%96, %97, %98, %99, %100, %101, %102, %103, %104, %105, %106, %107, %108, %109, %110, %111, "
    "%112, %113, %114, %115, %116, %117, %118, %119, %120, %121, %122, %123, %124, %125, %126, %127}, "
    "{%128, %129, %130, %131}, %132, p, 1, 1, 1;\n}\n"
    : "+f"(d[0]), "+f"(d[1]), "+f"(d[2]), "+f"(d[3]), "+f"(d[4]), "+f"(d[5]), "+f"(d[6]), "+f"(d[7]),
      "+f"(d[8]), "+f"(d[9]), "+f"(d[10]), "+f"(d[11]), "+f"(d[12]), "+f"(d[13]), "+f"(d[14]), "+f"(d[15]),
      "+f"(d[16]), "+f"(d[17]), "+f"(d[18]), "+f"(d[19]), "+f"(d[20]), "+f"(d[21]), "+f"(d[22]), "+f"(d[23]),
      "+f"(d[24]), "+f"(d[25]), "+f"(d[26]), "+f"(d[27]), "+f"(d[28]), "+f"(d[29]), "+f"(d[30]), "+f"(d[31]),
      "+f"(d[32]), "+f"(d[33]), "+f"(d[34]), "+f"(d[35]), "+f"(d[36]), "+f"(d[37]), "+f"(d[38]), "+f"(d[39]),
      "+f"(d[40]), "+f"(d[41]), "+f"(d[42]), "+f"(d[43]), "+f"(d[44]), "+f"(d[45]), "+f"(d[46]), "+f"(d[47]),
      "+f"(d[48]), "+f"(d[49]), "+f"(d[50]), "+f"(d[51]), "+f"(d[52]), "+f"(d[53]), "+f"(d[54]), "+f"(d[55]),
      "+f"(d[56]), "+f"(d[57]), "+f"(d[58]), "+f"(d[59]), "+f"(d[60]), "+f"(d[61]), "+f"(d[62]), "+f"(d[63]),
      "+f"(d[64]), "+f"(d[65]), "+f"(d[66]), "+f"(d[67]), "+f"(d[68]), "+f"(d[69]), "+f"(d[70]), "+f"(d[71]),
      "+f"(d[72]), "+f"(d[73]), "+f"(d[74]), "+f"(d[75]), "+f"(d[76]), "+f"(d[77]), "+f"(d[78]), "+f"(d[79]),
      "+f"(d[80]), "+f"(d[81]), "+f"(d[82]), "+f"(d[83]), "+f"(d[84]), "+f"(d[85]), "+f"(d[86]), "+f"(d[87]),
      "+f"(d[88]), "+f"(d[89]), "+f"(d[90]), "+f"(d[91]), "+f"(d[92]), "+f"(d[93]), "+f"(d[94]), "+f"(d[95]),
      "+f"(d[96]), "+f"(d[97]), "+f"(d[98]), "+f"(d[99]), "+f"(d[100]), "+f"(d[101]), "+f"(d[102]), "+f"(d[103]),
      "+f"(d[104]), "+f"(d[105]), "+f"(d[106]), "+f"(d[107]), "+f"(d[108]), "+f"(d[109]), "+f"(d[110]), "+f"(d[111]),
      "+f"(d[112]), "+f"(d[113]), "+f"(d[114]), "+f"(d[115]), "+f"(d[116]), "+f"(d[117]), "+f"(d[118]), "+f"(d[119]),
      "+f"(d[120]), "+f"(d[121]), "+f"(d[122]), "+f"(d[123]), "+f"(d[124]), "+f"(d[125]), "+f"(d[126]), "+f"(d[127])
    : "r"(a0), "r"(a1), "r"(a2), "r"(a3), "l"(descB), "r"(scaleD));
}

constexpr uint32_t MSLOT = 32768, QSLOT = 49152;
constexpr int NM = 6;
constexpr uint32_t SM_X0 = 3 * QSLOT;
constexpr uint32_t SM_XR = SM_X0 + 16384;
constexpr uint32_t SM_STG = 196608;
constexpr uint32_t SM_XCH = SM_STG + 16384;
constexpr uint32_t SM_BAR = SM_STG + 32768;
constexpr uint32_t SM_VEC = SM_BAR + 512;
constexpr uint32_t SM_MODT = SM_VEC;
constexpr uint32_t SM_TOTAL = SM_VEC + 2048;
constexpr uint32_t B_X = SM_BAR  , B_EQ = B_X + 64, B_EM = B_EQ + 32, B_STREQ = B_EM + 48, B_STH = B_STREQ + 8, B_LN = B_STH + 8,
                   B_FQ = B_LN + 8, B_FM = B_FQ + 32, B_MOD = B_FM + 48  , B_GATE = B_MOD + 64, B_STFREE = B_GATE + 8, B_VEC = B_STFREE + 8  ,
                   B_FLG = B_VEC + 16  , B_H2A = B_FLG + 24, B_END = B_FLG + 96;
constexpr int NB_WG = 1  , NB_CONS = 3, NB_ORD = 4  ;
#define TUNE(name, value) constexpr int name = value
TUNE(PF_BYTES, 256);
TUNE(X_GAP, 250);
TUNE(AUX_HOLD, 3200);
TUNE(AUX_URG, 4);
TUNE(AUX_SLOW, 84);
TUNE(AUX_GAP, 500);
TUNE(MSEP, 6);
TUNE(WPRE, 2);
TUNE(GPRE, 5);
TUNE(DTAIL, 4);

struct Maps {
  CUtensorMap x, out;
  CUtensorMap o, h2, hh;
  CUtensorMap wqk, wvv, wq1, wo, w1, w3, w2;
  CUtensorMap wmod;
};

struct Ring { int st; uint32_t ph; int prev; uint32_t dl;
};
__device__ __forceinline__ void ring_next(Ring& r) { if (++r.st == NM) { r.st = 0; r.ph ^= 1; } }

__device__ __forceinline__ void retire_prev(uint32_t rel, bool on) {
  wgmma_commit();
  wgmma_wait<1>();
  if (on) mbar_arrive_e(rel);
}
struct Nop { __device__ __forceinline__ void operator()() const {} };
template <bool REL = true, class F = Nop>
__device__ __forceinline__ void mma_step(float (&acc)[64], uint32_t a, uint32_t b, bool first, uint32_t rel, F urgent = F()) {
  const uint32_t alo = (a >> 4) + (1u << 16), blo = (b >> 4) + (512u << 16);
  wgmma_fence();
  #pragma unroll
  for (int k = 0; k < 4; k++) {
    wgmma_m64n128k16_ss(acc, desc_from_lo(alo + k * 2), desc_from_lo(blo + k * 128), k > 0 || !first);
    if (k == 0) { retire_prev(rel, REL); urgent(); }
  }
  wgmma_commit();
}
__device__ __forceinline__ uint32_t m_wait(uint32_t sbase, const Ring& r) {
  mbar_wait(sbase + B_FM + 8 * r.st, r.ph, r.dl);
  return sbase + r.st * MSLOT;
}
__device__ __forceinline__ uint32_t m_prev(uint32_t sbase, const Ring& r) { return sbase + B_EM + 8 * r.prev; }
__device__ __forceinline__ void m_next(Ring& r) {
  r.prev = r.st; ring_next(r);
}
__device__ __forceinline__ void m_step(float (&acc)[64], uint32_t sbase, uint32_t wgoff, Ring& r, bool first = false) {
  const uint32_t slot = m_wait(sbase, r);
  mma_step(acc, slot + wgoff, slot + 16384, first, m_prev(sbase, r));
  m_next(r);
}

struct LnRow { uint32_t rs[2], nb[2]; };
__device__ __forceinline__ void ln_row(LnRow& l, int h, float mean, float rstd) {
  l.rs[h] = pack_bf16(rstd, rstd);
  const float nb = -mean * bf_lo(l.rs[h]);
  l.nb[h] = pack_bf16(nb, nb);
}
__device__ __forceinline__ uint32_t ln_mod(uint32_t x, const LnRow& l, int h, uint32_t c1, uint32_t s) {
  return fma_bf2(fma_bf2(x, l.rs[h], l.nb[h]), c1, s);
}

__device__ __forceinline__ uint32_t q_wait(int u, uint32_t sbase, uint32_t dl) {
  mbar_wait(sbase + B_FQ + 8 * (u & 3), (u >> 2) & 1, dl);
  return sbase + (u & 3) * QSLOT;
}
__device__ __forceinline__ uint32_t q_empty(int u, uint32_t sbase) { return sbase + B_EQ + 8 * (u & 3); }
struct Frag4 { uint32_t o[4]; };
__device__ __forceinline__ void q_load(uint32_t (&A)[16], uint4 (&p)[4], int kk, uint32_t tile, const Frag4& f, uint32_t t) {
  ldmatrix_x4(tile + f.o[kk], A[4 * kk], A[4 * kk + 1], A[4 * kk + 2], A[4 * kk + 3]);
  p[kk] = lds128(t + kk * 64);
}
__device__ __forceinline__ void q_norm(uint32_t (&A)[16], const uint4 (&p)[4], int kk, const LnRow& l) {
  A[4 * kk + 0] = ln_mod(A[4 * kk + 0], l, 0, p[kk].x, p[kk].z); A[4 * kk + 1] = ln_mod(A[4 * kk + 1], l, 1, p[kk].x, p[kk].z);
  A[4 * kk + 2] = ln_mod(A[4 * kk + 2], l, 0, p[kk].y, p[kk].w); A[4 * kk + 3] = ln_mod(A[4 * kk + 3], l, 1, p[kk].y, p[kk].w);
}
template <bool NEXT>
__device__ __forceinline__ void q_step_rs(float (&acc)[128], uint32_t (&A)[16], uint32_t (&N)[16], uint4 (&p)[4], int u, uint32_t sbase,
                                          const Frag4& f, uint32_t tab, const LnRow& l, uint32_t rot, bool keep, bool first, uint32_t dl, int wg, int zero) {
  const uint32_t slot = first ? sbase : q_wait(u, sbase, dl);
  const uint32_t blo = ((slot + 16384) >> 4) + (512u << 16) + rot * 128 + (zero << (u >> 2)), t = tab + ((u + 1) & 7) * 256;
  #pragma unroll
  for (int kk = 0; kk < 4; kk++) q_norm(A, p, kk, l);
  #pragma unroll
  for (int i = 0; i < 16; i++) asm volatile("" : "+r"(A[i]));
  if (!first) sched_fence(zero);
  if (first) {
    mbar_wait(sbase + B_GATE, 0, dl);
    PROF(6, threadIdx.x == 0);
  }
  if (!(first && wg == 0)) bar_sync(NB_ORD + wg, 256);
  wgmma_fence();
  #pragma unroll
  for (int kk = 0; kk < 4; kk++) {
    wgmma_m64n256k16_rs(acc, A[4 * kk], A[4 * kk + 1], A[4 * kk + 2], A[4 * kk + 3], desc_from_lo(blo ^ (kk * 128)), kk > 0 || !first);
    if (kk == 0) retire_prev(q_empty(u - 1, sbase), !first);
    if (NEXT && kk == 1) {
      if ((u & 1) && u < MSEP) mbar_wait(sbase + B_MOD + 4 * (u + 1), 0, dl);
      #pragma unroll
      for (int q = 0; q < 4; q++) q_load(N, p, q, slot, f, t);
    }
    if (kk == 3 && (NEXT || wg == 0)) bar_arrive(NB_ORD + (wg ^ 1), 256);
    if (kk == 1) stmatrix_x4_if(sbase + SM_STG + (u >> 3) * 16384 + (f.o[0] ^ (((u >> 1 & 3) ^ rot) << 5)), A[0], A[1], A[2], A[3], keep);
  }
  wgmma_commit();
}

typedef uint32_t Frag8[8];
template <int N> __device__ __forceinline__ void pack_half(Frag8& f, const float (&acc)[N], int off, int half) {
  #pragma unroll
  for (int e = 0; e < 8; e++) { f[e] = pack_bf16(acc[off + 4 * e + 2 * half], acc[off + 4 * e + 2 * half + 1]); asm volatile("" : "+r"(f[e])); }
}
__device__ __forceinline__ void transpose8(Frag8& f) {
  #pragma unroll
  for (int e = 0; e < 8; e++) f[e] = movmatrix_t(f[e]);
}
__device__ __forceinline__ void attn_send(const Frag8& f, int kv, uint32_t xch, int warp, uint4* halo_out, bool has_next) {
  if (warp == 3) {
    st_nonzero_v4(halo_out + kv * 64, f[0], f[1], f[2], f[3], has_next); st_nonzero_v4(halo_out + kv * 64 + 32, f[4], f[5], f[6], f[7], has_next);
  } else {
    sts128(xch + 2048 + kv * 1024, f[0], f[1], f[2], f[3]); sts128(xch + 2048 + kv * 1024 + 512, f[4], f[5], f[6], f[7]);
  }
}
template <int N>
__device__ __forceinline__ void attn_recv(uint4* p, int first, uint32_t xch, int wg, int warp, const uint4* halo_in, bool has_prev) {
  bar_sync(NB_WG + wg, 128);
  #pragma unroll
  for (int e = 0; e < N; e++)
    asm volatile("{\n.reg .pred p, q;\nsetp.ne.b32 p, %6, 0;\nsetp.ne.b32 q, %7, 0;\n"
                 "mov.b32 %0, 0;\nmov.b32 %1, 0;\nmov.b32 %2, 0;\nmov.b32 %3, 0;\n"
                 "@p ld.shared.v4.b32 {%0,%1,%2,%3}, [%4];\n@q ld.relaxed.gpu.global.v4.u32 {%0,%1,%2,%3}, [%5];\n}"
                 : "=&r"(p[e].x), "=&r"(p[e].y), "=&r"(p[e].z), "=&r"(p[e].w)
                 : "r"(xch + (first + e) * 512), "l"(halo_in + (first + e) * 32), "r"((int)(warp > 0)), "r"((int)(warp == 0 && has_prev)) : "memory");
}
template <int N>
__device__ __forceinline__ void attn_check(uint4* p, int first, bool remote, const uint4* halo_in, uint32_t dl) {
  if (remote) {
    while (true) {
      uint32_t m = ~0u;
      #pragma unroll
      for (int e = 0; e < N; e++) m = min(m, min4(p[e]));
      if (poll_done(m != 0, dl)) break;
      #pragma unroll
      for (int e = 0; e < N; e++) p[e] = ld_rlx_v4(halo_in + (first + e) * 32);
    }
  }
}
__device__ __forceinline__ void attn_core(const Frag8& qA, const Frag8& qB, const Frag8& kA, const Frag8& kB, const Frag8& vA, const Frag8& vB,
                                          const uint4* kP, const uint4* vP, bool noprev, int lane, float (&o)[2][5][4]) {
  const int g = lane >> 2, qd = lane & 3;
  const bool s0 = 2 * qd > g, s1 = 2 * qd + 1 > g;
  const uint32_t msk = (s0 ? 0xFFFFu : 0u) | (s1 ? 0xFFFF0000u : 0u);
  constexpr float SC = 0.17677669529663687f * 1.4426950408889634f;
  float s[2][3][4];
  #pragma unroll
  for (int h = 0; h < 2; h++) {
    #pragma unroll
    for (int nb = 0; nb < 3; nb++) s[h][nb][0] = s[h][nb][1] = s[h][nb][2] = s[h][nb][3] = 0.f;
    #pragma unroll
    for (int kk = 0; kk < 2; kk++) {
      const int e = 4 * h + 2 * kk;
      mma16(s[h][1], qA[e], qB[e], qA[e + 1], qB[e + 1], kA[e], kA[e + 1]);
      mma16(s[h][2], qA[e], qB[e], qA[e + 1], qB[e + 1], kB[e], kB[e + 1]);
      mma16(s[h][0], qA[e], qB[e], qA[e + 1], qB[e + 1], kk ? kP[h].z : kP[h].x, kk ? kP[h].w : kP[h].y);
    }
  }
  #pragma unroll
  for (int h = 0; h < 2; h++) {
    float l[4], m[2];
    l[0] = s0 ? (noprev ? -INFINITY : s[h][0][0]) : s[h][1][0];
    l[1] = s1 ? (noprev ? -INFINITY : s[h][0][1]) : s[h][1][1];
    l[2] = s0 ? s[h][1][2] : s[h][2][2];
    l[3] = s1 ? s[h][1][3] : s[h][2][3];
    m[0] = fmaxf(l[0], l[1]); m[1] = fmaxf(l[2], l[3]);
    #pragma unroll
    for (int x = 1; x <= 2; x <<= 1)
      #pragma unroll
      for (int e = 0; e < 2; e++) m[e] = fmaxf(m[e], __shfl_xor_sync(0xffffffffu, m[e], x));
    #pragma unroll
    for (int e = 0; e < 4; e++) l[e] = fast_ex2((l[e] - m[e >> 1]) * SC);
    const uint32_t plo = pack_bf16(l[0], l[1]), phi = pack_bf16(l[2], l[3]);
    const uint32_t vp[4] = {vP[h].x, vP[h].y, vP[h].z, vP[h].w};
    #pragma unroll
    for (int d = 0; d < 5; d++) o[h][d][0] = o[h][d][1] = o[h][d][2] = o[h][d][3] = 0.f;
    mma16(o[h][4], 0x3F803F80u, 0u, 0u, 0x3F803F80u, plo, phi);
    #pragma unroll
    for (int m2 = 0; m2 < 2; m2++) {
      const int e = 4 * h + 2 * m2;
      mma16(o[h][2 * m2], vp[2 * m2], vp[2 * m2 + 1], vA[e], vA[e + 1], plo & msk, plo & ~msk);
      mma16(o[h][2 * m2 + 1], vA[e], vA[e + 1], vB[e], vB[e + 1], phi & msk, phi & ~msk);
    }
  }
}
__device__ __forceinline__ void attn_store(const float (&o)[2][5][4], int h, uint32_t sbase, const Frag4& f) {
  float r[4];
  #pragma unroll
  for (int e = 0; e < 4; e++) r[e] = fast_rcp(o[h][4][e]);
  #pragma unroll
  for (int m = 0; m < 2; m++) {
    const float (&lo)[4] = o[h][2 * m], (&hi)[4] = o[h][2 * m + 1];
    stmatrix_x4_t(sbase + SM_STG + f.o[2 * h + m], pack_bf16(lo[0] * r[0], lo[1] * r[1]), pack_bf16(hi[0] * r[2], hi[1] * r[3]),
                  pack_bf16(lo[2] * r[0], lo[3] * r[1]), pack_bf16(hi[2] * r[2], hi[3] * r[3]));
  }
}

__device__ __forceinline__ void request_store(uint32_t bar) {
  fence_proxy_async_smem();
  mbar_arrive_e(bar);
}

__device__ __forceinline__ void g_switch(float (&cur)[64], float (&prv)[64], int nrest, bool first, int n, uint32_t sbase, uint32_t wgoff,
                                         const Frag4& f, Ring& r) {
  #pragma unroll 1
  for (int i = 1; i < nrest; i++) m_step(prv, sbase, wgoff, r);
  m_step(prv, sbase, wgoff, r);
  m_step(cur, sbase, wgoff, r, first);
  mbar_wait(sbase + B_STFREE, (n - 1) & 1, r.dl);
  fence_regs(prv);
  PROF(28 + n, threadIdx.x == 0);
  #pragma unroll
  for (int jj = 0; jj < 4; jj++) {
    uint32_t p[4];
    #pragma unroll
    for (int e = 0; e < 4; e++) {
      const int i = jj * 8 + e * 2;
      p[e] = pack_bf16(swiglu(prv[i], prv[i + 32]), swiglu(prv[i + 1], prv[i + 33]));
    }
    stmatrix_x4(sbase + SM_STG + f.o[jj], p[0], p[1], p[2], p[3]);
    m_step(cur, sbase, wgoff, r);
  }
  request_store(sbase + B_STREQ);
}

__device__ __forceinline__ uint32_t bad2(uint32_t a, uint32_t b, unsigned par) {
  uint32_t d; asm("lop3.b32 %0, %1, %2, %3, 0x7E;" : "=r"(d) : "r"(a), "r"(b), "r"(par)); return d;
}
__device__ __forceinline__ uint32_t bad4(const uint4& v, unsigned par) { return bad2(v.x, v.y, par) | bad2(v.z, v.w, par); }
__device__ __forceinline__ uint32_t hi_halves(uint32_t lo, uint32_t hi) { return __byte_perm(lo, hi, 0x7632); }

__device__ __forceinline__ void gather_table(const float* src, uint32_t dst, uint32_t bar, unsigned par, uint32_t dl) {
  asm volatile("{\n.reg .pred p, e;\n.reg .b32 s<4>, c<4>, t<4>, w<4>;\n"
               "elect.sync _|e, 0xffffffff;\n"
               "LAB_POLL:\n"
               "ld.relaxed.gpu.global.v4.u32 {s0, s1, s2, s3}, [%0];\n"
               "ld.relaxed.gpu.global.v4.u32 {c0, c1, c2, c3}, [%0 + 4096];\n"
               "prmt.b32 w0, c0, c1, 0x7632;\nprmt.b32 w1, c2, c3, 0x7632;\nprmt.b32 w2, s0, s1, 0x7632;\nprmt.b32 w3, s2, s3, 0x7632;\n"
               "st.shared.v4.b32 [%1], {w0, w1, w2, w3};\n"
               "lop3.b32 t0, s0, s1, %3, 0x7E;\nlop3.b32 t1, s2, s3, %3, 0x7E;\nlop3.b32 t2, c0, c1, %3, 0x7E;\nlop3.b32 t3, c2, c3, %3, 0x7E;\n"
               "lop3.b32 t0, t0, t1, 1, 0xA8;\nlop3.b32 t2, t2, t3, 1, 0xA8;\n"
               "or.b32 t0, t0, t2;\n"
               "setp.eq.u32 p, t0, 0;\n"
               "vote.sync.all.pred p, p, 0xffffffff;\n"
               "@p bra.uni LAB_OK;\n"
               "mov.u32 t0, %%clock;\nsub.s32 t0, t0, %4;\nsetp.lt.s32 p, t0, 0;\n"
               "vote.sync.all.pred p, p, 0xffffffff;\n"
               "@p bra.uni LAB_POLL;\n"
               "LAB_OK:\n"
               "@e mbarrier.arrive.shared::cta.b64 _, [%2];\n}"
               :: "l"(src), "r"(dst), "r"(bar), "r"(par), "r"(dl) : "memory");
}

__device__ __forceinline__ int other_slot(int i, int j) { return i < 4 ? (~j & 4) + i : (j & 4) + i - 4 + (i - 4 >= (j & 3)); }

__device__ __forceinline__ int aux_col(int a, int u) { return u < 8 ? (a & 1) * 1024 + (2 * u + (a >> 1)) * 64 : 2048 + ((u - 8) * 4 + a) * 64; }
constexpr int NA = 7;
constexpr uint32_t A_FULL = SM_BAR, A_EMPTY = SM_BAR + 64, A_SUM = SM_BAR + 128, A_FREE = SM_BAR + 136, SM_RED = SM_VEC;
__device__ __forceinline__ void aux_role(const Maps& maps, const bf16* __restrict__ cvec, Mail* mail0, int zero, int a, uint32_t sbase, int wid) {
  const int tid = threadIdx.x, lane = tid & 31;
  const uint32_t dl = clock32() + 800000000u;
  int st = 0; uint32_t ph = 0;
  if (wid == 8) {
    prefetch_tmap(&maps.wmod);
    #pragma unroll
    for (int i = 0; i < 18; i++) mbar_init_e(sbase + A_FULL + 8 * i, i < 8 ? 1 : i < 17 ? 8 : 2);
    fence_proxy_async_smem();
    bar_arrive(0, 352);
    PROF(39, lane == 0);
    #pragma unroll
    for (int i = 0; i < NA; i++) {
      mbar_expect_tx_e(sbase + A_FULL + 8 * i, 32768);
      tma_load_2d(sbase + i * MSLOT, &maps.wmod, sbase + A_FULL + 8 * i, aux_col(a, i >> 2), (i & 3) * 256);
    }
    PROF(40, lane == 0);
    #pragma unroll 1
    for (int i = NA; i < 96; i++) {
      if (i >= AUX_SLOW) wait_until(clock32() + AUX_GAP);
      if (i == 8) wait_until(dl - 800000000u + AUX_HOLD);
      mbar_wait(sbase + A_EMPTY + 8 * st, ph, dl);
      mbar_expect_tx_e(sbase + A_FULL + 8 * st, 32768);
      tma_load_2d<true>(sbase + st * MSLOT, &maps.wmod, sbase + A_FULL + 8 * st, aux_col(a, i >> 2), (i & 3) * 256);
      if (++st == NA) { st = 0; ph ^= 1; }
    }
  } else if (wid < 8) {
    const int g = lane >> 2, qd = lane & 3;
    uint32_t sc[16];
    const uint2 c = *reinterpret_cast<const uint2*>(cvec + tid * 4);
    sts64(sbase + SM_RED + tid * 8, pack_bf16(silu_f(bf_lo(c.x)), silu_f(bf_hi(c.x))), pack_bf16(silu_f(bf_lo(c.y)), silu_f(bf_hi(c.y))));
    bar_sync(0, 352);
    #pragma unroll
    for (int i = 0; i < 16; i++) sc[i] = lds32(sbase + SM_RED + ((i >> 2) * 256 + wid * 32 + (i & 3) * 8 + qd * 2) * 2);
    bar_sync(NB_CONS, 256);
    PROF(38, tid == 0);
    const uint32_t aoff = (wid * 32 + (lane & 7) + (lane >> 4) * 8) * 128 + ((((lane >> 3) & 1) ^ (lane & 7)) << 4);
    uint32_t w[2][8][4];
    auto fetch = [&](uint32_t (&f)[8][4]) {
      mbar_wait(sbase + A_FULL + 8 * st, ph, dl);
      #pragma unroll
      for (int e = 0; e < 8; e++) ldmatrix_x4_t((sbase + st * MSLOT + aoff + (e >> 2) * 2048) ^ ((e & 3) << 5), f[e]);
      if (++st == NA) { st = 0; ph ^= 1; }
    };
    #pragma unroll 1
    for (int u = 0; u < 24; u++) {
      float acc[4][4];
      #pragma unroll
      for (int m = 0; m < 4; m++) acc[m][0] = acc[m][1] = acc[m][2] = acc[m][3] = 0.f;
      fetch(w[0]);
      #pragma unroll
      for (int q = 0; q < 4; q++) {
        PROF(30 + (u & 1) * 4 + q, u < 2 && tid == 0);
        const uint32_t rel = sbase + A_EMPTY + 8 * (st == 0 ? NA - 1 : st - 1);
        if (q < 3) fetch(w[(q + 1) & 1]);
        uint32_t dep = 0;
        #pragma unroll
        for (int e = 0; e < 8; e++) dep |= w[q & 1][e][0];
        mbar_arrive_e(rel + (dep & zero));
        if (q == 1) mbar_wait(sbase + A_FREE, (u & 1) ^ 1, dl);
        #pragma unroll
        for (int e = 0; e < 8; e++) {
          const uint32_t (&f)[4] = w[q & 1][e];
          mma16(acc[e & 3], f[0], f[1], f[2], f[3], sc[4 * q + 2 * (e >> 2)], sc[4 * q + 2 * (e >> 2) + 1]);
        }
      }
      const float v0 = qd & 2 ? (qd & 1 ? acc[3][0] : acc[2][0]) : (qd & 1 ? acc[1][0] : acc[0][0]);
      const float v1 = qd & 2 ? (qd & 1 ? acc[3][2] : acc[2][2]) : (qd & 1 ? acc[1][2] : acc[0][2]);
      sts64(sbase + SM_RED + wid * 256 + (qd * 8 + g) * 8, __float_as_uint(v0), __float_as_uint(v1));
      mbar_arrive_e(sbase + A_SUM);
      if (u < AUX_URG) mbar_wait(sbase + A_FREE, u & 1, dl);
    }
  } else if (wid < 11) {
    float* const mail = &mail0->mod[(wid - 9) * 4 * 6 * D_ + 2 * lane];
    unsigned par = ld_relaxed(&mail0->flags[FL_EPOCH + (lane >> 5)]);
    bar_sync(0, 352);
    par = (par + 1) & 1;
    #pragma unroll 1
    for (int u = -2; u < 24; u++) {
      if (u >= 0) {
        const int col = aux_col(a, u);
        const float add = (col >> 10) == 1 || (col >> 10) == 4 ? 1.f : 0.f;
        const float mul = col < 3 * D_ ? 1.f : col < 5 * D_ ? 0.5f : 2.f;
        mbar_wait(sbase + A_SUM, u & 1, dl);
        float2 v[8];
        #pragma unroll
        for (int w = 0; w < 8; w++) v[w] = lds64f(sbase + SM_RED + w * 256 + lane * 8);
        const float t0 = ((v[0].x + v[1].x) + (v[2].x + v[3].x)) + ((v[4].x + v[5].x) + (v[6].x + v[7].x));
        const float t1 = ((v[0].y + v[1].y) + (v[2].y + v[3].y)) + ((v[4].y + v[5].y) + (v[6].y + v[7].y));
        mbar_arrive_e(sbase + A_FREE + (__float_as_uint(t0 + t1) & zero));
        const uint32_t w = pack_bf16((add + bf16_round(t0)) * mul, (add + bf16_round(t1)) * mul), o = __shfl_xor_sync(0xffffffffu, w, 1);
        const uint32_t m0 = (lane & 1) ? (o & 0xFFFF0000u) : (w << 16), m1 = (lane & 1) ? (w & 0xFFFF0000u) : (o << 16);
        #pragma unroll
        for (int c = 0; c < 4; c++) st_rlx_v2(mail + c * 6 * D_ + col, m0 | par, m1 | par, true);
        PROF(1 + u, tid == 288);
      }
      #pragma unroll 1
      for (int v = 2 * (u + 2); v < 2 * (u + 3) && v < 24; v++)
        #pragma unroll
        for (int c = 0; c < 4; c++) st_rlx_v2(mail + c * 6 * D_ + aux_col(a, v), par ^ 1, par ^ 1, true);
    }
    const int t = a * 64 + tid - 288;
    #pragma unroll 4
    for (int i = t; i < 16 * 16 * 256; i += 256) mail0->halo[par ^ 1][i] = make_uint4(0, 0, 0, 0);
    #pragma unroll 4
    for (int i = t; i < 16 * 8 * 64; i += 256) mail0->st2[par ^ 1][i] = make_uint4(0, 0, 0, 0);
  }
}

template <int MODE>
__global__ void __launch_bounds__(384, 1)
fused_block_kernel(const bf16* __restrict__ x, const bf16* __restrict__ cvec, const bf16* __restrict__ wmod, Mail* mail0, int zero,
                   const __grid_constant__ Maps maps) {
  extern __shared__ __align__(1024) uint8_t smem_raw[];
  const uint32_t sbase = smem_u32(smem_raw);
  const int tid = threadIdx.x, lane = tid & 31;
  PROFN(0, tid == 0);
  const int wid = __shfl_sync(0xffffffffu, tid >> 5, 0);
  const int b = cta_role<MODE>();
  if (b >= NCTA) { aux_role(maps, cvec, mail0, zero, b - NCTA, sbase, wid); return; }
  const int jg = b >> 6, mb = jg ? 31 - (b >> 2) : (b >> 2), j = 4 * jg + (b & 3);
  const uint32_t dl = clock32() + 800000000u;
  unsigned* const flags = &mail0->flags[mb * 32];
  const int row0 = mb * 128;

  if (wid >= 8) {
    if (wid == 8) {
      #pragma unroll
      for (int i = 0; i < 8; i++) mbar_init_e(sbase + B_X + 8 * i, 1);
      fence_proxy_async_smem();
      mbar_expect_tx_e(sbase + B_X, 4096);
      bulk_load(sbase + SM_XR, x + (size_t)(row0 + j * 16) * D_, 4096, sbase + B_X);
    } else if (wid == 11) {
      #pragma unroll
      for (int i = 0; i < 12; i++) prefetch_tmap(&maps.x + i);
    } else if (wid == 9) {
      #pragma unroll
      for (uint32_t bar = B_EQ; bar < B_FM; bar += 8) mbar_init_e(sbase + bar, bar < B_FQ ? 8 : bar == B_FQ + 8 || bar == B_FQ + 24 ? 2 : 1);
      fence_proxy_async_smem();
    } else {
      #pragma unroll
      for (uint32_t bar = B_FM; bar < B_END; bar += 8) mbar_init_e(sbase + bar, 1);
      fence_proxy_async_smem();
    }
    bar_sync(0, 384);
    reg_dealloc<40>();
    PROF(92, tid == 256);
    if (wid == 8) {
      uint32_t tnext = clock32();
      #pragma unroll 1
      for (int q = 1; q < 8; q++) {
        wait_until(tnext);
        mbar_expect_tx_e(sbase + B_X + 8 * q, 4096);
        bulk_load(sbase + SM_XR + q * 4096, x + (size_t)(row0 + j * 16 + 2 * q) * D_, 4096, sbase + B_X + 8 * q);
        tnext += X_GAP;
      }
      #pragma unroll 1
      for (int u = 0; u < 16; u++) {
        const int st = u & 3;
        if (u == 1) mbar_wait(sbase + B_X + 56, 0, dl);
        if (u == 2) { mbar_wait(sbase + B_GATE, 0, dl); PROFN(60, lane == 0); }
        if (u == 3) mbar_wait(sbase + B_EQ, 0, dl);
        mbar_wait(sbase + B_EQ + 8 * st, ((u >> 2) & 1) ^ 1, dl);
        const uint32_t slot = sbase + st * QSLOT, fb = sbase + B_FQ + 8 * st;
        mbar_expect_tx_e(fb, u == 0 ? 65536 : u == 15 ? 32768 : 49152);
        if ((u & 1) && (u < MSEP || u == 15)) mbar_arrive_e(fb);
        if (u == 0) tma_load_3d(sbase + SM_X0, &maps.x, fb, 0, mb * 64, 0);
        tma_load_4d<true>(slot + 16384, &maps.wqk, fb, 0, u * 64, j, 0);
        tma_load_4d<true>(slot + 32768, &maps.wvv, fb, 0, u * 64, j, 0);
        if (u < 15) tma_load_3d(slot, &maps.x, fb, u * 64 + 64, mb * 64, 0);
      }
      const unsigned e1 = 1 + ld_relaxed(flags + FO_EPOCH);
      Ring r{0, 1, 0, dl};
      uint32_t slot, fb;
      auto acquire = [&](uint32_t bytes) {
        mbar_wait(sbase + B_EM + 8 * r.st, r.ph, dl);
        slot = sbase + r.st * MSLOT; fb = sbase + B_FM + 8 * r.st;
        mbar_expect_tx_e(fb, bytes);
        ring_next(r);
      };
      #pragma unroll 1
      for (int kt = 0; kt < 16; kt++) {
        if (kt < 5) mbar_wait(sbase + B_EQ + 8 * (kt - (kt >= 2)), 1, dl);
        if ((kt & 7) == 0) { PROF(46, lane == 0 && kt == 8); mbar_wait(sbase + B_FLG + kt, 0, dl); PROF(47, lane == 0 && kt == 8); }
        acquire(32768);
        tma_load_4d<true>(slot + 16384, &maps.wq1, fb, (j + 8) * 64, (kt & 1) * 64 + (kt & 6) * 8, (kt >> 3) * 4, 0);
        tma_load_3d(slot, &maps.hh, fb, (kt & 7) * 64, row0, kt >> 3);
      }
      PROF(82, lane == 0);
      mbar_wait(sbase + B_FLG + 16, 0, dl);
      PROF(83, lane == 0);
      #pragma unroll 1
      for (int kt = 0; kt < 8; kt++) {
        if (kt == 4) {
          acquire(32768);
          tma_load_3d(slot, &maps.x, fb, j * 128, mb * 64, 0);
          tma_load_3d(slot + 16384, &maps.x, fb, j * 128 + 64, mb * 64, 0);
        }
        acquire(32768);
        tma_load_3d<true>(slot + 16384, &maps.wo, fb, 0, kt * 64, 2 * j);
        tma_load_2d(slot, &maps.o, fb, kt * 64, row0);
      }
      acquire(16384);
      tma_load_3d<true>(slot + 16384, &maps.wo, fb, 0, (8 + j) * 64, 2 * j);
      auto deferred = [&](const CUtensorMap* map, const unsigned* flag, Ring ra, int n, int col0, int step) {
        uint32_t dst = sbase + ra.st * MSLOT, bar = sbase + B_FM + 8 * ra.st, col = col0 + other_slot(0, j) * step;
        asm volatile("" : "+r"(dst), "+r"(bar), "+r"(col));
        wait_flag(flag, e1 * NCTA, dl);
        tma_load_2d(dst, map, bar, col, row0);
        #pragma unroll 1
        for (int i = 1; i < n; i++) { ring_next(ra); tma_load_2d(sbase + ra.st * MSLOT, map, sbase + B_FM + 8 * ra.st, col0 + other_slot(i, j) * step, row0); }
      };
      {
        const Ring ra = r;
        #pragma unroll 1
        for (int i = 0; i < 7; i++) {
          const int kt = 8 + other_slot(i, j);
          acquire(32768);
          tma_load_3d<true>(slot + 16384, &maps.wo, fb, 0, kt * 64, 2 * j);
          if (i == WPRE - 1) { deferred(&maps.o, &mail0->flags[FL_O], ra, WPRE, 512, 64); PROFN(61, lane == 0); }
          if (i >= WPRE) tma_load_2d(slot, &maps.o, fb, kt * 64, row0);
        }
      }
      #pragma unroll 1
      for (int t = 0; t < 2; t++) {
        acquire(32768);
        tma_load_2d<true>(slot, &maps.w1, fb, j * 64, (2 * j + t) * 64);
        tma_load_2d<true>(slot + 8192, &maps.w3, fb, j * 64, (2 * j + t) * 64);
        tma_load_2d<true>(slot + 16384, &maps.w1, fb, (8 + j) * 64, (2 * j + t) * 64);
        tma_load_2d<true>(slot + 24576, &maps.w3, fb, (8 + j) * 64, (2 * j + t) * 64);
      }
      {
        const Ring ra = r;
        #pragma unroll 1
        for (int i = 0; i < GPRE; i++) {
          const int kt = 2 * other_slot(i, j);
          acquire(32768);
          tma_load_2d<true>(slot + 16384, &maps.w1, fb, j * 64, kt * 64);
          tma_load_2d<true>(slot + 24576, &maps.w3, fb, j * 64, kt * 64);
        }
        deferred(&maps.h2, &mail0->flags[FL_H2], ra, GPRE, 0, 128);
        PROFN(62, lane == 0);
        mbar_arrive_e(sbase + B_H2A);
      }
      #pragma unroll 1
      for (int gt = 0; gt < 7; gt++) {
        const int ncol = (8 * gt + j) * 64;
        #pragma unroll 1
        for (int i = (gt == 0 ? GPRE : 0); i < (gt < 2 ? 14 : 16); i++) {
          const int kt = gt >= 2 ? i : i < 7 ? 2 * other_slot(i, j) : 2 * other_slot(i - 7, j) + 1;
          if (gt == 0 && i == 7) mbar_wait(sbase + B_FLG + 32, 0, dl);
          acquire(32768);
          tma_load_2d<true>(slot + 16384, &maps.w1, fb, ncol, kt * 64);
          tma_load_2d<true>(slot + 24576, &maps.w3, fb, ncol, kt * 64);
          tma_load_2d(slot, &maps.h2, fb, kt * 64, row0);
        }
      }
      #pragma unroll 1
      for (int kt = 0; kt < 56; kt++) {
        if ((kt & 7) == 0) mbar_wait(sbase + B_FLG + 40 + kt, 0, dl);
        acquire(32768);
        tma_load_3d(slot + 16384, &maps.w2, fb, 0, kt * 64, 2 * j);
        tma_load_3d(slot, &maps.hh, fb, (kt & 7) * 64, row0, kt >> 3);
      }
    } else {
      const unsigned e1 = 1 + ld_relaxed(wid == 9 ? flags + FO_EPOCH : &mail0->flags[FL_EPOCH]), par = e1 & 1;
      if (wid == 9) {
        #pragma unroll 1
        for (int n = 0; n < 12; n++) {
          if (n == 4) {
            mbar_wait(sbase + B_STH, 0, dl);
            tma_store_2d(&maps.h2, sbase + SM_STG, j * 128, row0);
            bulk_commit();
            bulk_wait0();
            red_add_e(&mail0->flags[FL_H2], 1);
            PROF(84, lane == 0);
            mbar_wait(sbase + B_H2A, 0, dl);
          }
          if (n >= 1 && n <= 4) mbar_wait(sbase + B_STREQ, n & 1, dl); else mbar_sleep(sbase + B_STREQ, n & 1, dl);
          if (n == 0) fence_proxy_async_smem();
          if (n == 2 || n == 3) tma_store_2d(&maps.o, sbase + SM_STG, (j + 8 * (n - 2)) * 64, row0);
          else if (n == 4) tma_store_2d(&maps.h2, sbase + SM_STG + 16384, j * 128 + 64, row0);
          else tma_store_3d(&maps.hh, sbase + SM_STG + (n == 1 ? 16384 : 0), j * 64, row0, n < 2 ? n : n - 5);
          bulk_commit();
          bulk_wait0();
          red_add_e(n == 3 ? &mail0->flags[FL_O] : flags + FO_CNT + n, 1);
          mbar_arrive_e(sbase + B_STFREE);
          PROFN(70 + n, lane == 0 && n > 0); PROF(85, lane == 0 && n == 0);
          if (n != 3) { wait_flag(flags + FO_CNT + n, e1 * 8, dl); mbar_arrive_e(sbase + B_FLG + 8 * n); }
        }
      } else {
        mbar_wait(sbase + B_X + 24, 0, dl);
        const float* const mail = &mail0->mod[(b & 7) * 6 * D_ + lane * 4];
        if (wid == 10) {
          #pragma unroll 1
          for (int p = 0; p < 8; p++) {
            if (p >= 2) mbar_wait(p == 2 ? q_empty(0, sbase) : q_empty(2 * p - 5, sbase), p == 2 ? 0 : ((2 * p - 5) >> 2) & 1, dl);
            gather_table(mail + p * 128, sbase + SM_MODT + (p & 3) * 512 + ((lane * 16) ^ ((j >> 1) << 6)), 2 * p - 1 < MSEP ? sbase + B_MOD + 8 * p : sbase + B_FQ + 8 * ((2 * p - 1) & 3), par, dl);
            PROF(63 + p, lane == 0 && p < 7);
          }
          const uint32_t vdst = sbase + SM_VEC + (lane >> 3) * 64 + (lane & 3) * 16 + ((lane >> 2) & 1) * 8;
          #pragma unroll 1
          for (int v = 0; v < 2; v++) {
            mbar_sleep(sbase + B_FLG + 16 + 24 * v, 0, dl);
            uint4 m[3];
            while (true) {
              #pragma unroll
              for (int e = 0; e < 3; e++) m[e] = ld_rlx_v4(mail + (2 + v + e) * 1024 + j * 128);
              if (poll_done(((bad4(m[0], par) | bad4(m[1], par) | bad4(m[2], par)) & 1) == 0, dl)) break;
              __nanosleep(200);
            }
            #pragma unroll
            for (int e = 0; e < 3; e++) sts64(vdst + (v + e) * 256, hi_halves(m[e].x, m[e].y), hi_halves(m[e].z, m[e].w));
            mbar_arrive_e(sbase + B_VEC + 8 * v);
            PROF(70, lane == 0 && v == 0);
          }
        } else {
          mbar_wait(sbase + B_LN, 0, dl);
          red_add_e(&mail0->flags[FL_LN1], 1);
          wait_flag(&mail0->flags[FL_LN1], e1 * NCTA, dl);
          mbar_arrive_e(sbase + B_GATE);
          PROF(41, lane == 0);
        }
      }
    }
  } else {
    const int wg = wid >> 2, warp = wid & 3;
    const int g = lane >> 2, qd = lane & 3;
    bulk_prefetch(wmod + (size_t)(b * 8 + wid) * (6 * D_), PF_BYTES);
    bulk_prefetch(wmod + (size_t)(b * 8 + wid) * (6 * D_) + D_, PF_BYTES);
    bar_sync(0, 384);
    bulk_prefetch(wmod + (size_t)(b * 8 + wid) * (6 * D_) + PF_BYTES / 2, PF_BYTES);
    bulk_prefetch(wmod + (size_t)(b * 8 + wid) * (6 * D_) + PF_BYTES / 2 + D_, PF_BYTES);
    const unsigned e1 = 1 + ld_relaxed(flags + FO_EPOCH), par = e1 & 1;
    reg_alloc<232>();
    PROF(1, tid == 0);
    const uint32_t wgoff = wg * 8192;
    const uint32_t frag0 = wid * 2048 + (lane & 15) * 128 + (((lane >> 4) ^ (lane & 7)) << 4);
    const uint32_t slab = sbase + SM_STG + wid * 2048;

    LnRow ln;
    {
      uint2* const lmail = &mail0->ln1[(mb * 8 + (lane & 1) * 4 + (j >> 1)) * 16 + (j & 1) * 8 + wid];
      st_rlx_v2(lmail, par ^ 1, par ^ 1, lane < 2);
      mbar_wait(sbase + B_X + 8 * wid, 0, dl);
      PROF(3, tid == 224); PROF(93, tid == 0);
      float s[2][2] = {{0.f, 0.f}, {0.f, 0.f}}, q2[2][2] = {{0.f, 0.f}, {0.f, 0.f}};
      #pragma unroll
      for (int c = 0; c < 8; c++) {
        const uint4 v = lds128(sbase + SM_XR + wid * 4096 + c * 512 + lane * 16);
        const uint32_t vv[4] = {v.x, v.y, v.z, v.w};
        #pragma unroll
        for (int e = 0; e < 4; e++) {
          const float lo = bf_lo(vv[e]), hi = bf_hi(vv[e]);
          s[c >> 2][0] += lo; s[c >> 2][1] += hi; q2[c >> 2][0] = fmaf(lo, lo, q2[c >> 2][0]); q2[c >> 2][1] = fmaf(hi, hi, q2[c >> 2][1]);
        }
      }
      const bool odd = lane & 1;
      float sm = (s[0][0] + s[0][1]), so = (s[1][0] + s[1][1]), qm = (q2[0][0] + q2[0][1]), qo = (q2[1][0] + q2[1][1]);
      { const float a = odd ? so : sm, c = odd ? qo : qm;
        sm = a + __shfl_xor_sync(0xffffffffu, odd ? sm : so, 1); qm = c + __shfl_xor_sync(0xffffffffu, odd ? qm : qo, 1); }
      #pragma unroll
      for (int o = 2; o < 32; o <<= 1) { sm += __shfl_xor_sync(0xffffffffu, sm, o); qm += __shfl_xor_sync(0xffffffffu, qm, o); }
      sm *= (1.f / D_);
      ln_row(ln, 0, sm, fast_rsqrt(fmaxf(qm * (1.f / D_) - sm * sm, 0.f) + 1e-5f));
      st_rlx_v2(lmail, (ln.rs[0] << 16) | par, (ln.nb[0] << 16) | par, lane < 2);
      mbar_arrive_e(sbase + B_LN);
      PROF(4, tid == 224);
    }

    uint4* const halo_out = mail0->halo[par] + ((mb * 16 + j) * 2 + wg) * 128 + lane;
    const uint4* const halo_in = halo_out - 16 * 256;
    const uint32_t xch = sbase + SM_XCH + (tid >> 5) * 2048 + lane * 16;
    const bool noprev = mb == 0 && warp == 0, remote = mb > 0 && warp == 0;
    float a0[64], a1[64];
    uint32_t x2[32];
    Ring r{zero, 0, 0, dl};
    Frag8 qA, qB, kA, kB, vA, vB, wA, wB;
    {
      float acc[128];
      uint32_t A0[16], A1[16];
      undef_regs(acc);
      const uint32_t tab = sbase + SM_MODT + qd * 16;
      uint4 p[4];
      const uint32_t rot = j >> 1;
      Frag4 fq;
      #pragma unroll
      for (int q = 0; q < 4; q++) fq.o[q] = frag0 ^ ((q ^ rot) << 5);
      mbar_wait(sbase + B_LN, 0, dl);
      const uint2* const lin = &mail0->ln1[(mb * 8 + wid) * 16 + g];
      uint2 v0, v1;
      do { v0 = ld_rlx_v2(lin); v1 = ld_rlx_v2(lin + 8); } while (!poll_done(((bad2(v0.x, v0.y, par) | bad2(v1.x, v1.y, par)) & 1) == 0, dl));
      ln.rs[0] = hi_halves(v0.x, v0.x); ln.nb[0] = hi_halves(v0.y, v0.y); ln.rs[1] = hi_halves(v1.x, v1.x); ln.nb[1] = hi_halves(v1.y, v1.y);
      q_wait(0, sbase, dl);
      mbar_wait(sbase + B_MOD, 0, dl);
      #pragma unroll
      for (int kk = 0; kk < 4; kk++) q_load(A0, p, kk, sbase + SM_X0, fq, tab);
      PROF(5, tid == 0);
      q_step_rs<true>(acc, A0, A1, p, 0, sbase, fq, tab, ln, rot, !(j & 1), true, dl, wg, zero);
      #pragma unroll
      for (int u = 1; u < 15; u += 2) {
        q_step_rs<true>(acc, A1, A0, p, u, sbase, fq, tab, ln, rot, j & 1, false, dl, wg, zero);
        q_step_rs<true>(acc, A0, A1, p, u + 1, sbase, fq, tab, ln, rot, !(j & 1), false, dl, wg, zero);
        if (u == 7) mbar_arrive_e(sbase + B_STREQ);
      }
      q_step_rs<false>(acc, A1, A0, p, 15, sbase, fq, tab, ln, rot, j & 1, false, dl, wg, zero);
      PROF(7, tid == 0);
      mbar_wait(sbase + B_STFREE, 0, dl);
      request_store(sbase + B_STREQ);
      wgmma_wait<0>();
      undef_regs(a0);
      { const uint32_t slot = m_wait(sbase, r); mma_step(a0, slot + wgoff, slot + 16384, true, q_empty(15, sbase)); m_next(r); }
      fence_regs(acc);
      PROF(8, tid == 0);
      sched_fence(zero);
      pack_half(vB, acc, 64, 1); transpose8(vB);
      m_step(a0, sbase, wgoff, r);
      sched_fence(zero);
      pack_half(kB, acc, 32, 1);
      attn_send(vB, 1, xch - 16384, warp, halo_out, mb < 15); attn_send(kB, 0, xch - 16384, warp, halo_out, mb < 15);
      m_step(a0, sbase, wgoff, r);
      sched_fence(zero);
      pack_half(qA, acc, 0, 0); pack_half(qB, acc, 0, 1); pack_half(kA, acc, 32, 0); pack_half(wB, acc, 96, 1); pack_half(wA, acc, 96, 0);
      m_step(a0, sbase, wgoff, r);
      sched_fence(zero);
      pack_half(vA, acc, 64, 0); transpose8(vA);
    }
    uint4 wP[2];
    Frag4 frag;
    #pragma unroll
    for (int q = 0; q < 4; q++) frag.o[q] = frag0 ^ (q << 5);
    {
      m_step(a0, sbase, wgoff, r);
      uint4 pv[4];
      attn_recv<4>(pv, 0, xch - 16384, wg, warp, halo_in, mb > 0);
      m_step(a0, sbase, wgoff, r);
      mbar_wait(sbase + B_STFREE, 1, dl);
      transpose8(wB);
      m_step(a0, sbase, wgoff, r);
      attn_check<4>(pv, 0, remote, halo_in, dl);
      wgmma_wait<0>();
      PROF(9, tid == 0);
      float o[2][5][4];
      sched_fence(zero);
      attn_core(qA, qB, kA, kB, vA, vB, pv, pv + 2, noprev, lane, o);
      attn_store(o, 0, sbase, frag);
      attn_store(o, 1, sbase, frag);
      request_store(sbase + B_STREQ);
      bar_sync(NB_CONS, 256);
      PROF(10, tid == 0);
      m_step(a0, sbase, wgoff, r);
      sched_fence(zero);
      attn_send(wB, 1, xch, warp, halo_out + 8 * 256, mb < 15);
      m_step(a0, sbase, wgoff, r);
      sched_fence(zero);
      transpose8(wA);
      #pragma unroll 1
      for (int i = 9; i < 15; i++) m_step(a0, sbase, wgoff, r);
      attn_recv<2>(wP, 2, xch, wg, warp, halo_in + 8 * 256, mb > 0);
      m_step(a0, sbase, wgoff, r);
    }
    {
      undef_regs(a1);
      {
        const uint32_t slot = m_wait(sbase, r);
        mma_step(a1, slot + wgoff, slot + 16384, true, m_prev(sbase, r), [&] {
          fence_regs(a0);
          pack_half(kB, a0, 32, 1);
          attn_send(kB, 0, xch, warp, halo_out + 8 * 256, mb < 15);
        });
        m_next(r);
      }
      PROF(14, tid == 0);
      sched_fence(zero);
      pack_half(kA, a0, 32, 0); pack_half(qA, a0, 0, 0); pack_half(qB, a0, 0, 1);
      m_step(a1, sbase, wgoff, r);
      attn_check<2>(wP, 2, remote, halo_in + 8 * 256, dl);
      uint4 kP[2];
      attn_recv<2>(kP, 0, xch, wg, warp, halo_in + 8 * 256, mb > 0);
      m_step(a1, sbase, wgoff, r);
      attn_check<2>(kP, 0, remote, halo_in + 8 * 256, dl);
      wgmma_wait<0>();
      PROF(15, tid == 0);
      float o[2][5][4];
      mbar_wait(sbase + B_STFREE, 0, dl);
      attn_core(qA, qB, kA, kB, wA, wB, kP, wP, noprev, lane, o);
      attn_store(o, 0, sbase, frag);
      attn_store(o, 1, sbase, frag);
      request_store(sbase + B_STREQ);
      bar_sync(NB_CONS, 256);
      PROF(16, tid == 0);
      auto residual = [&] {
        const uint32_t xs = m_wait(sbase, r), xe = sbase + B_EM + 8 * r.st;
        ring_next(r);
        #pragma unroll
        for (int t = 0; t < 2; t++) {
          #pragma unroll
          for (int jj = 4 * t; jj < 4 * t + 4; jj++) ldmatrix_x4(xs + t * 16384 + frag.o[jj & 3], x2[4 * jj], x2[4 * jj + 1], x2[4 * jj + 2], x2[4 * jj + 3]);
          if (t == 1) {
            uint32_t dep = 0;
            #pragma unroll
            for (int jj = 0; jj < 8; jj++) dep |= x2[4 * jj];
            mbar_arrive_e(xe + (dep & zero));
          }
          m_step(a1, sbase, wgoff, r);
        }
      };
      m_step(a1, sbase, wgoff, r);
      residual();
      #pragma unroll 1
      for (int i = 6; i < 8; i++) m_step(a1, sbase, wgoff, r);
      mma_step(a1, sbase + SM_STG + wgoff, m_wait(sbase, r) + 16384, false, m_prev(sbase, r));
      m_next(r);
      PROF(17, tid == 0);
      uint4* const sm = mail0->st2[par] + (mb * 8 + wid) * 64 + g;
      st_rlx_v4(sm + j * 8, 0, 0, 0, 0, qd == (g >> 1));
      #pragma unroll 1
      for (int i = 0; i < 7; i++) { m_step(a1, sbase, wgoff, r); PROF(42, tid == 0 && i == 0); }
      PROF(45, tid == 0);
      mbar_wait(sbase + B_VEC, 0, dl);
      mbar_wait(sbase + B_STFREE, 1, dl);
      const uint32_t vec = sbase + SM_VEC + qd * 16;
      uint4 ga[4];
      #pragma unroll
      for (int q = 0; q < 4; q++) ga[q] = lds128(vec + q * 64);
      wgmma_wait<0>();
      mbar_arrive_e(m_prev(sbase, r));
      fence_regs(a1);
      PROF(18, tid == 0);
      float gl[4] = {0.f, 0.f, 0.f, 0.f}, gh[4] = {0.f, 0.f, 0.f, 0.f};
      #pragma unroll
      for (int jj = 0; jj < 8; jj++) {
        uint32_t* v = &x2[4 * jj];
        const uint32_t wl = (jj & 1) ? ga[jj >> 1].z : ga[jj >> 1].x, wh = (jj & 1) ? ga[jj >> 1].w : ga[jj >> 1].y;
        #pragma unroll
        for (int e = 0; e < 4; e++) v[e] = fma_bf2(e & 2 ? wh : wl, pack_bf16(a1[8 * jj + 2 * e], a1[8 * jj + 2 * e + 1]), v[e]);
        mma16(gl, v[0], 0x3F803F80u, v[2], 0x3F803F80u, v[0], v[2]);
        mma16(gh, v[1], 0x3F803F80u, v[3], 0x3F803F80u, v[1], v[3]);
      }
      st_nonzero_v4(sm + j * 8, __float_as_uint(g & 1 ? gl[3] : gl[2]), __float_as_uint(g & 1 ? gl[1] : gl[0]),
                __float_as_uint(g & 1 ? gh[3] : gh[2]), __float_as_uint(g & 1 ? gh[1] : gh[0]), qd == (g >> 1));
      float s[2], q2[2];
      PROF(19, tid == 0);
      uint4 sb[4], cb[4];
      #pragma unroll
      for (int q = 0; q < 4; q++) { sb[q] = lds128(vec + 256 + q * 64); cb[q] = lds128(vec + 512 + q * 64); }
      uint4 p0, p1;
      while (true) {
        p0 = ld_rlx_v4(sm + qd * 16); p1 = ld_rlx_v4(sm + qd * 16 + 8);
        if (poll_done(min(min4(p0), min4(p1)) != 0, dl)) break;
      }
      PROF(20, tid == 0);
      s[0] = __uint_as_float(p0.x) + __uint_as_float(p1.x); q2[0] = __uint_as_float(p0.y) + __uint_as_float(p1.y);
      s[1] = __uint_as_float(p0.z) + __uint_as_float(p1.z); q2[1] = __uint_as_float(p0.w) + __uint_as_float(p1.w);
      #pragma unroll
      for (int o2 = 1; o2 <= 2; o2 <<= 1)
        #pragma unroll
        for (int h = 0; h < 2; h++) { s[h] += __shfl_xor_sync(0xffffffffu, s[h], o2); q2[h] += __shfl_xor_sync(0xffffffffu, q2[h], o2); }
      #pragma unroll
      for (int h = 0; h < 2; h++) {
        const float m = s[h] * (1.f / D_);
        ln_row(ln, h, m, fast_rsqrt(fmaxf(q2[h] * (1.f / D_) - m * m, 0.f) + 1e-5f));
      }
      #pragma unroll
      for (int jj = 0; jj < 8; jj++) {
        const uint32_t cl = (jj & 1) ? cb[jj >> 1].z : cb[jj >> 1].x, ch = (jj & 1) ? cb[jj >> 1].w : cb[jj >> 1].y;
        const uint32_t sl = (jj & 1) ? sb[jj >> 1].z : sb[jj >> 1].x, sh = (jj & 1) ? sb[jj >> 1].w : sb[jj >> 1].y;
        stmatrix_x4(sbase + SM_STG + (jj >> 2) * 16384 + frag.o[jj & 3], ln_mod(x2[4 * jj], ln, 0, cl, sl), ln_mod(x2[4 * jj + 1], ln, 1, cl, sl),
                    ln_mod(x2[4 * jj + 2], ln, 0, ch, sh), ln_mod(x2[4 * jj + 3], ln, 1, ch, sh));
        if (jj == 3) { request_store(sbase + B_STH); sched_fence(zero); }
      }
      request_store(sbase + B_STREQ);
      bar_sync(NB_WG + wg, 128);
      PROF(21, tid == 0);
    }

    undef_regs(a0);
    #pragma unroll
    for (int t = 0; t < 2; t++) {
      const uint32_t slot = m_wait(sbase, r);
      if (t == 0) mma_step<false>(a0, sbase + SM_STG + wgoff, slot, true, 0);
      else mma_step(a0, sbase + SM_STG + 16384 + wgoff, slot, false, m_prev(sbase, r));
      mma_step<false>(a1, sbase + SM_STG + t * 16384 + wgoff, slot + 16384, t == 0, 0);
      m_next(r);
    }
    PROF(22, tid == 0);
    #pragma unroll 1
    for (int t = 0; t < 7; t += 2) {
      g_switch(a1, a0, t == 0 ? 14 : 11, t > 0, 5 + t, sbase, wgoff, frag, r);
      if (t == 6) break;
      g_switch(a0, a1, t == 0 ? 9 : 11, true, 6 + t, sbase, wgoff, frag, r);
    }
    #pragma unroll 1
    for (int i = 5; i < 56 - DTAIL; i++) m_step(a1, sbase, wgoff, r);
    if (DTAIL) {
      if (wg == 1) { wgmma_wait<0>(); mbar_arrive_e(m_prev(sbase, r)); bar_sync(NB_ORD, 256); }
      #pragma unroll
      for (int i = 0; i < DTAIL; i++) {
        const uint32_t slot = m_wait(sbase, r);
        const uint32_t alo = ((slot + wgoff) >> 4) + (1u << 16), blo = ((slot + 16384) >> 4) + (512u << 16);
        wgmma_fence();
        #pragma unroll
        for (int k = 0; k < 4; k++) wgmma_m64n128k16_ss(a1, desc_from_lo(alo + k * 2), desc_from_lo(blo + k * 128), true);
        wgmma_commit();
        ring_next(r);
      }
      if (wg == 0) bar_arrive(NB_ORD, 256);
    }
    {
      mbar_wait(sbase + B_STFREE, 1, dl);
      mbar_wait(sbase + B_VEC + 8, 0, dl);
      uint4 gb[4];
      #pragma unroll
      for (int q = 0; q < 4; q++) gb[q] = lds128(sbase + SM_VEC + 768 + qd * 16 + q * 64);
      wgmma_wait<0>();
      fence_regs(a1);
      PROF(50, tid == 128);
      #pragma unroll
      for (int t = 0; t < 2; t++) {
        #pragma unroll
        for (int jj = 4 * t; jj < 4 * t + 4; jj++) {
          const uint32_t gl = (jj & 1) ? gb[jj >> 1].z : gb[jj >> 1].x, gh = (jj & 1) ? gb[jj >> 1].w : gb[jj >> 1].y;
          const int i = 8 * jj;
          stmatrix_x4(sbase + SM_STG + t * 16384 + frag.o[jj & 3],
                      fma_bf2(gl, pack_bf16(a1[i], a1[i + 1]), x2[4 * jj]), fma_bf2(gl, pack_bf16(a1[i + 2], a1[i + 3]), x2[4 * jj + 1]),
                      fma_bf2(gh, pack_bf16(a1[i + 4], a1[i + 5]), x2[4 * jj + 2]), fma_bf2(gh, pack_bf16(a1[i + 6], a1[i + 7]), x2[4 * jj + 3]));
        }
        fence_proxy_async_smem();
        tma_store_3d(&maps.out, slab + t * 16384, j * 128 + t * 64, mb * 64 + warp * 16, wg);
      }
      bulk_commit();
      st_rlx(tid == 0 ? flags + FO_EPOCH : &mail0->flags[FL_EPOCH], e1, j == 0 && (tid == 0 || (tid == 1 && mb == 0)));
      bulk_wait_read0();
      PROFN(51, tid == 128);
    }
  }
}

typedef CUresult (*PFN_encodeTiled)(CUtensorMap*, CUtensorMapDataType, cuuint32_t, void*, const cuuint64_t*, const cuuint64_t*,
                                    const cuuint32_t*, const cuuint32_t*, CUtensorMapInterleave, CUtensorMapSwizzle,
                                    CUtensorMapL2promotion, CUtensorMapFloatOOBfill);

void encode(PFN_encodeTiled fn, CUtensorMap* m, const void* ptr, int rank, const cuuint64_t* dims, const cuuint64_t* strides,
            const cuuint32_t* box) {
  const cuuint32_t es[5] = {1, 1, 1, 1, 1};
  fn(m, CU_TENSOR_MAP_DATA_TYPE_BFLOAT16, rank, const_cast<void*>(ptr), dims, strides, box, es, CU_TENSOR_MAP_INTERLEAVE_NONE,
     CU_TENSOR_MAP_SWIZZLE_128B, CU_TENSOR_MAP_L2_PROMOTION_L2_256B, CU_TENSOR_MAP_FLOAT_OOB_FILL_NONE);
}
void map2d(PFN_encodeTiled fn, CUtensorMap* m, const void* ptr, int cols, int rows, int boxrows) {
  const cuuint64_t dims[2] = {(cuuint64_t)cols, (cuuint64_t)rows}, strides[1] = {(cuuint64_t)cols * 2};
  const cuuint32_t box[2] = {64, (cuuint32_t)boxrows};
  encode(fn, m, ptr, 2, dims, strides, box);
}
void map_w2chunk(PFN_encodeTiled fn, CUtensorMap* m, const void* ptr, int cols, int rows) {
  const cuuint64_t dims[3] = {64, (cuuint64_t)rows, (cuuint64_t)cols / 64}, strides[2] = {(cuuint64_t)cols * 2, 128};
  const cuuint32_t box[3] = {64, 64, 2};
  encode(fn, m, ptr, 3, dims, strides, box);
}
void map_parity(PFN_encodeTiled fn, CUtensorMap* m, const void* ptr, int boxpairs, int boxpar) {
  const cuuint64_t dims[3] = {D_, S_ / 2, 2}, strides[2] = {D_ * 4, D_ * 2};
  const cuuint32_t box[3] = {64, (cuuint32_t)boxpairs, (cuuint32_t)boxpar};
  encode(fn, m, ptr, 3, dims, strides, box);
}

}

extern "C" void kernel_launch(void* const* d_in, const int* in_sizes, int n_in, void* d_out, int out_size) {
  (void)in_sizes; (void)n_in; (void)out_size;
  const bf16* x = (const bf16*)d_in[0];
  const bf16* wqkv = (const bf16*)d_in[1];
  const bf16* wo = (const bf16*)d_in[2];
  const bf16* w1 = (const bf16*)d_in[4];
  const bf16* w3 = (const bf16*)d_in[5];
  const bf16* w2 = (const bf16*)d_in[6];
  const bf16* cvec = (const bf16*)d_in[7];
  const bf16* w_mod = (const bf16*)d_in[8];

  static PFN_encodeTiled fn = nullptr;
  static Maps maps;
  static const void* cached[8] = {};
  static int sms = 0;
  static void* mail = nullptr;
  if (!fn) {
    void* p = nullptr; cudaDriverEntryPointQueryResult st;
    cudaGetDriverEntryPoint("cuTensorMapEncodeTiled", &p, cudaEnableDefault, &st);
    fn = (PFN_encodeTiled)p;
    cudaFuncSetAttribute(fused_block_kernel<0>, cudaFuncAttributeMaxDynamicSharedMemorySize, SM_TOTAL + SM_PROF);
    cudaFuncSetAttribute(fused_block_kernel<1>, cudaFuncAttributeMaxDynamicSharedMemorySize, SM_TOTAL + SM_PROF);
    cudaFuncSetAttribute(fused_block_kernel<2>, cudaFuncAttributeMaxDynamicSharedMemorySize, SM_TOTAL + SM_PROF);
    cudaGetSymbolAddress(&mail, g_mail);
    int dev = 0;
    cudaGetDevice(&dev);
    cudaDeviceGetAttribute(&sms, cudaDevAttrMultiProcessorCount, dev);
  }
  const void* cur[8] = {x, wqkv, wo, w1, w3, w2, d_out, w_mod};
  bool same = true;
  for (int i = 0; i < 8; i++) same = same && cached[i] == cur[i];
  if (!same) {
    void *o, *h2, *hh;
    cudaGetSymbolAddress(&hh, g_hh); cudaGetSymbolAddress(&o, g_o);
    h2 = o;
    map_parity(fn, &maps.x, x, 64, 2); map_parity(fn, &maps.out, d_out, 16, 1);
    map2d(fn, &maps.o, o, D_, S_, 128); map2d(fn, &maps.h2, h2, D_, S_, 128);
    {
      const cuuint64_t dims[3] = {512, (cuuint64_t)S_, 7}, strides[2] = {1024, (cuuint64_t)S_ * 1024};
      const cuuint32_t box[3] = {64, 128, 1};
      encode(fn, &maps.hh, hh, 3, dims, strides, box);
    }
    {
      const cuuint64_t dims[4] = {64, 1024, 16, 2}, strides[3] = {3072 * 2, 128, 2048};
      const cuuint64_t dimv[4] = {64, 1024, 8, 2}, stridev[3] = {3072 * 2, 128, 1024};
      const cuuint32_t box[4] = {64, 64, 1, 2};
      encode(fn, &maps.wqk, wqkv, 4, dims, strides, box);
      encode(fn, &maps.wvv, wqkv + 2048, 4, dimv, stridev, box);
      const cuuint64_t dim1[4] = {1024, 128, 8, 2}, stride1[3] = {3072 * 2, 128 * 3072 * 2, 2048};
      const cuuint32_t box1[4] = {64, 16, 4, 2};
      encode(fn, &maps.wq1, wqkv, 4, dim1, stride1, box1);
    }
    map_w2chunk(fn, &maps.wo, wo, D_, D_); map_w2chunk(fn, &maps.w2, w2, D_, F_);
    map2d(fn, &maps.w1, w1, F_, D_, 64); map2d(fn, &maps.w3, w3, F_, D_, 64);
    map2d(fn, &maps.wmod, w_mod, 6 * D_, D_, 256);
    for (int i = 0; i < 8; i++) cached[i] = cur[i];
  }
  if (sms == NCTA + NAUX) {
    fused_block_kernel<0><<<NCTA + NAUX, 384, SM_TOTAL + SM_PROF>>>(x, cvec, w_mod, (Mail*)mail, 0, maps);
  } else {
    fused_block_kernel<1><<<NAUX, 384, SM_TOTAL + SM_PROF>>>(x, cvec, w_mod, (Mail*)mail, 0, maps);
    fused_block_kernel<2><<<NCTA, 384, SM_TOTAL + SM_PROF>>>(x, cvec, w_mod, (Mail*)mail, 0, maps);
  }
}
```

```cpp
#include <cuda.h>
#include <cuda_runtime.h>
#include <cuda_bf16.h>
#include <stdint.h>

namespace {

typedef __nv_bfloat16 bf16;

constexpr int S_ = 2048, D_ = 1024, F_ = 3584;
constexpr int NCTA = 128, NAUX = 4;

__device__ __align__(1024) bf16 g_o[S_ * D_];
__device__ __align__(1024) bf16 g_hh[S_ * F_];
constexpr int FO_EPOCH = 0, FO_CNT = 1;
constexpr int FL_EPOCH = 16 * 32, FL_LN1 = FL_EPOCH + 2, FL_H2 = FL_EPOCH + 3, FL_O = FL_EPOCH + 4;
struct Mail {
  unsigned flags[32 * 32];
  float mod[8 * 6 * D_];
  uint2 ln1[16 * 8 * 16];
  uint4 halo[2][16 * 16 * 2 * 4 * 32];
  uint4 st2[2][16 * 8 * 8 * 8];
};
__device__ __align__(1024) Mail g_mail;

template <int mode>
__device__ __forceinline__ int cta_role() {
  if (mode) return mode == 1 ? NCTA + (blockIdx.x & 3) : blockIdx.x & 127;
  uint32_t sm;
  asm("mov.u32 %0, %%smid;" : "=r"(sm));
  sm = (sm & ~3u) == 12 ? sm + 108 : (sm & ~3u) == 120 ? sm - 108 : sm;
  const int t = sm >> 1;
  int r;
  if (t < 32) r = (t & 7) * 16 + (t >> 3) * 2 + (sm & 1);
  else if (t < 60) r = (1 + (t - 32) % 7) * 16 + 8 + ((t - 32) / 7) * 2 + (sm & 1);
  else if (t < 62) r = NCTA + sm - 120;
  else r = sm - 116;
  return r;
}
#define PROF(slot, on) do {} while (0)
#define PROFN(slot, on) do {} while (0)
#define PROF_OUT(role, t) do {} while (0)
constexpr uint32_t SM_PROF = 0;

__device__ __forceinline__ uint32_t smem_u32(const void* p) { return (uint32_t)__cvta_generic_to_shared(p); }
#define ELECT "{\n.reg .pred p;\nelect.sync _|p, 0xffffffff;\n@p "
__device__ __forceinline__ void mbar_init_e(uint32_t bar, uint32_t count) {
  asm volatile(ELECT "mbarrier.init.shared::cta.b64 [%0], %1;\n}" :: "r"(bar), "r"(count) : "memory");
}
__device__ __forceinline__ void mbar_expect_tx_e(uint32_t bar, uint32_t bytes) {
  asm volatile(ELECT "mbarrier.arrive.expect_tx.shared::cta.b64 _, [%0], %1;\n}" :: "r"(bar), "r"(bytes) : "memory");
}
__device__ __forceinline__ void mbar_arrive_e(uint32_t bar) {
  asm volatile(ELECT "mbarrier.arrive.shared::cta.b64 _, [%0];\n}" :: "r"(bar) : "memory");
}
__device__ __forceinline__ uint32_t clock32() { uint32_t t; asm volatile("mov.u32 %0, %%clock;" : "=r"(t)); return t; }
__device__ __forceinline__ void mbar_wait(uint32_t bar, uint32_t parity, uint32_t dl) {
  asm volatile("{\n.reg .pred p, q;\n.reg .b32 t;\n"
               "mbarrier.try_wait.parity.shared::cta.b64 p, [%0], %1;\n"
               "@p bra LAB_DONE;\n"
               "LAB_WAIT:\n"
               "mbarrier.try_wait.parity.shared::cta.b64 p, [%0], %1;\n"
               "mov.u32 t, %%clock;\n"
               "sub.s32 t, t, %2;\n"
               "setp.lt.and.s32 q, t, 0, !p;\n"
               "@q bra LAB_WAIT;\n"
               "LAB_DONE:\n}" :: "r"(bar), "r"(parity), "r"(dl) : "memory");
}
__device__ __forceinline__ void mbar_sleep(uint32_t bar, uint32_t parity, uint32_t dl) {
  asm volatile("{\n.reg .pred p;\n.reg .b32 t;\n"
               "LAB_WAIT:\n"
               "mbarrier.try_wait.parity.shared::cta.b64 p, [%0], %1, 20000;\n"
               "@p bra LAB_DONE;\n"
               "mov.u32 t, %%clock;\n"
               "sub.s32 t, t, %2;\n"
               "setp.lt.s32 p, t, 0;\n"
               "@p bra LAB_WAIT;\n"
               "LAB_DONE:\n}" :: "r"(bar), "r"(parity), "r"(dl) : "memory");
}
__device__ __forceinline__ bool poll_done(bool ok, uint32_t dl) {
  return __all_sync(0xffffffffu, ok || (int)(clock32() - dl) >= 0);
}
__device__ __forceinline__ unsigned ld_relaxed(const unsigned* p) {
  unsigned v; asm volatile("ld.relaxed.gpu.global.u32 %0, [%1];" : "=r"(v) : "l"(p) : "memory"); return v;
}
__device__ __forceinline__ void red_add_e(unsigned* p, unsigned v) {
  asm volatile(ELECT "red.relaxed.gpu.global.add.u32 [%0], %1;\n}" :: "l"(p), "r"(v) : "memory");
}
__device__ __forceinline__ void wait_flag(const unsigned* p, unsigned target, uint32_t dl) {
  asm volatile("{\n.reg .pred p;\n.reg .b32 t;\n"
               "LAB_WAIT:\n"
               "ld.relaxed.gpu.global.u32 t, [%0];\n"
               "sub.s32 t, t, %1;\n"
               "setp.ge.s32 p, t, 0;\n"
               "@p bra LAB_DONE;\n"
               "mov.u32 t, %%clock;\n"
               "sub.s32 t, t, %2;\n"
               "setp.lt.s32 p, t, 0;\n"
               "@p bra LAB_WAIT;\n"
               "LAB_DONE:\n}" :: "l"(p), "r"(target), "r"(dl) : "memory");
}
__device__ __forceinline__ void wait_until(uint32_t t) { while ((int)(clock32() - t) < 0) {} }
__device__ __forceinline__ void fence_proxy_async_smem() { asm volatile("fence.proxy.async.shared::cta;" ::: "memory"); }

constexpr uint64_t EVICT_FIRST = 0x12F0000000000000ull;
template <bool STREAM = false>
__device__ __forceinline__ void tma_load_2d(uint32_t dst, const CUtensorMap* m, uint32_t bar, int c0, int c1) {
  if (STREAM)
    asm volatile(ELECT "cp.async.bulk.tensor.2d.shared::cluster.global.mbarrier::complete_tx::bytes.L2::cache_hint [%0], [%1, {%3, %4}], [%2], %5;\n}"
                 :: "r"(dst), "l"(m), "r"(bar), "r"(c0), "r"(c1), "l"(EVICT_FIRST) : "memory");
  else
    asm volatile(ELECT "cp.async.bulk.tensor.2d.shared::cluster.global.mbarrier::complete_tx::bytes [%0], [%1, {%3, %4}], [%2];\n}"
                 :: "r"(dst), "l"(m), "r"(bar), "r"(c0), "r"(c1) : "memory");
}
template <bool STREAM = false>
__device__ __forceinline__ void tma_load_3d(uint32_t dst, const CUtensorMap* m, uint32_t bar, int c0, int c1, int c2) {
  if (STREAM)
    asm volatile(ELECT "cp.async.bulk.tensor.3d.shared::cluster.global.mbarrier::complete_tx::bytes.L2::cache_hint [%0], [%1, {%3, %4, %5}], [%2], %6;\n}"
                 :: "r"(dst), "l"(m), "r"(bar), "r"(c0), "r"(c1), "r"(c2), "l"(EVICT_FIRST) : "memory");
  else
    asm volatile(ELECT "cp.async.bulk.tensor.3d.shared::cluster.global.mbarrier::complete_tx::bytes [%0], [%1, {%3, %4, %5}], [%2];\n}"
                 :: "r"(dst), "l"(m), "r"(bar), "r"(c0), "r"(c1), "r"(c2) : "memory");
}
template <bool STREAM = false>
__device__ __forceinline__ void tma_load_4d(uint32_t dst, const CUtensorMap* m, uint32_t bar, int c0, int c1, int c2, int c3) {
  if (STREAM)
    asm volatile(ELECT "cp.async.bulk.tensor.4d.shared::cluster.global.mbarrier::complete_tx::bytes.L2::cache_hint [%0], [%1, {%3, %4, %5, %6}], [%2], %7;\n}"
                 :: "r"(dst), "l"(m), "r"(bar), "r"(c0), "r"(c1), "r"(c2), "r"(c3), "l"(EVICT_FIRST) : "memory");
  else
    asm volatile(ELECT "cp.async.bulk.tensor.4d.shared::cluster.global.mbarrier::complete_tx::bytes [%0], [%1, {%3, %4, %5, %6}], [%2];\n}"
                 :: "r"(dst), "l"(m), "r"(bar), "r"(c0), "r"(c1), "r"(c2), "r"(c3) : "memory");
}
__device__ __forceinline__ void tma_store_2d(const CUtensorMap* m, uint32_t src, int c0, int c1) {
  asm volatile(ELECT "cp.async.bulk.tensor.2d.global.shared::cta.bulk_group [%0, {%2, %3}], [%1];\n}"
               :: "l"(m), "r"(src), "r"(c0), "r"(c1) : "memory");
}
__device__ __forceinline__ void tma_store_3d(const CUtensorMap* m, uint32_t src, int c0, int c1, int c2) {
  asm volatile(ELECT "cp.async.bulk.tensor.3d.global.shared::cta.bulk_group [%0, {%2, %3, %4}], [%1];\n}"
               :: "l"(m), "r"(src), "r"(c0), "r"(c1), "r"(c2) : "memory");
}
__device__ __forceinline__ void bulk_load(uint32_t dst, const void* src, uint32_t bytes, uint32_t bar) {
  asm volatile(ELECT "cp.async.bulk.shared::cluster.global.mbarrier::complete_tx::bytes [%0], [%1], %2, [%3];\n}"
               :: "r"(dst), "l"(src), "r"(bytes), "r"(bar) : "memory");
}
__device__ __forceinline__ void bulk_prefetch(const void* src, uint32_t bytes) {
  asm volatile(ELECT "cp.async.bulk.prefetch.L2.global [%0], %1;\n}" :: "l"(src), "r"(bytes) : "memory");
}
__device__ __forceinline__ void bulk_commit() { asm volatile("cp.async.bulk.commit_group;" ::: "memory"); }
__device__ __forceinline__ void bulk_wait0() { asm volatile("cp.async.bulk.wait_group 0;" ::: "memory"); }
__device__ __forceinline__ void bulk_wait_read0() { asm volatile("cp.async.bulk.wait_group.read 0;" ::: "memory"); }
__device__ __forceinline__ void prefetch_tmap(const CUtensorMap* m) { asm volatile(ELECT "prefetch.tensormap [%0];\n}" :: "l"(m) : "memory"); }
__device__ __forceinline__ void wgmma_fence() { asm volatile("wgmma.fence.sync.aligned;" ::: "memory"); }
__device__ __forceinline__ void wgmma_commit() { asm volatile("wgmma.commit_group.sync.aligned;" ::: "memory"); }
template <int N> __device__ __forceinline__ void wgmma_wait() { asm volatile("wgmma.wait_group.sync.aligned %0;" :: "n"(N) : "memory"); }
template <int R> __device__ __forceinline__ void reg_alloc() { asm volatile("setmaxnreg.inc.sync.aligned.u32 %0;" :: "n"(R)); }
template <int R> __device__ __forceinline__ void reg_dealloc() { asm volatile("setmaxnreg.dec.sync.aligned.u32 %0;" :: "n"(R)); }
__device__ __forceinline__ void bar_sync(int id, int n) { asm volatile("bar.sync %0, %1;" :: "r"(id), "r"(n) : "memory"); }
__device__ __forceinline__ void bar_arrive(int id, int n) { asm volatile("bar.arrive %0, %1;" :: "r"(id), "r"(n) : "memory"); }
__device__ __forceinline__ void sched_fence(int zero) {
  asm volatile("{\n.reg .pred p;\n.reg .b32 t;\nsetp.eq.s32 p, %0, 0;\n@p bra.uni LAB_S;\n"
               "LAB_F:\nmov.u32 t, %%clock;\nsetp.eq.u32 p, t, 0;\n@p bra LAB_F;\nLAB_S:\n}" :: "r"(zero) : "memory");
}
template <int N> __device__ __forceinline__ void fence_regs(float (&a)[N]) {
  #pragma unroll
  for (int i = 0; i < N; i++) asm volatile("" : "+f"(a[i]) :: "memory");
}
template <int N> __device__ __forceinline__ void undef_regs(float (&a)[N]) {
  #pragma unroll
  for (int i = 0; i < N; i++) asm volatile("" : "=f"(a[i]));
}

__device__ __forceinline__ uint64_t desc_from_lo(uint32_t lo) { return (uint64_t)lo | ((uint64_t)0x40000040u << 32); }
__device__ __forceinline__ uint32_t pack_bf16(float lo, float hi) {
  uint32_t r; asm("cvt.rn.bf16x2.f32 %0, %1, %2;" : "=r"(r) : "f"(hi), "f"(lo)); return r;
}
__device__ __forceinline__ uint32_t fma_bf2(uint32_t a, uint32_t b, uint32_t c) {
  uint32_t d; asm("fma.rn.bf16x2 %0, %1, %2, %3;" : "=r"(d) : "r"(a), "r"(b), "r"(c)); return d;
}
__device__ __forceinline__ float bf_lo(uint32_t v) { return __uint_as_float(v << 16); }
__device__ __forceinline__ float bf_hi(uint32_t v) { return __uint_as_float(v & 0xFFFF0000u); }
__device__ __forceinline__ float bf16_round(float x) { return bf_lo(pack_bf16(x, 0.f)); }
__device__ __forceinline__ void stmatrix_x4(uint32_t addr, uint32_t r0, uint32_t r1, uint32_t r2, uint32_t r3) {
  asm volatile("stmatrix.sync.aligned.m8n8.x4.shared.b16 [%0], {%1, %2, %3, %4};" :: "r"(addr), "r"(r0), "r"(r1), "r"(r2), "r"(r3) : "memory");
}
__device__ __forceinline__ void stmatrix_x4_t(uint32_t addr, uint32_t r0, uint32_t r1, uint32_t r2, uint32_t r3) {
  asm volatile("stmatrix.sync.aligned.m8n8.x4.trans.shared.b16 [%0], {%1, %2, %3, %4};" :: "r"(addr), "r"(r0), "r"(r1), "r"(r2), "r"(r3) : "memory");
}
__device__ __forceinline__ void stmatrix_x4_if(uint32_t addr, uint32_t r0, uint32_t r1, uint32_t r2, uint32_t r3, bool on) {
  asm volatile("{\n.reg .pred p;\nsetp.ne.b32 p, %5, 0;\n@p stmatrix.sync.aligned.m8n8.x4.shared.b16 [%0], {%1, %2, %3, %4};\n}"
               :: "r"(addr), "r"(r0), "r"(r1), "r"(r2), "r"(r3), "r"((int)on) : "memory");
}
__device__ __forceinline__ void ldmatrix_x4(uint32_t addr, uint32_t& r0, uint32_t& r1, uint32_t& r2, uint32_t& r3) {
  asm volatile("ldmatrix.sync.aligned.m8n8.x4.shared.b16 {%0, %1, %2, %3}, [%4];" : "=r"(r0), "=r"(r1), "=r"(r2), "=r"(r3) : "r"(addr) : "memory");
}
__device__ __forceinline__ void ldmatrix_x4_t(uint32_t addr, uint32_t (&r)[4]) {
  asm volatile("ldmatrix.sync.aligned.m8n8.x4.trans.shared.b16 {%0, %1, %2, %3}, [%4];" : "=r"(r[0]), "=r"(r[1]), "=r"(r[2]), "=r"(r[3]) : "r"(addr) : "memory");
}
__device__ __forceinline__ void st_rlx(void* p, uint32_t a, bool on) {
  asm volatile("{\n.reg .pred p;\nsetp.ne.b32 p, %2, 0;\n@p st.relaxed.gpu.global.u32 [%0], %1;\n}" :: "l"(p), "r"(a), "r"((int)on) : "memory");
}
__device__ __forceinline__ void st_rlx_v2(void* p, uint32_t a, uint32_t b, bool on) {
  asm volatile("{\n.reg .pred p;\nsetp.ne.b32 p, %3, 0;\n@p st.relaxed.gpu.global.v2.u32 [%0], {%1, %2};\n}" :: "l"(p), "r"(a), "r"(b), "r"((int)on) : "memory");
}
__device__ __forceinline__ uint2 ld_rlx_v2(const void* p) {
  uint2 v; asm volatile("ld.relaxed.gpu.global.v2.u32 {%0,%1}, [%2];" : "=r"(v.x), "=r"(v.y) : "l"(p) : "memory"); return v;
}
__device__ __forceinline__ void st_rlx_v4(void* p, uint32_t a, uint32_t b, uint32_t c, uint32_t d, bool on) {
  asm volatile("{\n.reg .pred p;\nsetp.ne.b32 p, %5, 0;\n@p st.relaxed.gpu.global.v4.u32 [%0], {%1, %2, %3, %4};\n}"
               :: "l"(p), "r"(a), "r"(b), "r"(c), "r"(d), "r"((int)on) : "memory");
}
__device__ __forceinline__ void st_nonzero_v4(void* p, uint32_t a, uint32_t b, uint32_t c, uint32_t d, bool on) {
  st_rlx_v4(p, max(a, 1u), max(b, 1u), max(c, 1u), max(d, 1u), on);
}
__device__ __forceinline__ uint32_t min4(const uint4& v) { return min(min(v.x, v.y), min(v.z, v.w)); }
__device__ __forceinline__ uint4 ld_rlx_v4(const void* p) {
  uint4 v; asm volatile("ld.relaxed.gpu.global.v4.u32 {%0,%1,%2,%3}, [%4];" : "=r"(v.x), "=r"(v.y), "=r"(v.z), "=r"(v.w) : "l"(p) : "memory"); return v;
}
__device__ __forceinline__ uint32_t movmatrix_t(uint32_t a) {
  uint32_t d; asm volatile("movmatrix.sync.aligned.m8n8.trans.b16 %0, %1;" : "=r"(d) : "r"(a)); return d;
}
__device__ __forceinline__ void mma16(float (&c)[4], uint32_t a0, uint32_t a1, uint32_t a2, uint32_t a3, uint32_t b0, uint32_t b1) {
  asm volatile("mma.sync.aligned.m16n8k16.row.col.f32.bf16.bf16.f32 {%0,%1,%2,%3}, {%4,%5,%6,%7}, {%8,%9}, {%0,%1,%2,%3};"
               : "+f"(c[0]), "+f"(c[1]), "+f"(c[2]), "+f"(c[3]) : "r"(a0), "r"(a1), "r"(a2), "r"(a3), "r"(b0), "r"(b1));
}
__device__ __forceinline__ void sts128(uint32_t addr, uint32_t a, uint32_t b, uint32_t c, uint32_t d) {
  asm volatile("st.shared.v4.b32 [%0], {%1,%2,%3,%4};" :: "r"(addr), "r"(a), "r"(b), "r"(c), "r"(d) : "memory");
}
__device__ __forceinline__ uint4 lds128(uint32_t addr) {
  uint4 v; asm volatile("ld.shared.v4.b32 {%0,%1,%2,%3}, [%4];" : "=r"(v.x), "=r"(v.y), "=r"(v.z), "=r"(v.w) : "r"(addr) : "memory"); return v;
}
__device__ __forceinline__ uint32_t lds32(uint32_t addr) {
  uint32_t v; asm volatile("ld.shared.b32 %0, [%1];" : "=r"(v) : "r"(addr) : "memory"); return v;
}
__device__ __forceinline__ float2 lds64f(uint32_t addr) {
  float2 v; asm volatile("ld.shared.v2.f32 {%0,%1}, [%2];" : "=f"(v.x), "=f"(v.y) : "r"(addr) : "memory"); return v;
}
__device__ __forceinline__ void sts64(uint32_t addr, uint32_t a, uint32_t b) {
  asm volatile("st.shared.v2.b32 [%0], {%1, %2};" :: "r"(addr), "r"(a), "r"(b) : "memory");
}
__device__ __forceinline__ float fast_ex2(float x) { float y; asm("ex2.approx.ftz.f32 %0, %1;" : "=f"(y) : "f"(x)); return y; }
__device__ __forceinline__ float fast_rcp(float x) { float y; asm("rcp.approx.ftz.f32 %0, %1;" : "=f"(y) : "f"(x)); return y; }
__device__ __forceinline__ float fast_rsqrt(float x) { float y; asm("rsqrt.approx.ftz.f32 %0, %1;" : "=f"(y) : "f"(x)); return y; }
__device__ __forceinline__ float silu_f(float g) { return g * fast_rcp(1.f + fast_ex2(g * -1.4426950408889634f)); }
__device__ __forceinline__ float swiglu(float h, float v) {
  float t; asm("tanh.approx.f32 %0, %1;" : "=f"(t) : "f"(h));
  const float p = h * v;
  return fmaf(p, t, p);
}

__device__ __forceinline__ void wgmma_m64n128k16_ss(float (&d)[64], uint64_t descA, uint64_t descB, int scaleD) {
  asm volatile("{\n.reg .pred p;\nsetp.ne.b32 p, %66, 0;\n"
    "wgmma.mma_async.sync.aligned.m64n128k16.f32.bf16.bf16 "
    "{%0, %1, %2, %3, %4, %5, %6, %7, %8, %9, %10, %11, %12, %13, %14, %15, "
    "%16, %17, %18, %19, %20, %21, %22, %23, %24, %25, %26, %27, %28, %29, %30, %31, "
    "%32, %33, %34, %35, %36, %37, %38, %39, %40, %41, %42, %43, %44, %45, %46, %47, "
    "%48, %49, %50, %51, %52, %53, %54, %55, %56, %57, %58, %59, %60, %61, %62, %63}, "
    "%64, %65, p, 1, 1, 0, 1;\n}\n"
    : "+f"(d[0]), "+f"(d[1]), "+f"(d[2]), "+f"(d[3]), "+f"(d[4]), "+f"(d[5]), "+f"(d[6]), "+f"(d[7]),
      "+f"(d[8]), "+f"(d[9]), "+f"(d[10]), "+f"(d[11]), "+f"(d[12]), "+f"(d[13]), "+f"(d[14]), "+f"(d[15]),
      "+f"(d[16]), "+f"(d[17]), "+f"(d[18]), "+f"(d[19]), "+f"(d[20]), "+f"(d[21]), "+f"(d[22]), "+f"(d[23]),
      "+f"(d[24]), "+f"(d[25]), "+f"(d[26]), "+f"(d[27]), "+f"(d[28]), "+f"(d[29]), "+f"(d[30]), "+f"(d[31]),
      "+f"(d[32]), "+f"(d[33]), "+f"(d[34]), "+f"(d[35]), "+f"(d[36]), "+f"(d[37]), "+f"(d[38]), "+f"(d[39]),
      "+f"(d[40]), "+f"(d[41]), "+f"(d[42]), "+f"(d[43]), "+f"(d[44]), "+f"(d[45]), "+f"(d[46]), "+f"(d[47]),
      "+f"(d[48]), "+f"(d[49]), "+f"(d[50]), "+f"(d[51]), "+f"(d[52]), "+f"(d[53]), "+f"(d[54]), "+f"(d[55]),
      "+f"(d[56]), "+f"(d[57]), "+f"(d[58]), "+f"(d[59]), "+f"(d[60]), "+f"(d[61]), "+f"(d[62]), "+f"(d[63])
    : "l"(descA), "l"(descB), "r"(scaleD));
}
__device__ __forceinline__ void wgmma_m64n256k16_rs(float (&d)[128], uint32_t a0, uint32_t a1, uint32_t a2, uint32_t a3, uint64_t descB, int scaleD) {
  asm volatile("{\n.reg .pred p;\nsetp.ne.b32 p, %133, 0;\n"
    "wgmma.mma_async.sync.aligned.m64n256k16.f32.bf16.bf16 "
    "{%0, %1, %2, %3, %4, %5, %6, %7, %8, %9, %10, %11, %12, %13, %14, %15, "
    "%16, %17, %18, %19, %20, %21, %22, %23, %24, %25, %26, %27, %28, %29, %30, %31, "
    "%32, %33, %34, %35, %36, %37, %38, %39, %40, %41, %42, %43, %44, %45, %46, %47, "
    "%48, %49, %50, %51, %52, %53, %54, %55, %56, %57, %58, %59, %60, %61, %62, %63, "
    "%64, %65, %66, %67, %68, %69, %70, %71, %72, %73, %74, %75, %76, %77, %78, %79, "
    "%80, %81, %82, %83, %84, %85, %86, %87, %88, %89, %90, %91, %92, %93, %94, %95, "
    "%96, %97, %98, %99, %100, %101, %102, %103, %104, %105, %106, %107, %108, %109, %110, %111, "
    "%112, %113, %114, %115, %116, %117, %118, %119, %120, %121, %122, %123, %124, %125, %126, %127}, "
    "{%128, %129, %130, %131}, %132, p, 1, 1, 1;\n}\n"
    : "+f"(d[0]), "+f"(d[1]), "+f"(d[2]), "+f"(d[3]), "+f"(d[4]), "+f"(d[5]), "+f"(d[6]), "+f"(d[7]),
      "+f"(d[8]), "+f"(d[9]), "+f"(d[10]), "+f"(d[11]), "+f"(d[12]), "+f"(d[13]), "+f"(d[14]), "+f"(d[15]),
      "+f"(d[16]), "+f"(d[17]), "+f"(d[18]), "+f"(d[19]), "+f"(d[20]), "+f"(d[21]), "+f"(d[22]), "+f"(d[23]),
      "+f"(d[24]), "+f"(d[25]), "+f"(d[26]), "+f"(d[27]), "+f"(d[28]), "+f"(d[29]), "+f"(d[30]), "+f"(d[31]),
      "+f"(d[32]), "+f"(d[33]), "+f"(d[34]), "+f"(d[35]), "+f"(d[36]), "+f"(d[37]), "+f"(d[38]), "+f"(d[39]),
      "+f"(d[40]), "+f"(d[41]), "+f"(d[42]), "+f"(d[43]), "+f"(d[44]), "+f"(d[45]), "+f"(d[46]), "+f"(d[47]),
      "+f"(d[48]), "+f"(d[49]), "+f"(d[50]), "+f"(d[51]), "+f"(d[52]), "+f"(d[53]), "+f"(d[54]), "+f"(d[55]),
      "+f"(d[56]), "+f"(d[57]), "+f"(d[58]), "+f"(d[59]), "+f"(d[60]), "+f"(d[61]), "+f"(d[62]), "+f"(d[63]),
      "+f"(d[64]), "+f"(d[65]), "+f"(d[66]), "+f"(d[67]), "+f"(d[68]), "+f"(d[69]), "+f"(d[70]), "+f"(d[71]),
      "+f"(d[72]), "+f"(d[73]), "+f"(d[74]), "+f"(d[75]), "+f"(d[76]), "+f"(d[77]), "+f"(d[78]), "+f"(d[79]),
      "+f"(d[80]), "+f"(d[81]), "+f"(d[82]), "+f"(d[83]), "+f"(d[84]), "+f"(d[85]), "+f"(d[86]), "+f"(d[87]),
      "+f"(d[88]), "+f"(d[89]), "+f"(d[90]), "+f"(d[91]), "+f"(d[92]), "+f"(d[93]), "+f"(d[94]), "+f"(d[95]),
      "+f"(d[96]), "+f"(d[97]), "+f"(d[98]), "+f"(d[99]), "+f"(d[100]), "+f"(d[101]), "+f"(d[102]), "+f"(d[103]),
      "+f"(d[104]), "+f"(d[105]), "+f"(d[106]), "+f"(d[107]), "+f"(d[108]), "+f"(d[109]), "+f"(d[110]), "+f"(d[111]),
      "+f"(d[112]), "+f"(d[113]), "+f"(d[114]), "+f"(d[115]), "+f"(d[116]), "+f"(d[117]), "+f"(d[118]), "+f"(d[119]),
      "+f"(d[120]), "+f"(d[121]), "+f"(d[122]), "+f"(d[123]), "+f"(d[124]), "+f"(d[125]), "+f"(d[126]), "+f"(d[127])
    : "r"(a0), "r"(a1), "r"(a2), "r"(a3), "l"(descB), "r"(scaleD));
}

constexpr uint32_t MSLOT = 32768, QSLOT = 49152;
constexpr int NM = 6;
constexpr uint32_t SM_X0 = 3 * QSLOT;
constexpr uint32_t SM_XR = SM_X0 + 16384;
constexpr uint32_t SM_STG = 196608;
constexpr uint32_t SM_XCH = SM_STG + 16384;
constexpr uint32_t SM_BAR = SM_STG + 32768;
constexpr uint32_t SM_VEC = SM_BAR + 512;
constexpr uint32_t SM_MODT = SM_VEC;
constexpr uint32_t SM_TOTAL = SM_VEC + 2048;
constexpr uint32_t B_X = SM_BAR  , B_EQ = B_X + 64, B_EM = B_EQ + 32, B_STREQ = B_EM + 48, B_STH = B_STREQ + 8, B_LN = B_STH + 8,
                   B_FQ = B_LN + 8, B_FM = B_FQ + 32, B_MOD = B_FM + 48  , B_GATE = B_MOD + 64, B_STFREE = B_GATE + 8, B_VEC = B_STFREE + 8  ,
                   B_FLG = B_VEC + 16  , B_H2A = B_FLG + 24, B_END = B_FLG + 96;
constexpr int NB_WG = 1  , NB_CONS = 3, NB_ORD = 4  ;
#define TUNE(name, value) constexpr int name = value
TUNE(PF_BYTES, 256);
TUNE(X_GAP, 250);
TUNE(AUX_HOLD, 3200);
TUNE(AUX_URG, 4);
TUNE(AUX_SLOW, 84);
TUNE(AUX_GAP, 500);
TUNE(MSEP, 6);
TUNE(WPRE, 2);
TUNE(GPRE, 5);
TUNE(DTAIL, 4);

struct Maps {
  CUtensorMap x, out;
  CUtensorMap o, h2, hh;
  CUtensorMap wqk, wvv, wq1, wo, w1, w3, w2;
  CUtensorMap wmod;
};

struct Ring { int st; uint32_t ph; int prev; uint32_t dl;
};
__device__ __forceinline__ void ring_next(Ring& r) { if (++r.st == NM) { r.st = 0; r.ph ^= 1; } }

__device__ __forceinline__ void retire_prev(uint32_t rel, bool on) {
  wgmma_commit();
  wgmma_wait<1>();
  if (on) mbar_arrive_e(rel);
}
struct Nop { __device__ __forceinline__ void operator()() const {} };
template <bool REL = true, class F = Nop>
__device__ __forceinline__ void mma_step(float (&acc)[64], uint32_t a, uint32_t b, bool first, uint32_t rel, F urgent = F()) {
  const uint32_t alo = (a >> 4) + (1u << 16), blo = (b >> 4) + (512u << 16);
  wgmma_fence();
  #pragma unroll
  for (int k = 0; k < 4; k++) {
    wgmma_m64n128k16_ss(acc, desc_from_lo(alo + k * 2), desc_from_lo(blo + k * 128), k > 0 || !first);
    if (k == 0) { retire_prev(rel, REL); urgent(); }
  }
  wgmma_commit();
}
__device__ __forceinline__ uint32_t m_wait(uint32_t sbase, const Ring& r) {
  mbar_wait(sbase + B_FM + 8 * r.st, r.ph, r.dl);
  return sbase + r.st * MSLOT;
}
__device__ __forceinline__ uint32_t m_prev(uint32_t sbase, const Ring& r) { return sbase + B_EM + 8 * r.prev; }
__device__ __forceinline__ void m_next(Ring& r) {
  r.prev = r.st; ring_next(r);
}
__device__ __forceinline__ void m_step(float (&acc)[64], uint32_t sbase, uint32_t wgoff, Ring& r, bool first = false) {
  const uint32_t slot = m_wait(sbase, r);
  mma_step(acc, slot + wgoff, slot + 16384, first, m_prev(sbase, r));
  m_next(r);
}

struct LnRow { uint32_t rs[2], nb[2]; };
__device__ __forceinline__ void ln_row(LnRow& l, int h, float mean, float rstd) {
  l.rs[h] = pack_bf16(rstd, rstd);
  const float nb = -mean * bf_lo(l.rs[h]);
  l.nb[h] = pack_bf16(nb, nb);
}
__device__ __forceinline__ uint32_t ln_mod(uint32_t x, const LnRow& l, int h, uint32_t c1, uint32_t s) {
  return fma_bf2(fma_bf2(x, l.rs[h], l.nb[h]), c1, s);
}

__device__ __forceinline__ uint32_t q_wait(int u, uint32_t sbase, uint32_t dl) {
  mbar_wait(sbase + B_FQ + 8 * (u & 3), (u >> 2) & 1, dl);
  return sbase + (u & 3) * QSLOT;
}
__device__ __forceinline__ uint32_t q_empty(int u, uint32_t sbase) { return sbase + B_EQ + 8 * (u & 3); }
struct Frag4 { uint32_t o[4]; };
__device__ __forceinline__ void q_load(uint32_t (&A)[16], uint4 (&p)[4], int kk, uint32_t tile, const Frag4& f, uint32_t t) {
  ldmatrix_x4(tile + f.o[kk], A[4 * kk], A[4 * kk + 1], A[4 * kk + 2], A[4 * kk + 3]);
  p[kk] = lds128(t + kk * 64);
}
__device__ __forceinline__ void q_norm(uint32_t (&A)[16], const uint4 (&p)[4], int kk, const LnRow& l) {
  A[4 * kk + 0] = ln_mod(A[4 * kk + 0], l, 0, p[kk].x, p[kk].z); A[4 * kk + 1] = ln_mod(A[4 * kk + 1], l, 1, p[kk].x, p[kk].z);
  A[4 * kk + 2] = ln_mod(A[4 * kk + 2], l, 0, p[kk].y, p[kk].w); A[4 * kk + 3] = ln_mod(A[4 * kk + 3], l, 1, p[kk].y, p[kk].w);
}
template <bool NEXT>
__device__ __forceinline__ void q_step_rs(float (&acc)[128], uint32_t (&A)[16], uint32_t (&N)[16], uint4 (&p)[4], int u, uint32_t sbase,
                                          const Frag4& f, uint32_t tab, const LnRow& l, uint32_t rot, bool keep, bool first, uint32_t dl, int wg, int zero) {
  const uint32_t slot = first ? sbase : q_wait(u, sbase, dl);
  const uint32_t blo = ((slot + 16384) >> 4) + (512u << 16) + rot * 128 + (zero << (u >> 2)), t = tab + ((u + 1) & 7) * 256;
  #pragma unroll
  for (int kk = 0; kk < 4; kk++) q_norm(A, p, kk, l);
  #pragma unroll
  for (int i = 0; i < 16; i++) asm volatile("" : "+r"(A[i]));
  if (!first) sched_fence(zero);
  if (first) {
    mbar_wait(sbase + B_GATE, 0, dl);
    PROF(6, threadIdx.x == 0);
  }
  if (!(first && wg == 0)) bar_sync(NB_ORD + wg, 256);
  wgmma_fence();
  #pragma unroll
  for (int kk = 0; kk < 4; kk++) {
    wgmma_m64n256k16_rs(acc, A[4 * kk], A[4 * kk + 1], A[4 * kk + 2], A[4 * kk + 3], desc_from_lo(blo ^ (kk * 128)), kk > 0 || !first);
    if (kk == 0) retire_prev(q_empty(u - 1, sbase), !first);
    if (NEXT && kk == 1) {
      if ((u & 1) && u < MSEP) mbar_wait(sbase + B_MOD + 4 * (u + 1), 0, dl);
      #pragma unroll
      for (int q = 0; q < 4; q++) q_load(N, p, q, slot, f, t);
    }
    if (kk == 3 && (NEXT || wg == 0)) bar_arrive(NB_ORD + (wg ^ 1), 256);
    if (kk == 1) stmatrix_x4_if(sbase + SM_STG + (u >> 3) * 16384 + (f.o[0] ^ (((u >> 1 & 3) ^ rot) << 5)), A[0], A[1], A[2], A[3], keep);
  }
  wgmma_commit();
}

typedef uint32_t Frag8[8];
template <int N> __device__ __forceinline__ void pack_half(Frag8& f, const float (&acc)[N], int off, int half) {
  #pragma unroll
  for (int e = 0; e < 8; e++) { f[e] = pack_bf16(acc[off + 4 * e + 2 * half], acc[off + 4 * e + 2 * half + 1]); asm volatile("" : "+r"(f[e])); }
}
__device__ __forceinline__ void transpose8(Frag8& f) {
  #pragma unroll
  for (int e = 0; e < 8; e++) f[e] = movmatrix_t(f[e]);
}
__device__ __forceinline__ void attn_send(const Frag8& f, int kv, uint32_t xch, int warp, uint4* halo_out, bool has_next) {
  if (warp == 3) {
    st_nonzero_v4(halo_out + kv * 64, f[0], f[1], f[2], f[3], has_next); st_nonzero_v4(halo_out + kv * 64 + 32, f[4], f[5], f[6], f[7], has_next);
  } else {
    sts128(xch + 2048 + kv * 1024, f[0], f[1], f[2], f[3]); sts128(xch + 2048 + kv * 1024 + 512, f[4], f[5], f[6], f[7]);
  }
}
template <int N>
__device__ __forceinline__ void attn_recv(uint4* p, int first, uint32_t xch, int wg, int warp, const uint4* halo_in, bool has_prev) {
  bar_sync(NB_WG + wg, 128);
  #pragma unroll
  for (int e = 0; e < N; e++)
    asm volatile("{\n.reg .pred p, q;\nsetp.ne.b32 p, %6, 0;\nsetp.ne.b32 q, %7, 0;\n"
                 "mov.b32 %0, 0;\nmov.b32 %1, 0;\nmov.b32 %2, 0;\nmov.b32 %3, 0;\n"
                 "@p ld.shared.v4.b32 {%0,%1,%2,%3}, [%4];\n@q ld.relaxed.gpu.global.v4.u32 {%0,%1,%2,%3}, [%5];\n}"
                 : "=&r"(p[e].x), "=&r"(p[e].y), "=&r"(p[e].z), "=&r"(p[e].w)
                 : "r"(xch + (first + e) * 512), "l"(halo_in + (first + e) * 32), "r"((int)(warp > 0)), "r"((int)(warp == 0 && has_prev)) : "memory");
}
template <int N>
__device__ __forceinline__ void attn_check(uint4* p, int first, bool remote, const uint4* halo_in, uint32_t dl) {
  if (remote) {
    while (true) {
      uint32_t m = ~0u;
      #pragma unroll
      for (int e = 0; e < N; e++) m = min(m, min4(p[e]));
      if (poll_done(m != 0, dl)) break;
      #pragma unroll
      for (int e = 0; e < N; e++) p[e] = ld_rlx_v4(halo_in + (first + e) * 32);
    }
  }
}
__device__ __forceinline__ void attn_core(const Frag8& qA, const Frag8& qB, const Frag8& kA, const Frag8& kB, const Frag8& vA, const Frag8& vB,
                                          const uint4* kP, const uint4* vP, bool noprev, int lane, float (&o)[2][5][4]) {
  const int g = lane >> 2, qd = lane & 3;
  const bool s0 = 2 * qd > g, s1 = 2 * qd + 1 > g;
  const uint32_t msk = (s0 ? 0xFFFFu : 0u) | (s1 ? 0xFFFF0000u : 0u);
  constexpr float SC = 0.17677669529663687f * 1.4426950408889634f;
  float s[2][3][4];
  #pragma unroll
  for (int h = 0; h < 2; h++) {
    #pragma unroll
    for (int nb = 0; nb < 3; nb++) s[h][nb][0] = s[h][nb][1] = s[h][nb][2] = s[h][nb][3] = 0.f;
    #pragma unroll
    for (int kk = 0; kk < 2; kk++) {
      const int e = 4 * h + 2 * kk;
      mma16(s[h][1], qA[e], qB[e], qA[e + 1], qB[e + 1], kA[e], kA[e + 1]);
      mma16(s[h][2], qA[e], qB[e], qA[e + 1], qB[e + 1], kB[e], kB[e + 1]);
      mma16(s[h][0], qA[e], qB[e], qA[e + 1], qB[e + 1], kk ? kP[h].z : kP[h].x, kk ? kP[h].w : kP[h].y);
    }
  }
  #pragma unroll
  for (int h = 0; h < 2; h++) {
    float l[4], m[2];
    l[0] = s0 ? (noprev ? -INFINITY : s[h][0][0]) : s[h][1][0];
    l[1] = s1 ? (noprev ? -INFINITY : s[h][0][1]) : s[h][1][1];
    l[2] = s0 ? s[h][1][2] : s[h][2][2];
    l[3] = s1 ? s[h][1][3] : s[h][2][3];
    m[0] = fmaxf(l[0], l[1]); m[1] = fmaxf(l[2], l[3]);
    #pragma unroll
    for (int x = 1; x <= 2; x <<= 1)
      #pragma unroll
      for (int e = 0; e < 2; e++) m[e] = fmaxf(m[e], __shfl_xor_sync(0xffffffffu, m[e], x));
    #pragma unroll
    for (int e = 0; e < 4; e++) l[e] = fast_ex2((l[e] - m[e >> 1]) * SC);
    const uint32_t plo = pack_bf16(l[0], l[1]), phi = pack_bf16(l[2], l[3]);
    const uint32_t vp[4] = {vP[h].x, vP[h].y, vP[h].z, vP[h].w};
    #pragma unroll
    for (int d = 0; d < 5; d++) o[h][d][0] = o[h][d][1] = o[h][d][2] = o[h][d][3] = 0.f;
    mma16(o[h][4], 0x3F803F80u, 0u, 0u, 0x3F803F80u, plo, phi);
    #pragma unroll
    for (int m2 = 0; m2 < 2; m2++) {
      const int e = 4 * h + 2 * m2;
      mma16(o[h][2 * m2], vp[2 * m2], vp[2 * m2 + 1], vA[e], vA[e + 1], plo & msk, plo & ~msk);
      mma16(o[h][2 * m2 + 1], vA[e], vA[e + 1], vB[e], vB[e + 1], phi & msk, phi & ~msk);
    }
  }
}
__device__ __forceinline__ void attn_store(const float (&o)[2][5][4], int h, uint32_t sbase, const Frag4& f) {
  float r[4];
  #pragma unroll
  for (int e = 0; e < 4; e++) r[e] = fast_rcp(o[h][4][e]);
  #pragma unroll
  for (int m = 0; m < 2; m++) {
    const float (&lo)[4] = o[h][2 * m], (&hi)[4] = o[h][2 * m + 1];
    stmatrix_x4_t(sbase + SM_STG + f.o[2 * h + m], pack_bf16(lo[0] * r[0], lo[1] * r[1]), pack_bf16(hi[0] * r[2], hi[1] * r[3]),
                  pack_bf16(lo[2] * r[0], lo[3] * r[1]), pack_bf16(hi[2] * r[2], hi[3] * r[3]));
  }
}

__device__ __forceinline__ void request_store(uint32_t bar) {
  fence_proxy_async_smem();
  mbar_arrive_e(bar);
}

__device__ __forceinline__ void g_switch(float (&cur)[64], float (&prv)[64], int nrest, bool first, int n, uint32_t sbase, uint32_t wgoff,
                                         const Frag4& f, Ring& r) {
  #pragma unroll 1
  for (int i = 1; i < nrest; i++) m_step(prv, sbase, wgoff, r);
  m_step(prv, sbase, wgoff, r);
  m_step(cur, sbase, wgoff, r, first);
  mbar_wait(sbase + B_STFREE, (n - 1) & 1, r.dl);
  fence_regs(prv);
  PROF(28 + n, threadIdx.x == 0);
  #pragma unroll
  for (int jj = 0; jj < 4; jj++) {
    uint32_t p[4];
    #pragma unroll
    for (int e = 0; e < 4; e++) {
      const int i = jj * 8 + e * 2;
      p[e] = pack_bf16(swiglu(prv[i], prv[i + 32]), swiglu(prv[i + 1], prv[i + 33]));
    }
    stmatrix_x4(sbase + SM_STG + f.o[jj], p[0], p[1], p[2], p[3]);
    m_step(cur, sbase, wgoff, r);
  }
  request_store(sbase + B_STREQ);
}

__device__ __forceinline__ uint32_t bad2(uint32_t a, uint32_t b, unsigned par) {
  uint32_t d; asm("lop3.b32 %0, %1, %2, %3, 0x7E;" : "=r"(d) : "r"(a), "r"(b), "r"(par)); return d;
}
__device__ __forceinline__ uint32_t bad4(const uint4& v, unsigned par) { return bad2(v.x, v.y, par) | bad2(v.z, v.w, par); }
__device__ __forceinline__ uint32_t hi_halves(uint32_t lo, uint32_t hi) { return __byte_perm(lo, hi, 0x7632); }

__device__ __forceinline__ void gather_table(const float* src, uint32_t dst, uint32_t bar, unsigned par, uint32_t dl) {
  asm volatile("{\n.reg .pred p, e;\n.reg .b32 s<4>, c<4>, t<4>, w<4>;\n"
               "elect.sync _|e, 0xffffffff;\n"
               "LAB_POLL:\n"
               "ld.relaxed.gpu.global.v4.u32 {s0, s1, s2, s3}, [%0];\n"
               "ld.relaxed.gpu.global.v4.u32 {c0, c1, c2, c3}, [%0 + 4096];\n"
               "prmt.b32 w0, c0, c1, 0x7632;\nprmt.b32 w1, c2, c3, 0x7632;\nprmt.b32 w2, s0, s1, 0x7632;\nprmt.b32 w3, s2, s3, 0x7632;\n"
               "st.shared.v4.b32 [%1], {w0, w1, w2, w3};\n"
               "lop3.b32 t0, s0, s1, %3, 0x7E;\nlop3.b32 t1, s2, s3, %3, 0x7E;\nlop3.b32 t2, c0, c1, %3, 0x7E;\nlop3.b32 t3, c2, c3, %3, 0x7E;\n"
               "lop3.b32 t0, t0, t1, 1, 0xA8;\nlop3.b32 t2, t2, t3, 1, 0xA8;\n"
               "or.b32 t0, t0, t2;\n"
               "setp.eq.u32 p, t0, 0;\n"
               "vote.sync.all.pred p, p, 0xffffffff;\n"
               "@p bra.uni LAB_OK;\n"
               "mov.u32 t0, %%clock;\nsub.s32 t0, t0, %4;\nsetp.lt.s32 p, t0, 0;\n"
               "vote.sync.all.pred p, p, 0xffffffff;\n"
               "@p bra.uni LAB_POLL;\n"
               "LAB_OK:\n"
               "@e mbarrier.arrive.shared::cta.b64 _, [%2];\n}"
               :: "l"(src), "r"(dst), "r"(bar), "r"(par), "r"(dl) : "memory");
}

__device__ __forceinline__ int other_slot(int i, int j) { return i < 4 ? (~j & 4) + i : (j & 4) + i - 4 + (i - 4 >= (j & 3)); }

__device__ __forceinline__ int aux_col(int a, int u) { return u < 8 ? (a & 1) * 1024 + (2 * u + (a >> 1)) * 64 : 2048 + ((u - 8) * 4 + a) * 64; }
constexpr int NA = 7;
constexpr uint32_t A_FULL = SM_BAR, A_EMPTY = SM_BAR + 64, A_SUM = SM_BAR + 128, A_FREE = SM_BAR + 136, SM_RED = SM_VEC;
__device__ __forceinline__ void aux_role(const Maps& maps, const bf16* __restrict__ cvec, Mail* mail0, int zero, int a, uint32_t sbase, int wid) {
  const int tid = threadIdx.x, lane = tid & 31;
  const uint32_t dl = clock32() + 800000000u;
  int st = 0; uint32_t ph = 0;
  if (wid == 8) {
    prefetch_tmap(&maps.wmod);
    #pragma unroll
    for (int i = 0; i < 18; i++) mbar_init_e(sbase + A_FULL + 8 * i, i < 8 ? 1 : i < 17 ? 8 : 2);
    fence_proxy_async_smem();
    bar_arrive(0, 352);
    PROF(39, lane == 0);
    #pragma unroll
    for (int i = 0; i < NA; i++) {
      mbar_expect_tx_e(sbase + A_FULL + 8 * i, 32768);
      tma_load_2d(sbase + i * MSLOT, &maps.wmod, sbase + A_FULL + 8 * i, aux_col(a, i >> 2), (i & 3) * 256);
    }
    PROF(40, lane == 0);
    #pragma unroll 1
    for (int i = NA; i < 96; i++) {
      if (i >= AUX_SLOW) wait_until(clock32() + AUX_GAP);
      if (i == 8) wait_until(dl - 800000000u + AUX_HOLD);
      mbar_wait(sbase + A_EMPTY + 8 * st, ph, dl);
      mbar_expect_tx_e(sbase + A_FULL + 8 * st, 32768);
      tma_load_2d<true>(sbase + st * MSLOT, &maps.wmod, sbase + A_FULL + 8 * st, aux_col(a, i >> 2), (i & 3) * 256);
      if (++st == NA) { st = 0; ph ^= 1; }
    }
  } else if (wid < 8) {
    const int g = lane >> 2, qd = lane & 3;
    uint32_t sc[16];
    const uint2 c = *reinterpret_cast<const uint2*>(cvec + tid * 4);
    sts64(sbase + SM_RED + tid * 8, pack_bf16(silu_f(bf_lo(c.x)), silu_f(bf_hi(c.x))), pack_bf16(silu_f(bf_lo(c.y)), silu_f(bf_hi(c.y))));
    bar_sync(0, 352);
    #pragma unroll
    for (int i = 0; i < 16; i++) sc[i] = lds32(sbase + SM_RED + ((i >> 2) * 256 + wid * 32 + (i & 3) * 8 + qd * 2) * 2);
    bar_sync(NB_CONS, 256);
    PROF(38, tid == 0);
    const uint32_t aoff = (wid * 32 + (lane & 7) + (lane >> 4) * 8) * 128 + ((((lane >> 3) & 1) ^ (lane & 7)) << 4);
    uint32_t w[2][8][4];
    auto fetch = [&](uint32_t (&f)[8][4]) {
      mbar_wait(sbase + A_FULL + 8 * st, ph, dl);
      #pragma unroll
      for (int e = 0; e < 8; e++) ldmatrix_x4_t((sbase + st * MSLOT + aoff + (e >> 2) * 2048) ^ ((e & 3) << 5), f[e]);
      if (++st == NA) { st = 0; ph ^= 1; }
    };
    #pragma unroll 1
    for (int u = 0; u < 24; u++) {
      float acc[4][4];
      #pragma unroll
      for (int m = 0; m < 4; m++) acc[m][0] = acc[m][1] = acc[m][2] = acc[m][3] = 0.f;
      fetch(w[0]);
      #pragma unroll
      for (int q = 0; q < 4; q++) {
        PROF(30 + (u & 1) * 4 + q, u < 2 && tid == 0);
        const uint32_t rel = sbase + A_EMPTY + 8 * (st == 0 ? NA - 1 : st - 1);
        if (q < 3) fetch(w[(q + 1) & 1]);
        uint32_t dep = 0;
        #pragma unroll
        for (int e = 0; e < 8; e++) dep |= w[q & 1][e][0];
        mbar_arrive_e(rel + (dep & zero));
        if (q == 1) mbar_wait(sbase + A_FREE, (u & 1) ^ 1, dl);
        #pragma unroll
        for (int e = 0; e < 8; e++) {
          const uint32_t (&f)[4] = w[q & 1][e];
          mma16(acc[e & 3], f[0], f[1], f[2], f[3], sc[4 * q + 2 * (e >> 2)], sc[4 * q + 2 * (e >> 2) + 1]);
        }
      }
      const float v0 = qd & 2 ? (qd & 1 ? acc[3][0] : acc[2][0]) : (qd & 1 ? acc[1][0] : acc[0][0]);
      const float v1 = qd & 2 ? (qd & 1 ? acc[3][2] : acc[2][2]) : (qd & 1 ? acc[1][2] : acc[0][2]);
      sts64(sbase + SM_RED + wid * 256 + (qd * 8 + g) * 8, __float_as_uint(v0), __float_as_uint(v1));
      mbar_arrive_e(sbase + A_SUM);
      if (u < AUX_URG) mbar_wait(sbase + A_FREE, u & 1, dl);
    }
  } else if (wid < 11) {
    float* const mail = &mail0->mod[(wid - 9) * 4 * 6 * D_ + 2 * lane];
    unsigned par = ld_relaxed(&mail0->flags[FL_EPOCH + (lane >> 5)]);
    bar_sync(0, 352);
    par = (par + 1) & 1;
    #pragma unroll 1
    for (int u = -2; u < 24; u++) {
      if (u >= 0) {
        const int col = aux_col(a, u);
        const float add = (col >> 10) == 1 || (col >> 10) == 4 ? 1.f : 0.f;
        const float mul = col < 3 * D_ ? 1.f : col < 5 * D_ ? 0.5f : 2.f;
        mbar_wait(sbase + A_SUM, u & 1, dl);
        float2 v[8];
        #pragma unroll
        for (int w = 0; w < 8; w++) v[w] = lds64f(sbase + SM_RED + w * 256 + lane * 8);
        const float t0 = ((v[0].x + v[1].x) + (v[2].x + v[3].x)) + ((v[4].x + v[5].x) + (v[6].x + v[7].x));
        const float t1 = ((v[0].y + v[1].y) + (v[2].y + v[3].y)) + ((v[4].y + v[5].y) + (v[6].y + v[7].y));
        mbar_arrive_e(sbase + A_FREE + (__float_as_uint(t0 + t1) & zero));
        const uint32_t w = pack_bf16((add + bf16_round(t0)) * mul, (add + bf16_round(t1)) * mul), o = __shfl_xor_sync(0xffffffffu, w, 1);
        const uint32_t m0 = (lane & 1) ? (o & 0xFFFF0000u) : (w << 16), m1 = (lane & 1) ? (w & 0xFFFF0000u) : (o << 16);
        #pragma unroll
        for (int c = 0; c < 4; c++) st_rlx_v2(mail + c * 6 * D_ + col, m0 | par, m1 | par, true);
        PROF(1 + u, tid == 288);
      }
      #pragma unroll 1
      for (int v = 2 * (u + 2); v < 2 * (u + 3) && v < 24; v++)
        #pragma unroll
        for (int c = 0; c < 4; c++) st_rlx_v2(mail + c * 6 * D_ + aux_col(a, v), par ^ 1, par ^ 1, true);
    }
    const int t = a * 64 + tid - 288;
    #pragma unroll 4
    for (int i = t; i < 16 * 16 * 256; i += 256) mail0->halo[par ^ 1][i] = make_uint4(0, 0, 0, 0);
    #pragma unroll 4
    for (int i = t; i < 16 * 8 * 64; i += 256) mail0->st2[par ^ 1][i] = make_uint4(0, 0, 0, 0);
  }
}

template <int MODE>
__global__ void __launch_bounds__(384, 1)
fused_block_kernel(const bf16* __restrict__ x, const bf16* __restrict__ cvec, const bf16* __restrict__ wmod, Mail* mail0, int zero,
                   const __grid_constant__ Maps maps) {
  extern __shared__ __align__(1024) uint8_t smem_raw[];
  const uint32_t sbase = smem_u32(smem_raw);
  const int tid = threadIdx.x, lane = tid & 31;
  PROFN(0, tid == 0);
  const int wid = __shfl_sync(0xffffffffu, tid >> 5, 0);
  const int b = cta_role<MODE>();
  if (b >= NCTA) { aux_role(maps, cvec, mail0, zero, b - NCTA, sbase, wid); return; }
  const int jg = b >> 6, mb = jg ? 31 - (b >> 2) : (b >> 2), j = 4 * jg + (b & 3);
  const uint32_t dl = clock32() + 800000000u;
  unsigned* const flags = &mail0->flags[mb * 32];
  const int row0 = mb * 128;

  if (wid >= 8) {
    if (wid == 8) {
      #pragma unroll
      for (int i = 0; i < 8; i++) mbar_init_e(sbase + B_X + 8 * i, 1);
      fence_proxy_async_smem();
      mbar_expect_tx_e(sbase + B_X, 4096);
      bulk_load(sbase + SM_XR, x + (size_t)(row0 + j * 16) * D_, 4096, sbase + B_X);
    } else if (wid == 11) {
      #pragma unroll
      for (int i = 0; i < 12; i++) prefetch_tmap(&maps.x + i);
    } else if (wid == 9) {
      #pragma unroll
      for (uint32_t bar = B_EQ; bar < B_FM; bar += 8) mbar_init_e(sbase + bar, bar < B_FQ ? 8 : bar == B_FQ + 8 || bar == B_FQ + 24 ? 2 : 1);
      fence_proxy_async_smem();
    } else {
      #pragma unroll
      for (uint32_t bar = B_FM; bar < B_END; bar += 8) mbar_init_e(sbase + bar, 1);
      fence_proxy_async_smem();
    }
    bar_sync(0, 384);
    reg_dealloc<40>();
    PROF(92, tid == 256);
    if (wid == 8) {
      uint32_t tnext = clock32();
      #pragma unroll 1
      for (int q = 1; q < 8; q++) {
        wait_until(tnext);
        mbar_expect_tx_e(sbase + B_X + 8 * q, 4096);
        bulk_load(sbase + SM_XR + q * 4096, x + (size_t)(row0 + j * 16 + 2 * q) * D_, 4096, sbase + B_X + 8 * q);
        tnext += X_GAP;
      }
      #pragma unroll 1
      for (int u = 0; u < 16; u++) {
        const int st = u & 3;
        if (u == 1) mbar_wait(sbase + B_X + 56, 0, dl);
        if (u == 2) { mbar_wait(sbase + B_GATE, 0, dl); PROFN(60, lane == 0); }
        if (u == 3) mbar_wait(sbase + B_EQ, 0, dl);
        mbar_wait(sbase + B_EQ + 8 * st, ((u >> 2) & 1) ^ 1, dl);
        const uint32_t slot = sbase + st * QSLOT, fb = sbase + B_FQ + 8 * st;
        mbar_expect_tx_e(fb, u == 0 ? 65536 : u == 15 ? 32768 : 49152);
        if ((u & 1) && (u < MSEP || u == 15)) mbar_arrive_e(fb);
        if (u == 0) tma_load_3d(sbase + SM_X0, &maps.x, fb, 0, mb * 64, 0);
        tma_load_4d<true>(slot + 16384, &maps.wqk, fb, 0, u * 64, j, 0);
        tma_load_4d<true>(slot + 32768, &maps.wvv, fb, 0, u * 64, j, 0);
        if (u < 15) tma_load_3d(slot, &maps.x, fb, u * 64 + 64, mb * 64, 0);
      }
      const unsigned e1 = 1 + ld_relaxed(flags + FO_EPOCH);
      Ring r{0, 1, 0, dl};
      uint32_t slot, fb;
      auto acquire = [&](uint32_t bytes) {
        mbar_wait(sbase + B_EM + 8 * r.st, r.ph, dl);
        slot = sbase + r.st * MSLOT; fb = sbase + B_FM + 8 * r.st;
        mbar_expect_tx_e(fb, bytes);
        ring_next(r);
      };
      #pragma unroll 1
      for (int kt = 0; kt < 16; kt++) {
        if (kt < 5) mbar_wait(sbase + B_EQ + 8 * (kt - (kt >= 2)), 1, dl);
        if ((kt & 7) == 0) { PROF(46, lane == 0 && kt == 8); mbar_wait(sbase + B_FLG + kt, 0, dl); PROF(47, lane == 0 && kt == 8); }
        acquire(32768);
        tma_load_4d<true>(slot + 16384, &maps.wq1, fb, (j + 8) * 64, (kt & 1) * 64 + (kt & 6) * 8, (kt >> 3) * 4, 0);
        tma_load_3d(slot, &maps.hh, fb, (kt & 7) * 64, row0, kt >> 3);
      }
      PROF(82, lane == 0);
      mbar_wait(sbase + B_FLG + 16, 0, dl);
      PROF(83, lane == 0);
      #pragma unroll 1
      for (int kt = 0; kt < 8; kt++) {
        if (kt == 4) {
          acquire(32768);
          tma_load_3d(slot, &maps.x, fb, j * 128, mb * 64, 0);
          tma_load_3d(slot + 16384, &maps.x, fb, j * 128 + 64, mb * 64, 0);
        }
        acquire(32768);
        tma_load_3d<true>(slot + 16384, &maps.wo, fb, 0, kt * 64, 2 * j);
        tma_load_2d(slot, &maps.o, fb, kt * 64, row0);
      }
      acquire(16384);
      tma_load_3d<true>(slot + 16384, &maps.wo, fb, 0, (8 + j) * 64, 2 * j);
      auto deferred = [&](const CUtensorMap* map, const unsigned* flag, Ring ra, int n, int col0, int step) {
        uint32_t dst = sbase + ra.st * MSLOT, bar = sbase + B_FM + 8 * ra.st, col = col0 + other_slot(0, j) * step;
        asm volatile("" : "+r"(dst), "+r"(bar), "+r"(col));
        wait_flag(flag, e1 * NCTA, dl);
        tma_load_2d(dst, map, bar, col, row0);
        #pragma unroll 1
        for (int i = 1; i < n; i++) { ring_next(ra); tma_load_2d(sbase + ra.st * MSLOT, map, sbase + B_FM + 8 * ra.st, col0 + other_slot(i, j) * step, row0); }
      };
      {
        const Ring ra = r;
        #pragma unroll 1
        for (int i = 0; i < 7; i++) {
          const int kt = 8 + other_slot(i, j);
          acquire(32768);
          tma_load_3d<true>(slot + 16384, &maps.wo, fb, 0, kt * 64, 2 * j);
          if (i == WPRE - 1) { deferred(&maps.o, &mail0->flags[FL_O], ra, WPRE, 512, 64); PROFN(61, lane == 0); }
          if (i >= WPRE) tma_load_2d(slot, &maps.o, fb, kt * 64, row0);
        }
      }
      #pragma unroll 1
      for (int t = 0; t < 2; t++) {
        acquire(32768);
        tma_load_2d<true>(slot, &maps.w1, fb, j * 64, (2 * j + t) * 64);
        tma_load_2d<true>(slot + 8192, &maps.w3, fb, j * 64, (2 * j + t) * 64);
        tma_load_2d<true>(slot + 16384, &maps.w1, fb, (8 + j) * 64, (2 * j + t) * 64);
        tma_load_2d<true>(slot + 24576, &maps.w3, fb, (8 + j) * 64, (2 * j + t) * 64);
      }
      {
        const Ring ra = r;
        #pragma unroll 1
        for (int i = 0; i < GPRE; i++) {
          const int kt = 2 * other_slot(i, j);
          acquire(32768);
          tma_load_2d<true>(slot + 16384, &maps.w1, fb, j * 64, kt * 64);
          tma_load_2d<true>(slot + 24576, &maps.w3, fb, j * 64, kt * 64);
        }
        deferred(&maps.h2, &mail0->flags[FL_H2], ra, GPRE, 0, 128);
        PROFN(62, lane == 0);
        mbar_arrive_e(sbase + B_H2A);
      }
      #pragma unroll 1
      for (int gt = 0; gt < 7; gt++) {
        const int ncol = (8 * gt + j) * 64;
        #pragma unroll 1
        for (int i = (gt == 0 ? GPRE : 0); i < (gt < 2 ? 14 : 16); i++) {
          const int kt = gt >= 2 ? i : i < 7 ? 2 * other_slot(i, j) : 2 * other_slot(i - 7, j) + 1;
          if (gt == 0 && i == 7) mbar_wait(sbase + B_FLG + 32, 0, dl);
          acquire(32768);
          tma_load_2d<true>(slot + 16384, &maps.w1, fb, ncol, kt * 64);
          tma_load_2d<true>(slot + 24576, &maps.w3, fb, ncol, kt * 64);
          tma_load_2d(slot, &maps.h2, fb, kt * 64, row0);
        }
      }
      #pragma unroll 1
      for (int kt = 0; kt < 56; kt++) {
        if ((kt & 7) == 0) mbar_wait(sbase + B_FLG + 40 + kt, 0, dl);
        acquire(32768);
        tma_load_3d(slot + 16384, &maps.w2, fb, 0, kt * 64, 2 * j);
        tma_load_3d(slot, &maps.hh, fb, (kt & 7) * 64, row0, kt >> 3);
      }
    } else {
      const unsigned e1 = 1 + ld_relaxed(wid == 9 ? flags + FO_EPOCH : &mail0->flags[FL_EPOCH]), par = e1 & 1;
      if (wid == 9) {
        #pragma unroll 1
        for (int n = 0; n < 12; n++) {
          if (n == 4) {
            mbar_wait(sbase + B_STH, 0, dl);
            tma_store_2d(&maps.h2, sbase + SM_STG, j * 128, row0);
            bulk_commit();
            bulk_wait0();
            red_add_e(&mail0->flags[FL_H2], 1);
            PROF(84, lane == 0);
            mbar_wait(sbase + B_H2A, 0, dl);
          }
          if (n >= 1 && n <= 4) mbar_wait(sbase + B_STREQ, n & 1, dl); else mbar_sleep(sbase + B_STREQ, n & 1, dl);
          if (n == 0) fence_proxy_async_smem();
          if (n == 2 || n == 3) tma_store_2d(&maps.o, sbase + SM_STG, (j + 8 * (n - 2)) * 64, row0);
          else if (n == 4) tma_store_2d(&maps.h2, sbase + SM_STG + 16384, j * 128 + 64, row0);
          else tma_store_3d(&maps.hh, sbase + SM_STG + (n == 1 ? 16384 : 0), j * 64, row0, n < 2 ? n : n - 5);
          bulk_commit();
          bulk_wait0();
          red_add_e(n == 3 ? &mail0->flags[FL_O] : flags + FO_CNT + n, 1);
          mbar_arrive_e(sbase + B_STFREE);
          PROFN(70 + n, lane == 0 && n > 0); PROF(85, lane == 0 && n == 0);
          if (n != 3) { wait_flag(flags + FO_CNT + n, e1 * 8, dl); mbar_arrive_e(sbase + B_FLG + 8 * n); }
        }
      } else {
        mbar_wait(sbase + B_X + 24, 0, dl);
        const float* const mail = &mail0->mod[(b & 7) * 6 * D_ + lane * 4];
        if (wid == 10) {
          #pragma unroll 1
          for (int p = 0; p < 8; p++) {
            if (p >= 2) mbar_wait(p == 2 ? q_empty(0, sbase) : q_empty(2 * p - 5, sbase), p == 2 ? 0 : ((2 * p - 5) >> 2) & 1, dl);
            gather_table(mail + p * 128, sbase + SM_MODT + (p & 3) * 512 + ((lane * 16) ^ ((j >> 1) << 6)), 2 * p - 1 < MSEP ? sbase + B_MOD + 8 * p : sbase + B_FQ + 8 * ((2 * p - 1) & 3), par, dl);
            PROF(63 + p, lane == 0 && p < 7);
          }
          const uint32_t vdst = sbase + SM_VEC + (lane >> 3) * 64 + (lane & 3) * 16 + ((lane >> 2) & 1) * 8;
          #pragma unroll 1
          for (int v = 0; v < 2; v++) {
            mbar_sleep(sbase + B_FLG + 16 + 24 * v, 0, dl);
            uint4 m[3];
            while (true) {
              #pragma unroll
              for (int e = 0; e < 3; e++) m[e] = ld_rlx_v4(mail + (2 + v + e) * 1024 + j * 128);
              if (poll_done(((bad4(m[0], par) | bad4(m[1], par) | bad4(m[2], par)) & 1) == 0, dl)) break;
              __nanosleep(200);
            }
            #pragma unroll
            for (int e = 0; e < 3; e++) sts64(vdst + (v + e) * 256, hi_halves(m[e].x, m[e].y), hi_halves(m[e].z, m[e].w));
            mbar_arrive_e(sbase + B_VEC + 8 * v);
            PROF(70, lane == 0 && v == 0);
          }
        } else {
          mbar_wait(sbase + B_LN, 0, dl);
          red_add_e(&mail0->flags[FL_LN1], 1);
          wait_flag(&mail0->flags[FL_LN1], e1 * NCTA, dl);
          mbar_arrive_e(sbase + B_GATE);
          PROF(41, lane == 0);
        }
      }
    }
  } else {
    const int wg = wid >> 2, warp = wid & 3;
    const int g = lane >> 2, qd = lane & 3;
    bulk_prefetch(wmod + (size_t)(b * 8 + wid) * (6 * D_), PF_BYTES);
    bulk_prefetch(wmod + (size_t)(b * 8 + wid) * (6 * D_) + D_, PF_BYTES);
    bar_sync(0, 384);
    bulk_prefetch(wmod + (size_t)(b * 8 + wid) * (6 * D_) + PF_BYTES / 2, PF_BYTES);
    bulk_prefetch(wmod + (size_t)(b * 8 + wid) * (6 * D_) + PF_BYTES / 2 + D_, PF_BYTES);
    const unsigned e1 = 1 + ld_relaxed(flags + FO_EPOCH), par = e1 & 1;
    reg_alloc<232>();
    PROF(1, tid == 0);
    const uint32_t wgoff = wg * 8192;
    const uint32_t frag0 = wid * 2048 + (lane & 15) * 128 + (((lane >> 4) ^ (lane & 7)) << 4);
    const uint32_t slab = sbase + SM_STG + wid * 2048;

    LnRow ln;
    {
      uint2* const lmail = &mail0->ln1[(mb * 8 + (wid & 1) * 4 + (j >> 1)) * 16 + (j & 1) * 8 + (wid >> 1) + (lane & 1) * 4];
      st_rlx_v2(lmail, par ^ 1, par ^ 1, lane < 2);
      float s[2][2] = {{0.f, 0.f}, {0.f, 0.f}}, q2[2][2] = {{0.f, 0.f}, {0.f, 0.f}};
      #pragma unroll
      for (int c = 0; c < 8; c++) {
        if (c == 4) asm volatile("" : "+f"(s[0][0]), "+f"(s[0][1]), "+f"(q2[0][0]), "+f"(q2[0][1]));
        if ((c & 3) == 0) mbar_wait(sbase + B_X + 8 * (c + (wid >> 1)), 0, dl);
        if (c == 4) { PROF(3, tid == 224); PROF(93, tid == 0); }
        const uint4 v = lds128(sbase + SM_XR + (c >> 2) * 16384 + wid * 2048 + (c & 3) * 512 + lane * 16);
        const uint32_t vv[4] = {v.x, v.y, v.z, v.w};
        #pragma unroll
        for (int e = 0; e < 4; e++) {
          const float lo = bf_lo(vv[e]), hi = bf_hi(vv[e]);
          s[c >> 2][0] += lo; s[c >> 2][1] += hi; q2[c >> 2][0] = fmaf(lo, lo, q2[c >> 2][0]); q2[c >> 2][1] = fmaf(hi, hi, q2[c >> 2][1]);
        }
      }
      const bool odd = lane & 1;
      float sm = (s[0][0] + s[0][1]), so = (s[1][0] + s[1][1]), qm = (q2[0][0] + q2[0][1]), qo = (q2[1][0] + q2[1][1]);
      { const float a = odd ? so : sm, c = odd ? qo : qm;
        sm = a + __shfl_xor_sync(0xffffffffu, odd ? sm : so, 1); qm = c + __shfl_xor_sync(0xffffffffu, odd ? qm : qo, 1); }
      #pragma unroll
      for (int o = 2; o < 32; o <<= 1) { sm += __shfl_xor_sync(0xffffffffu, sm, o); qm += __shfl_xor_sync(0xffffffffu, qm, o); }
      sm *= (1.f / D_);
      ln_row(ln, 0, sm, fast_rsqrt(fmaxf(qm * (1.f / D_) - sm * sm, 0.f) + 1e-5f));
      st_rlx_v2(lmail, (ln.rs[0] << 16) | par, (ln.nb[0] << 16) | par, lane < 2);
      mbar_arrive_e(sbase + B_LN);
      PROF(4, tid == 224);
    }

    uint4* const halo_out = mail0->halo[par] + ((mb * 16 + j) * 2 + wg) * 128 + lane;
    const uint4* const halo_in = halo_out - 16 * 256;
    const uint32_t xch = sbase + SM_XCH + (tid >> 5) * 2048 + lane * 16;
    const bool noprev = mb == 0 && warp == 0, remote = mb > 0 && warp == 0;
    float a0[64], a1[64];
    uint32_t x2[32];
    Ring r{zero, 0, 0, dl};
    Frag8 qA, qB, kA, kB, vA, vB, wA, wB;
    {
      float acc[128];
      uint32_t A0[16], A1[16];
      undef_regs(acc);
      const uint32_t tab = sbase + SM_MODT + qd * 16;
      uint4 p[4];
      const uint32_t rot = j >> 1;
      Frag4 fq;
      #pragma unroll
      for (int q = 0; q < 4; q++) fq.o[q] = frag0 ^ ((q ^ rot) << 5);
      mbar_wait(sbase + B_LN, 0, dl);
      const uint2* const lin = &mail0->ln1[(mb * 8 + wid) * 16 + g];
      uint2 v0, v1;
      q_wait(0, sbase, dl);
      #pragma unroll
      for (int kk = 0; kk < 4; kk++) ldmatrix_x4(sbase + SM_X0 + fq.o[kk], A0[4 * kk], A0[4 * kk + 1], A0[4 * kk + 2], A0[4 * kk + 3]);
      do { v0 = ld_rlx_v2(lin); v1 = ld_rlx_v2(lin + 8); } while (!poll_done(((bad2(v0.x, v0.y, par) | bad2(v1.x, v1.y, par)) & 1) == 0, dl));
      ln.rs[0] = hi_halves(v0.x, v0.x); ln.nb[0] = hi_halves(v0.y, v0.y); ln.rs[1] = hi_halves(v1.x, v1.x); ln.nb[1] = hi_halves(v1.y, v1.y);
      mbar_wait(sbase + B_MOD, 0, dl);
      #pragma unroll
      for (int kk = 0; kk < 4; kk++) p[kk] = lds128(tab + kk * 64);
      PROF(5, tid == 0);
      q_step_rs<true>(acc, A0, A1, p, 0, sbase, fq, tab, ln, rot, !(j & 1), true, dl, wg, zero);
      #pragma unroll
      for (int u = 1; u < 15; u += 2) {
        q_step_rs<true>(acc, A1, A0, p, u, sbase, fq, tab, ln, rot, j & 1, false, dl, wg, zero);
        q_step_rs<true>(acc, A0, A1, p, u + 1, sbase, fq, tab, ln, rot, !(j & 1), false, dl, wg, zero);
        if (u == 7) mbar_arrive_e(sbase + B_STREQ);
      }
      q_step_rs<false>(acc, A1, A0, p, 15, sbase, fq, tab, ln, rot, j & 1, false, dl, wg, zero);
      PROF(7, tid == 0);
      mbar_wait(sbase + B_STFREE, 0, dl);
      request_store(sbase + B_STREQ);
      wgmma_wait<0>();
      undef_regs(a0);
      { const uint32_t slot = m_wait(sbase, r); mma_step(a0, slot + wgoff, slot + 16384, true, q_empty(15, sbase)); m_next(r); }
      fence_regs(acc);
      PROF(8, tid == 0);
      sched_fence(zero);
      pack_half(vB, acc, 64, 1); transpose8(vB);
      m_step(a0, sbase, wgoff, r);
      sched_fence(zero);
      pack_half(kB, acc, 32, 1);
      attn_send(vB, 1, xch - 16384, warp, halo_out, mb < 15); attn_send(kB, 0, xch - 16384, warp, halo_out, mb < 15);
      m_step(a0, sbase, wgoff, r);
      sched_fence(zero);
      pack_half(qA, acc, 0, 0); pack_half(qB, acc, 0, 1); pack_half(kA, acc, 32, 0); pack_half(wB, acc, 96, 1); pack_half(wA, acc, 96, 0);
      m_step(a0, sbase, wgoff, r);
      sched_fence(zero);
      pack_half(vA, acc, 64, 0); transpose8(vA);
    }
    uint4 wP[2];
    Frag4 frag;
    #pragma unroll
    for (int q = 0; q < 4; q++) frag.o[q] = frag0 ^ (q << 5);
    {
      m_step(a0, sbase, wgoff, r);
      uint4 pv[4];
      attn_recv<4>(pv, 0, xch - 16384, wg, warp, halo_in, mb > 0);
      m_step(a0, sbase, wgoff, r);
      mbar_wait(sbase + B_STFREE, 1, dl);
      transpose8(wB);
      m_step(a0, sbase, wgoff, r);
      attn_check<4>(pv, 0, remote, halo_in, dl);
      wgmma_wait<0>();
      PROF(9, tid == 0);
      float o[2][5][4];
      sched_fence(zero);
      attn_core(qA, qB, kA, kB, vA, vB, pv, pv + 2, noprev, lane, o);
      attn_store(o, 0, sbase, frag);
      attn_store(o, 1, sbase, frag);
      request_store(sbase + B_STREQ);
      bar_sync(NB_CONS, 256);
      PROF(10, tid == 0);
      m_step(a0, sbase, wgoff, r);
      sched_fence(zero);
      attn_send(wB, 1, xch, warp, halo_out + 8 * 256, mb < 15);
      m_step(a0, sbase, wgoff, r);
      sched_fence(zero);
      transpose8(wA);
      #pragma unroll 1
      for (int i = 9; i < 15; i++) m_step(a0, sbase, wgoff, r);
      attn_recv<2>(wP, 2, xch, wg, warp, halo_in + 8 * 256, mb > 0);
      m_step(a0, sbase, wgoff, r);
    }
    {
      undef_regs(a1);
      {
        const uint32_t slot = m_wait(sbase, r);
        mma_step(a1, slot + wgoff, slot + 16384, true, m_prev(sbase, r), [&] {
          fence_regs(a0);
          pack_half(kB, a0, 32, 1);
          attn_send(kB, 0, xch, warp, halo_out + 8 * 256, mb < 15);
        });
        m_next(r);
      }
      PROF(14, tid == 0);
      sched_fence(zero);
      pack_half(kA, a0, 32, 0); pack_half(qA, a0, 0, 0); pack_half(qB, a0, 0, 1);
      m_step(a1, sbase, wgoff, r);
      attn_check<2>(wP, 2, remote, halo_in + 8 * 256, dl);
      uint4 kP[2];
      attn_recv<2>(kP, 0, xch, wg, warp, halo_in + 8 * 256, mb > 0);
      m_step(a1, sbase, wgoff, r);
      PROF(43, tid == 0);
      attn_check<2>(kP, 0, remote, halo_in + 8 * 256, dl);
      PROF(44, tid == 0);
      wgmma_wait<0>();
      PROF(15, tid == 0);
      float o[2][5][4];
      mbar_wait(sbase + B_STFREE, 0, dl);
      attn_core(qA, qB, kA, kB, wA, wB, kP, wP, noprev, lane, o);
      attn_store(o, 0, sbase, frag);
      attn_store(o, 1, sbase, frag);
      request_store(sbase + B_STREQ);
      bar_sync(NB_CONS, 256);
      PROF(16, tid == 0);
      auto residual = [&] {
        const uint32_t xs = m_wait(sbase, r), xe = sbase + B_EM + 8 * r.st;
        ring_next(r);
        #pragma unroll
        for (int t = 0; t < 2; t++) {
          #pragma unroll
          for (int jj = 4 * t; jj < 4 * t + 4; jj++) ldmatrix_x4(xs + t * 16384 + frag.o[jj & 3], x2[4 * jj], x2[4 * jj + 1], x2[4 * jj + 2], x2[4 * jj + 3]);
          if (t == 1) {
            uint32_t dep = 0;
            #pragma unroll
            for (int jj = 0; jj < 8; jj++) dep |= x2[4 * jj];
            mbar_arrive_e(xe + (dep & zero));
          }
          m_step(a1, sbase, wgoff, r);
        }
      };
      m_step(a1, sbase, wgoff, r);
      residual();
      #pragma unroll 1
      for (int i = 6; i < 8; i++) m_step(a1, sbase, wgoff, r);
      mma_step(a1, sbase + SM_STG + wgoff, m_wait(sbase, r) + 16384, false, m_prev(sbase, r));
      m_next(r);
      PROF(17, tid == 0);
      uint4* const sm = mail0->st2[par] + (mb * 8 + wid) * 64 + g;
      st_rlx_v4(sm + j * 8, 0, 0, 0, 0, qd == (g >> 1));
      #pragma unroll 1
      for (int i = 0; i < 7; i++) { m_step(a1, sbase, wgoff, r); PROF(42, tid == 0 && i == 0); }
      PROF(45, tid == 0);
      mbar_wait(sbase + B_VEC, 0, dl);
      mbar_wait(sbase + B_STFREE, 1, dl);
      const uint32_t vec = sbase + SM_VEC + qd * 16;
      uint4 ga[4];
      #pragma unroll
      for (int q = 0; q < 4; q++) ga[q] = lds128(vec + q * 64);
      wgmma_wait<0>();
      mbar_arrive_e(m_prev(sbase, r));
      fence_regs(a1);
      PROF(18, tid == 0);
      float gl[4] = {0.f, 0.f, 0.f, 0.f}, gh[4] = {0.f, 0.f, 0.f, 0.f};
      #pragma unroll
      for (int jj = 0; jj < 8; jj++) {
        uint32_t* v = &x2[4 * jj];
        const uint32_t wl = (jj & 1) ? ga[jj >> 1].z : ga[jj >> 1].x, wh = (jj & 1) ? ga[jj >> 1].w : ga[jj >> 1].y;
        #pragma unroll
        for (int e = 0; e < 4; e++) v[e] = fma_bf2(e & 2 ? wh : wl, pack_bf16(a1[8 * jj + 2 * e], a1[8 * jj + 2 * e + 1]), v[e]);
        mma16(gl, v[0], 0x3F803F80u, v[2], 0x3F803F80u, v[0], v[2]);
        mma16(gh, v[1], 0x3F803F80u, v[3], 0x3F803F80u, v[1], v[3]);
      }
      st_nonzero_v4(sm + j * 8, __float_as_uint(g & 1 ? gl[3] : gl[2]), __float_as_uint(g & 1 ? gl[1] : gl[0]),
                __float_as_uint(g & 1 ? gh[3] : gh[2]), __float_as_uint(g & 1 ? gh[1] : gh[0]), qd == (g >> 1));
      float s[2], q2[2];
      PROF(19, tid == 0);
      uint4 sb[4], cb[4];
      #pragma unroll
      for (int q = 0; q < 4; q++) { sb[q] = lds128(vec + 256 + q * 64); cb[q] = lds128(vec + 512 + q * 64); }
      uint4 p0, p1;
      while (true) {
        p0 = ld_rlx_v4(sm + qd * 16); p1 = ld_rlx_v4(sm + qd * 16 + 8);
        if (poll_done(min(min4(p0), min4(p1)) != 0, dl)) break;
      }
      PROF(20, tid == 0);
      s[0] = __uint_as_float(p0.x) + __uint_as_float(p1.x); q2[0] = __uint_as_float(p0.y) + __uint_as_float(p1.y);
      s[1] = __uint_as_float(p0.z) + __uint_as_float(p1.z); q2[1] = __uint_as_float(p0.w) + __uint_as_float(p1.w);
      #pragma unroll
      for (int o2 = 1; o2 <= 2; o2 <<= 1)
        #pragma unroll
        for (int h = 0; h < 2; h++) { s[h] += __shfl_xor_sync(0xffffffffu, s[h], o2); q2[h] += __shfl_xor_sync(0xffffffffu, q2[h], o2); }
      #pragma unroll
      for (int h = 0; h < 2; h++) {
        const float m = s[h] * (1.f / D_);
        ln_row(ln, h, m, fast_rsqrt(fmaxf(q2[h] * (1.f / D_) - m * m, 0.f) + 1e-5f));
      }
      #pragma unroll
      for (int jj = 0; jj < 8; jj++) {
        const uint32_t cl = (jj & 1) ? cb[jj >> 1].z : cb[jj >> 1].x, ch = (jj & 1) ? cb[jj >> 1].w : cb[jj >> 1].y;
        const uint32_t sl = (jj & 1) ? sb[jj >> 1].z : sb[jj >> 1].x, sh = (jj & 1) ? sb[jj >> 1].w : sb[jj >> 1].y;
        stmatrix_x4(sbase + SM_STG + (jj >> 2) * 16384 + frag.o[jj & 3], ln_mod(x2[4 * jj], ln, 0, cl, sl), ln_mod(x2[4 * jj + 1], ln, 1, cl, sl),
                    ln_mod(x2[4 * jj + 2], ln, 0, ch, sh), ln_mod(x2[4 * jj + 3], ln, 1, ch, sh));
        if (jj == 3) { request_store(sbase + B_STH); sched_fence(zero); }
      }
      request_store(sbase + B_STREQ);
      bar_sync(NB_WG + wg, 128);
      PROF(21, tid == 0);
    }

    undef_regs(a0);
    #pragma unroll
    for (int t = 0; t < 2; t++) {
      const uint32_t slot = m_wait(sbase, r);
      if (t == 0) mma_step<false>(a0, sbase + SM_STG + wgoff, slot, true, 0);
      else mma_step(a0, sbase + SM_STG + 16384 + wgoff, slot, false, m_prev(sbase, r));
      mma_step<false>(a1, sbase + SM_STG + t * 16384 + wgoff, slot + 16384, t == 0, 0);
      m_next(r);
    }
    PROF(22, tid == 0);
    #pragma unroll 1
    for (int t = 0; t < 7; t += 2) {
      g_switch(a1, a0, t == 0 ? 14 : 11, t > 0, 5 + t, sbase, wgoff, frag, r);
      if (t == 6) break;
      g_switch(a0, a1, t == 0 ? 9 : 11, true, 6 + t, sbase, wgoff, frag, r);
    }
    #pragma unroll 1
    for (int i = 5; i < 56 - DTAIL; i++) m_step(a1, sbase, wgoff, r);
    if (DTAIL) {
      if (wg == 1) { wgmma_wait<0>(); mbar_arrive_e(m_prev(sbase, r)); bar_sync(NB_ORD, 256); }
      #pragma unroll
      for (int i = 0; i < DTAIL; i++) {
        const uint32_t slot = m_wait(sbase, r);
        const uint32_t alo = ((slot + wgoff) >> 4) + (1u << 16), blo = ((slot + 16384) >> 4) + (512u << 16);
        wgmma_fence();
        #pragma unroll
        for (int k = 0; k < 4; k++) wgmma_m64n128k16_ss(a1, desc_from_lo(alo + k * 2), desc_from_lo(blo + k * 128), true);
        wgmma_commit();
        ring_next(r);
      }
      if (wg == 0) bar_arrive(NB_ORD, 256);
    }
    {
      mbar_wait(sbase + B_STFREE, 1, dl);
      mbar_wait(sbase + B_VEC + 8, 0, dl);
      uint4 gb[4];
      #pragma unroll
      for (int q = 0; q < 4; q++) gb[q] = lds128(sbase + SM_VEC + 768 + qd * 16 + q * 64);
      wgmma_wait<0>();
      fence_regs(a1);
      PROF(50, tid == 128);
      #pragma unroll
      for (int t = 0; t < 2; t++) {
        #pragma unroll
        for (int jj = 4 * t; jj < 4 * t + 4; jj++) {
          const uint32_t gl = (jj & 1) ? gb[jj >> 1].z : gb[jj >> 1].x, gh = (jj & 1) ? gb[jj >> 1].w : gb[jj >> 1].y;
          const int i = 8 * jj;
          stmatrix_x4(sbase + SM_STG + t * 16384 + frag.o[jj & 3],
                      fma_bf2(gl, pack_bf16(a1[i], a1[i + 1]), x2[4 * jj]), fma_bf2(gl, pack_bf16(a1[i + 2], a1[i + 3]), x2[4 * jj + 1]),
                      fma_bf2(gh, pack_bf16(a1[i + 4], a1[i + 5]), x2[4 * jj + 2]), fma_bf2(gh, pack_bf16(a1[i + 6], a1[i + 7]), x2[4 * jj + 3]));
        }
        fence_proxy_async_smem();
        tma_store_3d(&maps.out, slab + t * 16384, j * 128 + t * 64, mb * 64 + warp * 16, wg);
      }
      bulk_commit();
      st_rlx(tid == 0 ? flags + FO_EPOCH : &mail0->flags[FL_EPOCH], e1, j == 0 && (tid == 0 || (tid == 1 && mb == 0)));
      bulk_wait_read0();
      PROFN(51, tid == 128);
    }
  }
}

typedef CUresult (*PFN_encodeTiled)(CUtensorMap*, CUtensorMapDataType, cuuint32_t, void*, const cuuint64_t*, const cuuint64_t*,
                                    const cuuint32_t*, const cuuint32_t*, CUtensorMapInterleave, CUtensorMapSwizzle,
                                    CUtensorMapL2promotion, CUtensorMapFloatOOBfill);

void encode(PFN_encodeTiled fn, CUtensorMap* m, const void* ptr, int rank, const cuuint64_t* dims, const cuuint64_t* strides,
            const cuuint32_t* box) {
  const cuuint32_t es[5] = {1, 1, 1, 1, 1};
  fn(m, CU_TENSOR_MAP_DATA_TYPE_BFLOAT16, rank, const_cast<void*>(ptr), dims, strides, box, es, CU_TENSOR_MAP_INTERLEAVE_NONE,
     CU_TENSOR_MAP_SWIZZLE_128B, CU_TENSOR_MAP_L2_PROMOTION_L2_256B, CU_TENSOR_MAP_FLOAT_OOB_FILL_NONE);
}
void map2d(PFN_encodeTiled fn, CUtensorMap* m, const void* ptr, int cols, int rows, int boxrows) {
  const cuuint64_t dims[2] = {(cuuint64_t)cols, (cuuint64_t)rows}, strides[1] = {(cuuint64_t)cols * 2};
  const cuuint32_t box[2] = {64, (cuuint32_t)boxrows};
  encode(fn, m, ptr, 2, dims, strides, box);
}
void map_w2chunk(PFN_encodeTiled fn, CUtensorMap* m, const void* ptr, int cols, int rows) {
  const cuuint64_t dims[3] = {64, (cuuint64_t)rows, (cuuint64_t)cols / 64}, strides[2] = {(cuuint64_t)cols * 2, 128};
  const cuuint32_t box[3] = {64, 64, 2};
  encode(fn, m, ptr, 3, dims, strides, box);
}
void map_parity(PFN_encodeTiled fn, CUtensorMap* m, const void* ptr, int boxpairs, int boxpar) {
  const cuuint64_t dims[3] = {D_, S_ / 2, 2}, strides[2] = {D_ * 4, D_ * 2};
  const cuuint32_t box[3] = {64, (cuuint32_t)boxpairs, (cuuint32_t)boxpar};
  encode(fn, m, ptr, 3, dims, strides, box);
}

}

extern "C" void kernel_launch(void* const* d_in, const int* in_sizes, int n_in, void* d_out, int out_size) {
  (void)in_sizes; (void)n_in; (void)out_size;
  const bf16* x = (const bf16*)d_in[0];
  const bf16* wqkv = (const bf16*)d_in[1];
  const bf16* wo = (const bf16*)d_in[2];
  const bf16* w1 = (const bf16*)d_in[4];
  const bf16* w3 = (const bf16*)d_in[5];
  const bf16* w2 = (const bf16*)d_in[6];
  const bf16* cvec = (const bf16*)d_in[7];
  const bf16* w_mod = (const bf16*)d_in[8];

  static PFN_encodeTiled fn = nullptr;
  static Maps maps;
  static const void* cached[8] = {};
  static int sms = 0;
  static void* mail = nullptr;
  if (!fn) {
    void* p = nullptr; cudaDriverEntryPointQueryResult st;
    cudaGetDriverEntryPoint("cuTensorMapEncodeTiled", &p, cudaEnableDefault, &st);
    fn = (PFN_encodeTiled)p;
    cudaFuncSetAttribute(fused_block_kernel<0>, cudaFuncAttributeMaxDynamicSharedMemorySize, SM_TOTAL + SM_PROF);
    cudaFuncSetAttribute(fused_block_kernel<1>, cudaFuncAttributeMaxDynamicSharedMemorySize, SM_TOTAL + SM_PROF);
    cudaFuncSetAttribute(fused_block_kernel<2>, cudaFuncAttributeMaxDynamicSharedMemorySize, SM_TOTAL + SM_PROF);
    cudaGetSymbolAddress(&mail, g_mail);
    int dev = 0;
    cudaGetDevice(&dev);
    cudaDeviceGetAttribute(&sms, cudaDevAttrMultiProcessorCount, dev);
  }
  const void* cur[8] = {x, wqkv, wo, w1, w3, w2, d_out, w_mod};
  bool same = true;
  for (int i = 0; i < 8; i++) same = same && cached[i] == cur[i];
  if (!same) {
    void *o, *h2, *hh;
    cudaGetSymbolAddress(&hh, g_hh); cudaGetSymbolAddress(&o, g_o);
    h2 = o;
    map_parity(fn, &maps.x, x, 64, 2); map_parity(fn, &maps.out, d_out, 16, 1);
    map2d(fn, &maps.o, o, D_, S_, 128); map2d(fn, &maps.h2, h2, D_, S_, 128);
    {
      const cuuint64_t dims[3] = {512, (cuuint64_t)S_, 7}, strides[2] = {1024, (cuuint64_t)S_ * 1024};
      const cuuint32_t box[3] = {64, 128, 1};
      encode(fn, &maps.hh, hh, 3, dims, strides, box);
    }
    {
      const cuuint64_t dims[4] = {64, 1024, 16, 2}, strides[3] = {3072 * 2, 128, 2048};
      const cuuint64_t dimv[4] = {64, 1024, 8, 2}, stridev[3] = {3072 * 2, 128, 1024};
      const cuuint32_t box[4] = {64, 64, 1, 2};
      encode(fn, &maps.wqk, wqkv, 4, dims, strides, box);
      encode(fn, &maps.wvv, wqkv + 2048, 4, dimv, stridev, box);
      const cuuint64_t dim1[4] = {1024, 128, 8, 2}, stride1[3] = {3072 * 2, 128 * 3072 * 2, 2048};
      const cuuint32_t box1[4] = {64, 16, 4, 2};
      encode(fn, &maps.wq1, wqkv, 4, dim1, stride1, box1);
    }
    map_w2chunk(fn, &maps.wo, wo, D_, D_); map_w2chunk(fn, &maps.w2, w2, D_, F_);
    map2d(fn, &maps.w1, w1, F_, D_, 64); map2d(fn, &maps.w3, w3, F_, D_, 64);
    map2d(fn, &maps.wmod, w_mod, 6 * D_, D_, 256);
    for (int i = 0; i < 8; i++) cached[i] = cur[i];
  }
  if (sms == NCTA + NAUX) {
    fused_block_kernel<0><<<NCTA + NAUX, 384, SM_TOTAL + SM_PROF>>>(x, cvec, w_mod, (Mail*)mail, 0, maps);
  } else {
    fused_block_kernel<1><<<NAUX, 384, SM_TOTAL + SM_PROF>>>(x, cvec, w_mod, (Mail*)mail, 0, maps);
    fused_block_kernel<2><<<NCTA, 384, SM_TOTAL + SM_PROF>>>(x, cvec, w_mod, (Mail*)mail, 0, maps);
  }
}
```

```cpp
#include <cuda.h>
#include <cuda_runtime.h>
#include <cuda_bf16.h>
#include <stdint.h>

namespace {

typedef __nv_bfloat16 bf16;

constexpr int S_ = 2048, D_ = 1024, F_ = 3584;
constexpr int NCTA = 128, NAUX = 4;

__device__ __align__(1024) bf16 g_o[S_ * D_];
__device__ __align__(1024) bf16 g_hh[S_ * F_];
constexpr int FO_EPOCH = 0, FO_CNT = 1;
constexpr int FL_EPOCH = 16 * 32, FL_LN1 = FL_EPOCH + 2, FL_H2 = FL_EPOCH + 3, FL_O = FL_EPOCH + 4;
struct Mail {
  unsigned flags[32 * 32];
  float mod[8 * 6 * D_];
  uint2 ln1[16 * 8 * 16];
  uint4 halo[2][16 * 16 * 2 * 4 * 32];
  uint4 st2[2][16 * 8 * 8 * 8];
};
__device__ __align__(1024) Mail g_mail;

template <int mode>
__device__ __forceinline__ int cta_role() {
  if (mode) return mode == 1 ? NCTA + (blockIdx.x & 3) : blockIdx.x & 127;
  uint32_t sm;
  asm("mov.u32 %0, %%smid;" : "=r"(sm));
  sm = (sm & ~3u) == 12 ? sm + 108 : (sm & ~3u) == 120 ? sm - 108 : sm;
  const int t = sm >> 1;
  int r;
  if (t < 32) r = (t & 7) * 16 + (t >> 3) * 2 + (sm & 1);
  else if (t < 60) r = (1 + (t - 32) % 7) * 16 + 8 + ((t - 32) / 7) * 2 + (sm & 1);
  else if (t < 62) r = NCTA + sm - 120;
  else r = sm - 116;
  return r;
}
#define PROF(slot, on) do {} while (0)
#define PROFN(slot, on) do {} while (0)
#define PROF_OUT(role, t) do {} while (0)
constexpr uint32_t SM_PROF = 0;

__device__ __forceinline__ uint32_t smem_u32(const void* p) { return (uint32_t)__cvta_generic_to_shared(p); }
#define ELECT "{\n.reg .pred p;\nelect.sync _|p, 0xffffffff;\n@p "
__device__ __forceinline__ void mbar_init_e(uint32_t bar, uint32_t count) {
  asm volatile(ELECT "mbarrier.init.shared::cta.b64 [%0], %1;\n}" :: "r"(bar), "r"(count) : "memory");
}
__device__ __forceinline__ void mbar_expect_tx_e(uint32_t bar, uint32_t bytes) {
  asm volatile(ELECT "mbarrier.arrive.expect_tx.shared::cta.b64 _, [%0], %1;\n}" :: "r"(bar), "r"(bytes) : "memory");
}
__device__ __forceinline__ void mbar_arrive_e(uint32_t bar) {
  asm volatile(ELECT "mbarrier.arrive.shared::cta.b64 _, [%0];\n}" :: "r"(bar) : "memory");
}
__device__ __forceinline__ uint32_t clock32() { uint32_t t; asm volatile("mov.u32 %0, %%clock;" : "=r"(t)); return t; }
__device__ __forceinline__ void mbar_wait(uint32_t bar, uint32_t parity, uint32_t dl) {
  asm volatile("{\n.reg .pred p, q;\n.reg .b32 t;\n"
               "mbarrier.try_wait.parity.shared::cta.b64 p, [%0], %1;\n"
               "@p bra LAB_DONE;\n"
               "LAB_WAIT:\n"
               "mbarrier.try_wait.parity.shared::cta.b64 p, [%0], %1;\n"
               "mov.u32 t, %%clock;\n"
               "sub.s32 t, t, %2;\n"
               "setp.lt.and.s32 q, t, 0, !p;\n"
               "@q bra LAB_WAIT;\n"
               "LAB_DONE:\n}" :: "r"(bar), "r"(parity), "r"(dl) : "memory");
}
__device__ __forceinline__ void mbar_sleep(uint32_t bar, uint32_t parity, uint32_t dl) {
  asm volatile("{\n.reg .pred p;\n.reg .b32 t;\n"
               "LAB_WAIT:\n"
               "mbarrier.try_wait.parity.shared::cta.b64 p, [%0], %1, 20000;\n"
               "@p bra LAB_DONE;\n"
               "mov.u32 t, %%clock;\n"
               "sub.s32 t, t, %2;\n"
               "setp.lt.s32 p, t, 0;\n"
               "@p bra LAB_WAIT;\n"
               "LAB_DONE:\n}" :: "r"(bar), "r"(parity), "r"(dl) : "memory");
}
__device__ __forceinline__ bool poll_done(bool ok, uint32_t dl) {
  return __all_sync(0xffffffffu, ok || (int)(clock32() - dl) >= 0);
}
__device__ __forceinline__ unsigned ld_relaxed(const unsigned* p) {
  unsigned v; asm volatile("ld.relaxed.gpu.global.u32 %0, [%1];" : "=r"(v) : "l"(p) : "memory"); return v;
}
__device__ __forceinline__ void red_add_e(unsigned* p, unsigned v) {
  asm volatile(ELECT "red.relaxed.gpu.global.add.u32 [%0], %1;\n}" :: "l"(p), "r"(v) : "memory");
}
__device__ __forceinline__ void wait_flag(const unsigned* p, unsigned target, uint32_t dl) {
  asm volatile("{\n.reg .pred p;\n.reg .b32 t;\n"
               "LAB_WAIT:\n"
               "ld.relaxed.gpu.global.u32 t, [%0];\n"
               "sub.s32 t, t, %1;\n"
               "setp.ge.s32 p, t, 0;\n"
               "@p bra LAB_DONE;\n"
               "mov.u32 t, %%clock;\n"
               "sub.s32 t, t, %2;\n"
               "setp.lt.s32 p, t, 0;\n"
               "@p bra LAB_WAIT;\n"
               "LAB_DONE:\n}" :: "l"(p), "r"(target), "r"(dl) : "memory");
}
__device__ __forceinline__ void wait_until(uint32_t t) { while ((int)(clock32() - t) < 0) {} }
__device__ __forceinline__ void fence_proxy_async_smem() { asm volatile("fence.proxy.async.shared::cta;" ::: "memory"); }

constexpr uint64_t EVICT_FIRST = 0x12F0000000000000ull;
template <bool STREAM = false>
__device__ __forceinline__ void tma_load_2d(uint32_t dst, const CUtensorMap* m, uint32_t bar, int c0, int c1) {
  if (STREAM)
    asm volatile(ELECT "cp.async.bulk.tensor.2d.shared::cluster.global.mbarrier::complete_tx::bytes.L2::cache_hint [%0], [%1, {%3, %4}], [%2], %5;\n}"
                 :: "r"(dst), "l"(m), "r"(bar), "r"(c0), "r"(c1), "l"(EVICT_FIRST) : "memory");
  else
    asm volatile(ELECT "cp.async.bulk.tensor.2d.shared::cluster.global.mbarrier::complete_tx::bytes [%0], [%1, {%3, %4}], [%2];\n}"
                 :: "r"(dst), "l"(m), "r"(bar), "r"(c0), "r"(c1) : "memory");
}
template <bool STREAM = false>
__device__ __forceinline__ void tma_load_3d(uint32_t dst, const CUtensorMap* m, uint32_t bar, int c0, int c1, int c2) {
  if (STREAM)
    asm volatile(ELECT "cp.async.bulk.tensor.3d.shared::cluster.global.mbarrier::complete_tx::bytes.L2::cache_hint [%0], [%1, {%3, %4, %5}], [%2], %6;\n}"
                 :: "r"(dst), "l"(m), "r"(bar), "r"(c0), "r"(c1), "r"(c2), "l"(EVICT_FIRST) : "memory");
  else
    asm volatile(ELECT "cp.async.bulk.tensor.3d.shared::cluster.global.mbarrier::complete_tx::bytes [%0], [%1, {%3, %4, %5}], [%2];\n}"
                 :: "r"(dst), "l"(m), "r"(bar), "r"(c0), "r"(c1), "r"(c2) : "memory");
}
template <bool STREAM = false>
__device__ __forceinline__ void tma_load_4d(uint32_t dst, const CUtensorMap* m, uint32_t bar, int c0, int c1, int c2, int c3) {
  if (STREAM)
    asm volatile(ELECT "cp.async.bulk.tensor.4d.shared::cluster.global.mbarrier::complete_tx::bytes.L2::cache_hint [%0], [%1, {%3, %4, %5, %6}], [%2], %7;\n}"
                 :: "r"(dst), "l"(m), "r"(bar), "r"(c0), "r"(c1), "r"(c2), "r"(c3), "l"(EVICT_FIRST) : "memory");
  else
    asm volatile(ELECT "cp.async.bulk.tensor.4d.shared::cluster.global.mbarrier::complete_tx::bytes [%0], [%1, {%3, %4, %5, %6}], [%2];\n}"
                 :: "r"(dst), "l"(m), "r"(bar), "r"(c0), "r"(c1), "r"(c2), "r"(c3) : "memory");
}
__device__ __forceinline__ void tma_store_2d(const CUtensorMap* m, uint32_t src, int c0, int c1) {
  asm volatile(ELECT "cp.async.bulk.tensor.2d.global.shared::cta.bulk_group [%0, {%2, %3}], [%1];\n}"
               :: "l"(m), "r"(src), "r"(c0), "r"(c1) : "memory");
}
__device__ __forceinline__ void tma_store_3d(const CUtensorMap* m, uint32_t src, int c0, int c1, int c2) {
  asm volatile(ELECT "cp.async.bulk.tensor.3d.global.shared::cta.bulk_group [%0, {%2, %3, %4}], [%1];\n}"
               :: "l"(m), "r"(src), "r"(c0), "r"(c1), "r"(c2) : "memory");
}
__device__ __forceinline__ void bulk_load(uint32_t dst, const void* src, uint32_t bytes, uint32_t bar) {
  asm volatile(ELECT "cp.async.bulk.shared::cluster.global.mbarrier::complete_tx::bytes [%0], [%1], %2, [%3];\n}"
               :: "r"(dst), "l"(src), "r"(bytes), "r"(bar) : "memory");
}
__device__ __forceinline__ void bulk_prefetch(const void* src, uint32_t bytes) {
  asm volatile(ELECT "cp.async.bulk.prefetch.L2.global [%0], %1;\n}" :: "l"(src), "r"(bytes) : "memory");
}
__device__ __forceinline__ void bulk_commit() { asm volatile("cp.async.bulk.commit_group;" ::: "memory"); }
__device__ __forceinline__ void bulk_wait0() { asm volatile("cp.async.bulk.wait_group 0;" ::: "memory"); }
__device__ __forceinline__ void bulk_wait_read0() { asm volatile("cp.async.bulk.wait_group.read 0;" ::: "memory"); }
__device__ __forceinline__ void prefetch_tmap(const CUtensorMap* m) { asm volatile(ELECT "prefetch.tensormap [%0];\n}" :: "l"(m) : "memory"); }
__device__ __forceinline__ void wgmma_fence() { asm volatile("wgmma.fence.sync.aligned;" ::: "memory"); }
__device__ __forceinline__ void wgmma_commit() { asm volatile("wgmma.commit_group.sync.aligned;" ::: "memory"); }
template <int N> __device__ __forceinline__ void wgmma_wait() { asm volatile("wgmma.wait_group.sync.aligned %0;" :: "n"(N) : "memory"); }
template <int R> __device__ __forceinline__ void reg_alloc() { asm volatile("setmaxnreg.inc.sync.aligned.u32 %0;" :: "n"(R)); }
template <int R> __device__ __forceinline__ void reg_dealloc() { asm volatile("setmaxnreg.dec.sync.aligned.u32 %0;" :: "n"(R)); }
__device__ __forceinline__ void bar_sync(int id, int n) { asm volatile("bar.sync %0, %1;" :: "r"(id), "r"(n) : "memory"); }
__device__ __forceinline__ void bar_arrive(int id, int n) { asm volatile("bar.arrive %0, %1;" :: "r"(id), "r"(n) : "memory"); }
__device__ __forceinline__ void sched_fence(int zero) {
  asm volatile("{\n.reg .pred p;\n.reg .b32 t;\nsetp.eq.s32 p, %0, 0;\n@p bra.uni LAB_S;\n"
               "LAB_F:\nmov.u32 t, %%clock;\nsetp.eq.u32 p, t, 0;\n@p bra LAB_F;\nLAB_S:\n}" :: "r"(zero) : "memory");
}
template <int N> __device__ __forceinline__ void fence_regs(float (&a)[N]) {
  #pragma unroll
  for (int i = 0; i < N; i++) asm volatile("" : "+f"(a[i]) :: "memory");
}
template <int N> __device__ __forceinline__ void undef_regs(float (&a)[N]) {
  #pragma unroll
  for (int i = 0; i < N; i++) asm volatile("" : "=f"(a[i]));
}

__device__ __forceinline__ uint64_t desc_from_lo(uint32_t lo) { return (uint64_t)lo | ((uint64_t)0x40000040u << 32); }
__device__ __forceinline__ uint32_t pack_bf16(float lo, float hi) {
  uint32_t r; asm("cvt.rn.bf16x2.f32 %0, %1, %2;" : "=r"(r) : "f"(hi), "f"(lo)); return r;
}
__device__ __forceinline__ uint32_t fma_bf2(uint32_t a, uint32_t b, uint32_t c) {
  uint32_t d; asm("fma.rn.bf16x2 %0, %1, %2, %3;" : "=r"(d) : "r"(a), "r"(b), "r"(c)); return d;
}
__device__ __forceinline__ float bf_lo(uint32_t v) { return __uint_as_float(v << 16); }
__device__ __forceinline__ float bf_hi(uint32_t v) { return __uint_as_float(v & 0xFFFF0000u); }
__device__ __forceinline__ float bf16_round(float x) { return bf_lo(pack_bf16(x, 0.f)); }
__device__ __forceinline__ void stmatrix_x4(uint32_t addr, uint32_t r0, uint32_t r1, uint32_t r2, uint32_t r3) {
  asm volatile("stmatrix.sync.aligned.m8n8.x4.shared.b16 [%0], {%1, %2, %3, %4};" :: "r"(addr), "r"(r0), "r"(r1), "r"(r2), "r"(r3) : "memory");
}
__device__ __forceinline__ void stmatrix_x4_t(uint32_t addr, uint32_t r0, uint32_t r1, uint32_t r2, uint32_t r3) {
  asm volatile("stmatrix.sync.aligned.m8n8.x4.trans.shared.b16 [%0], {%1, %2, %3, %4};" :: "r"(addr), "r"(r0), "r"(r1), "r"(r2), "r"(r3) : "memory");
}
__device__ __forceinline__ void stmatrix_x4_if(uint32_t addr, uint32_t r0, uint32_t r1, uint32_t r2, uint32_t r3, bool on) {
  asm volatile("{\n.reg .pred p;\nsetp.ne.b32 p, %5, 0;\n@p stmatrix.sync.aligned.m8n8.x4.shared.b16 [%0], {%1, %2, %3, %4};\n}"
               :: "r"(addr), "r"(r0), "r"(r1), "r"(r2), "r"(r3), "r"((int)on) : "memory");
}
__device__ __forceinline__ void ldmatrix_x4(uint32_t addr, uint32_t& r0, uint32_t& r1, uint32_t& r2, uint32_t& r3) {
  asm volatile("ldmatrix.sync.aligned.m8n8.x4.shared.b16 {%0, %1, %2, %3}, [%4];" : "=r"(r0), "=r"(r1), "=r"(r2), "=r"(r3) : "r"(addr) : "memory");
}
__device__ __forceinline__ void ldmatrix_x4_t(uint32_t addr, uint32_t (&r)[4]) {
  asm volatile("ldmatrix.sync.aligned.m8n8.x4.trans.shared.b16 {%0, %1, %2, %3}, [%4];" : "=r"(r[0]), "=r"(r[1]), "=r"(r[2]), "=r"(r[3]) : "r"(addr) : "memory");
}
__device__ __forceinline__ void st_rlx(void* p, uint32_t a, bool on) {
  asm volatile("{\n.reg .pred p;\nsetp.ne.b32 p, %2, 0;\n@p st.relaxed.gpu.global.u32 [%0], %1;\n}" :: "l"(p), "r"(a), "r"((int)on) : "memory");
}
__device__ __forceinline__ void st_rlx_v2(void* p, uint32_t a, uint32_t b, bool on) {
  asm volatile("{\n.reg .pred p;\nsetp.ne.b32 p, %3, 0;\n@p st.relaxed.gpu.global.v2.u32 [%0], {%1, %2};\n}" :: "l"(p), "r"(a), "r"(b), "r"((int)on) : "memory");
}
__device__ __forceinline__ uint2 ld_rlx_v2(const void* p) {
  uint2 v; asm volatile("ld.relaxed.gpu.global.v2.u32 {%0,%1}, [%2];" : "=r"(v.x), "=r"(v.y) : "l"(p) : "memory"); return v;
}
__device__ __forceinline__ void st_rlx_v4(void* p, uint32_t a, uint32_t b, uint32_t c, uint32_t d, bool on) {
  asm volatile("{\n.reg .pred p;\nsetp.ne.b32 p, %5, 0;\n@p st.relaxed.gpu.global.v4.u32 [%0], {%1, %2, %3, %4};\n}"
               :: "l"(p), "r"(a), "r"(b), "r"(c), "r"(d), "r"((int)on) : "memory");
}
__device__ __forceinline__ void st_nonzero_v4(void* p, uint32_t a, uint32_t b, uint32_t c, uint32_t d, bool on) {
  st_rlx_v4(p, max(a, 1u), max(b, 1u), max(c, 1u), max(d, 1u), on);
}
__device__ __forceinline__ uint32_t min4(const uint4& v) { return min(min(v.x, v.y), min(v.z, v.w)); }
__device__ __forceinline__ uint4 ld_rlx_v4(const void* p) {
  uint4 v; asm volatile("ld.relaxed.gpu.global.v4.u32 {%0,%1,%2,%3}, [%4];" : "=r"(v.x), "=r"(v.y), "=r"(v.z), "=r"(v.w) : "l"(p) : "memory"); return v;
}
__device__ __forceinline__ uint32_t movmatrix_t(uint32_t a) {
  uint32_t d; asm volatile("movmatrix.sync.aligned.m8n8.trans.b16 %0, %1;" : "=r"(d) : "r"(a)); return d;
}
__device__ __forceinline__ void mma16(float (&c)[4], uint32_t a0, uint32_t a1, uint32_t a2, uint32_t a3, uint32_t b0, uint32_t b1) {
  asm volatile("mma.sync.aligned.m16n8k16.row.col.f32.bf16.bf16.f32 {%0,%1,%2,%3}, {%4,%5,%6,%7}, {%8,%9}, {%0,%1,%2,%3};"
               : "+f"(c[0]), "+f"(c[1]), "+f"(c[2]), "+f"(c[3]) : "r"(a0), "r"(a1), "r"(a2), "r"(a3), "r"(b0), "r"(b1));
}
__device__ __forceinline__ void sts128(uint32_t addr, uint32_t a, uint32_t b, uint32_t c, uint32_t d) {
  asm volatile("st.shared.v4.b32 [%0], {%1,%2,%3,%4};" :: "r"(addr), "r"(a), "r"(b), "r"(c), "r"(d) : "memory");
}
__device__ __forceinline__ uint4 lds128(uint32_t addr) {
  uint4 v; asm volatile("ld.shared.v4.b32 {%0,%1,%2,%3}, [%4];" : "=r"(v.x), "=r"(v.y), "=r"(v.z), "=r"(v.w) : "r"(addr) : "memory"); return v;
}
__device__ __forceinline__ uint32_t lds32(uint32_t addr) {
  uint32_t v; asm volatile("ld.shared.b32 %0, [%1];" : "=r"(v) : "r"(addr) : "memory"); return v;
}
__device__ __forceinline__ float2 lds64f(uint32_t addr) {
  float2 v; asm volatile("ld.shared.v2.f32 {%0,%1}, [%2];" : "=f"(v.x), "=f"(v.y) : "r"(addr) : "memory"); return v;
}
__device__ __forceinline__ void sts64(uint32_t addr, uint32_t a, uint32_t b) {
  asm volatile("st.shared.v2.b32 [%0], {%1, %2};" :: "r"(addr), "r"(a), "r"(b) : "memory");
}
__device__ __forceinline__ float fast_ex2(float x) { float y; asm("ex2.approx.ftz.f32 %0, %1;" : "=f"(y) : "f"(x)); return y; }
__device__ __forceinline__ float fast_rcp(float x) { float y; asm("rcp.approx.ftz.f32 %0, %1;" : "=f"(y) : "f"(x)); return y; }
__device__ __forceinline__ float fast_rsqrt(float x) { float y; asm("rsqrt.approx.ftz.f32 %0, %1;" : "=f"(y) : "f"(x)); return y; }
__device__ __forceinline__ float silu_f(float g) { return g * fast_rcp(1.f + fast_ex2(g * -1.4426950408889634f)); }
__device__ __forceinline__ float swiglu(float h, float v) {
  float t; asm("tanh.approx.f32 %0, %1;" : "=f"(t) : "f"(h));
  const float p = h * v;
  return fmaf(p, t, p);
}

__device__ __forceinline__ void wgmma_m64n128k16_ss(float (&d)[64], uint64_t descA, uint64_t descB, int scaleD) {
  asm volatile("{\n.reg .pred p;\nsetp.ne.b32 p, %66, 0;\n"
    "wgmma.mma_async.sync.aligned.m64n128k16.f32.bf16.bf16 "
    "{%0, %1, %2, %3, %4, %5, %6, %7, %8, %9, %10, %11, %12, %13, %14, %15, "
    "%16, %17, %18, %19, %20, %21, %22, %23, %24, %25, %26, %27, %28, %29, %30, %31, "
    "%32, %33, %34, %35, %36, %37, %38, %39, %40, %41, %42, %43, %44, %45, %46, %47, "
    "%48, %49, %50, %51, %52, %53, %54, %55, %56, %57, %58, %59, %60, %61, %62, %63}, "
    "%64, %65, p, 1, 1, 0, 1;\n}\n"
    : "+f"(d[0]), "+f"(d[1]), "+f"(d[2]), "+f"(d[3]), "+f"(d[4]), "+f"(d[5]), "+f"(d[6]), "+f"(d[7]),
      "+f"(d[8]), "+f"(d[9]), "+f"(d[10]), "+f"(d[11]), "+f"(d[12]), "+f"(d[13]), "+f"(d[14]), "+f"(d[15]),
      "+f"(d[16]), "+f"(d[17]), "+f"(d[18]), "+f"(d[19]), "+f"(d[20]), "+f"(d[21]), "+f"(d[22]), "+f"(d[23]),
      "+f"(d[24]), "+f"(d[25]), "+f"(d[26]), "+f"(d[27]), "+f"(d[28]), "+f"(d[29]), "+f"(d[30]), "+f"(d[31]),
      "+f"(d[32]), "+f"(d[33]), "+f"(d[34]), "+f"(d[35]), "+f"(d[36]), "+f"(d[37]), "+f"(d[38]), "+f"(d[39]),
      "+f"(d[40]), "+f"(d[41]), "+f"(d[42]), "+f"(d[43]), "+f"(d[44]), "+f"(d[45]), "+f"(d[46]), "+f"(d[47]),
      "+f"(d[48]), "+f"(d[49]), "+f"(d[50]), "+f"(d[51]), "+f"(d[52]), "+f"(d[53]), "+f"(d[54]), "+f"(d[55]),
      "+f"(d[56]), "+f"(d[57]), "+f"(d[58]), "+f"(d[59]), "+f"(d[60]), "+f"(d[61]), "+f"(d[62]), "+f"(d[63])
    : "l"(descA), "l"(descB), "r"(scaleD));
}
__device__ __forceinline__ void wgmma_m64n256k16_rs(float (&d)[128], uint32_t a0, uint32_t a1, uint32_t a2, uint32_t a3, uint64_t descB, int scaleD) {
  asm volatile("{\n.reg .pred p;\nsetp.ne.b32 p, %133, 0;\n"
    "wgmma.mma_async.sync.aligned.m64n256k16.f32.bf16.bf16 "
    "{%0, %1, %2, %3, %4, %5, %6, %7, %8, %9, %10, %11, %12, %13, %14, %15, "
    "%16, %17, %18, %19, %20, %21, %22, %23, %24, %25, %26, %27, %28, %29, %30, %31, "
    "%32, %33, %34, %35, %36, %37, %38, %39, %40, %41, %42, %43, %44, %45, %46, %47, "
    "%48, %49, %50, %51, %52, %53, %54, %55, %56, %57, %58, %59, %60, %61, %62, %63, "
    "%64, %65, %66, %67, %68, %69, %70, %71, %72, %73, %74, %75, %76, %77, %78, %79, "
    "%80, %81, %82, %83, %84, %85, %86, %87, %88, %89, %90, %91, %92, %93, %94, %95, "
    "%96, %97, %98, %99, %100, %101, %102, %103, %104, %105, %106, %107, %108, %109, %110, %111, "
    "%112, %113, %114, %115, %116, %117, %118, %119, %120, %121, %122, %123, %124, %125, %126, %127}, "
    "{%128, %129, %130, %131}, %132, p, 1, 1, 1;\n}\n"
    : "+f"(d[0]), "+f"(d[1]), "+f"(d[2]), "+f"(d[3]), "+f"(d[4]), "+f"(d[5]), "+f"(d[6]), "+f"(d[7]),
      "+f"(d[8]), "+f"(d[9]), "+f"(d[10]), "+f"(d[11]), "+f"(d[12]), "+f"(d[13]), "+f"(d[14]), "+f"(d[15]),
      "+f"(d[16]), "+f"(d[17]), "+f"(d[18]), "+f"(d[19]), "+f"(d[20]), "+f"(d[21]), "+f"(d[22]), "+f"(d[23]),
      "+f"(d[24]), "+f"(d[25]), "+f"(d[26]), "+f"(d[27]), "+f"(d[28]), "+f"(d[29]), "+f"(d[30]), "+f"(d[31]),
      "+f"(d[32]), "+f"(d[33]), "+f"(d[34]), "+f"(d[35]), "+f"(d[36]), "+f"(d[37]), "+f"(d[38]), "+f"(d[39]),
      "+f"(d[40]), "+f"(d[41]), "+f"(d[42]), "+f"(d[43]), "+f"(d[44]), "+f"(d[45]), "+f"(d[46]), "+f"(d[47]),
      "+f"(d[48]), "+f"(d[49]), "+f"(d[50]), "+f"(d[51]), "+f"(d[52]), "+f"(d[53]), "+f"(d[54]), "+f"(d[55]),
      "+f"(d[56]), "+f"(d[57]), "+f"(d[58]), "+f"(d[59]), "+f"(d[60]), "+f"(d[61]), "+f"(d[62]), "+f"(d[63]),
      "+f"(d[64]), "+f"(d[65]), "+f"(d[66]), "+f"(d[67]), "+f"(d[68]), "+f"(d[69]), "+f"(d[70]), "+f"(d[71]),
      "+f"(d[72]), "+f"(d[73]), "+f"(d[74]), "+f"(d[75]), "+f"(d[76]), "+f"(d[77]), "+f"(d[78]), "+f"(d[79]),
      "+f"(d[80]), "+f"(d[81]), "+f"(d[82]), "+f"(d[83]), "+f"(d[84]), "+f"(d[85]), "+f"(d[86]), "+f"(d[87]),
      "+f"(d[88]), "+f"(d[89]), "+f"(d[90]), "+f"(d[91]), "+f"(d[92]), "+f"(d[93]), "+f"(d[94]), "+f"(d[95]),
      "+f"(d[96]), "+f"(d[97]), "+f"(d[98]), "+f"(d[99]), "+f"(d[100]), "+f"(d[101]), "+f"(d[102]), "+f"(d[103]),
      "+f"(d[104]), "+f"(d[105]), "+f"(d[106]), "+f"(d[107]), "+f"(d[108]), "+f"(d[109]), "+f"(d[110]), "+f"(d[111]),
      "+f"(d[112]), "+f"(d[113]), "+f"(d[114]), "+f"(d[115]), "+f"(d[116]), "+f"(d[117]), "+f"(d[118]), "+f"(d[119]),
      "+f"(d[120]), "+f"(d[121]), "+f"(d[122]), "+f"(d[123]), "+f"(d[124]), "+f"(d[125]), "+f"(d[126]), "+f"(d[127])
    : "r"(a0), "r"(a1), "r"(a2), "r"(a3), "l"(descB), "r"(scaleD));
}

constexpr uint32_t MSLOT = 32768, QSLOT = 49152;
constexpr int NM = 6;
constexpr uint32_t SM_X0 = 3 * QSLOT;
constexpr uint32_t SM_XR = SM_X0 + 16384;
constexpr uint32_t SM_STG = 196608;
constexpr uint32_t SM_XCH = SM_STG + 16384;
constexpr uint32_t SM_BAR = SM_STG + 32768;
constexpr uint32_t SM_VEC = SM_BAR + 512;
constexpr uint32_t SM_MODT = SM_VEC;
constexpr uint32_t SM_TOTAL = SM_VEC + 2048;
constexpr uint32_t B_X = SM_BAR  , B_EQ = B_X + 64, B_EM = B_EQ + 32, B_STREQ = B_EM + 48, B_STH = B_STREQ + 8, B_LN = B_STH + 8,
                   B_FQ = B_LN + 8, B_FM = B_FQ + 32, B_MOD = B_FM + 48  , B_GATE = B_MOD + 64, B_STFREE = B_GATE + 8, B_VEC = B_STFREE + 8  ,
                   B_FLG = B_VEC + 16  , B_H2A = B_FLG + 24, B_END = B_FLG + 96;
constexpr int NB_WG = 1  , NB_CONS = 3, NB_ORD = 4  ;
#define TUNE(name, value) constexpr int name = value
TUNE(PF_BYTES, 256);
TUNE(X_GAP, 250);
TUNE(AUX_HOLD, 3200);
TUNE(AUX_URG, 4);
TUNE(AUX_SLOW, 84);
TUNE(AUX_GAP, 500);
TUNE(MSEP, 6);
TUNE(ASPLIT, 2);
TUNE(WPRE, 2);
TUNE(GPRE, 5);
TUNE(DTAIL, 4);

struct Maps {
  CUtensorMap x, out;
  CUtensorMap o, h2, hh;
  CUtensorMap wqk, wvv, wq1, wo, w1, w3, w2;
  CUtensorMap wmod;
};

struct Ring { int st; uint32_t ph; int prev; uint32_t dl;
};
__device__ __forceinline__ void ring_next(Ring& r) { if (++r.st == NM) { r.st = 0; r.ph ^= 1; } }

__device__ __forceinline__ void retire_prev(uint32_t rel, bool on) {
  wgmma_commit();
  wgmma_wait<1>();
  if (on) mbar_arrive_e(rel);
}
struct Nop { __device__ __forceinline__ void operator()() const {} };
template <bool REL = true, class F = Nop>
__device__ __forceinline__ void mma_step(float (&acc)[64], uint32_t a, uint32_t b, bool first, uint32_t rel, F urgent = F()) {
  const uint32_t alo = (a >> 4) + (1u << 16), blo = (b >> 4) + (512u << 16);
  wgmma_fence();
  #pragma unroll
  for (int k = 0; k < 4; k++) {
    wgmma_m64n128k16_ss(acc, desc_from_lo(alo + k * 2), desc_from_lo(blo + k * 128), k > 0 || !first);
    if (k == 0) { retire_prev(rel, REL); urgent(); }
  }
  wgmma_commit();
}
__device__ __forceinline__ uint32_t m_wait(uint32_t sbase, const Ring& r) {
  mbar_wait(sbase + B_FM + 8 * r.st, r.ph, r.dl);
  return sbase + r.st * MSLOT;
}
__device__ __forceinline__ uint32_t m_prev(uint32_t sbase, const Ring& r) { return sbase + B_EM + 8 * r.prev; }
__device__ __forceinline__ void m_next(Ring& r) {
  r.prev = r.st; ring_next(r);
}
__device__ __forceinline__ void m_step(float (&acc)[64], uint32_t sbase, uint32_t wgoff, Ring& r, bool first = false) {
  const uint32_t slot = m_wait(sbase, r);
  mma_step(acc, slot + wgoff, slot + 16384, first, m_prev(sbase, r));
  m_next(r);
}

struct LnRow { uint32_t rs[2], nb[2]; };
__device__ __forceinline__ void ln_row(LnRow& l, int h, float mean, float rstd) {
  l.rs[h] = pack_bf16(rstd, rstd);
  const float nb = -mean * bf_lo(l.rs[h]);
  l.nb[h] = pack_bf16(nb, nb);
}
__device__ __forceinline__ uint32_t ln_mod(uint32_t x, const LnRow& l, int h, uint32_t c1, uint32_t s) {
  return fma_bf2(fma_bf2(x, l.rs[h], l.nb[h]), c1, s);
}

__device__ __forceinline__ uint32_t q_wait(int u, uint32_t sbase, uint32_t dl) {
  mbar_wait(sbase + B_FQ + 8 * (u & 3), (u >> 2) & 1, dl);
  return sbase + (u & 3) * QSLOT;
}
__device__ __forceinline__ uint32_t q_empty(int u, uint32_t sbase) { return sbase + B_EQ + 8 * (u & 3); }
struct Frag4 { uint32_t o[4]; };
__device__ __forceinline__ void q_load(uint32_t (&A)[16], uint4 (&p)[4], int kk, uint32_t tile, const Frag4& f, uint32_t t) {
  ldmatrix_x4(tile + f.o[kk], A[4 * kk], A[4 * kk + 1], A[4 * kk + 2], A[4 * kk + 3]);
  p[kk] = lds128(t + kk * 64);
}
__device__ __forceinline__ void q_norm(uint32_t (&A)[16], const uint4 (&p)[4], int kk, const LnRow& l) {
  A[4 * kk + 0] = ln_mod(A[4 * kk + 0], l, 0, p[kk].x, p[kk].z); A[4 * kk + 1] = ln_mod(A[4 * kk + 1], l, 1, p[kk].x, p[kk].z);
  A[4 * kk + 2] = ln_mod(A[4 * kk + 2], l, 0, p[kk].y, p[kk].w); A[4 * kk + 3] = ln_mod(A[4 * kk + 3], l, 1, p[kk].y, p[kk].w);
}
template <bool NEXT>
__device__ __forceinline__ void q_step_rs(float (&acc)[128], uint32_t (&A)[16], uint32_t (&N)[16], uint4 (&p)[4], int u, uint32_t sbase,
                                          const Frag4& f, uint32_t tab, const LnRow& l, uint32_t rot, bool keep, bool first, uint32_t dl, int wg, int zero) {
  const uint32_t slot = first ? sbase : q_wait(u, sbase, dl);
  const uint32_t blo = ((slot + 16384) >> 4) + (512u << 16) + rot * 128 + (zero << (u >> 2)), t = tab + ((u + 1) & 7) * 256;
  #pragma unroll
  for (int kk = 0; kk < 4; kk++) q_norm(A, p, kk, l);
  #pragma unroll
  for (int i = 0; i < 16; i++) asm volatile("" : "+r"(A[i]));
  if (!first) sched_fence(zero);
  if (first) {
    mbar_wait(sbase + B_GATE, 0, dl);
    PROF(6, threadIdx.x == 0);
  }
  if (!(first && wg == 0)) bar_sync(NB_ORD + wg, 256);
  wgmma_fence();
  #pragma unroll
  for (int kk = 0; kk < 4; kk++) {
    wgmma_m64n256k16_rs(acc, A[4 * kk], A[4 * kk + 1], A[4 * kk + 2], A[4 * kk + 3], desc_from_lo(blo ^ (kk * 128)), kk > 0 || !first);
    if (kk == 0) retire_prev(q_empty(u - 1, sbase), !first);
    if (NEXT && kk == 1) {
      if ((u & 1) && u < MSEP) mbar_wait(sbase + B_MOD + 4 * (u + 1), 0, dl);
      #pragma unroll
      for (int q = 0; q < 4; q++) q_load(N, p, q, slot, f, t);
    }
    if (kk == 3 && (NEXT || wg == 0)) bar_arrive(NB_ORD + (wg ^ 1), 256);
    if (kk == 1) stmatrix_x4_if(sbase + SM_STG + (u >> 3) * 16384 + (f.o[0] ^ (((u >> 1 & 3) ^ rot) << 5)), A[0], A[1], A[2], A[3], keep);
  }
  wgmma_commit();
}

typedef uint32_t Frag8[8];
template <int N> __device__ __forceinline__ void pack_half(Frag8& f, const float (&acc)[N], int off, int half) {
  #pragma unroll
  for (int e = 0; e < 8; e++) { f[e] = pack_bf16(acc[off + 4 * e + 2 * half], acc[off + 4 * e + 2 * half + 1]); asm volatile("" : "+r"(f[e])); }
}
__device__ __forceinline__ void transpose8(Frag8& f) {
  #pragma unroll
  for (int e = 0; e < 8; e++) f[e] = movmatrix_t(f[e]);
}
__device__ __forceinline__ void attn_send(const Frag8& f, int kv, uint32_t xch, int warp, uint4* halo_out, bool has_next) {
  if (warp == 3) {
    st_nonzero_v4(halo_out + kv * 64, f[0], f[1], f[2], f[3], has_next); st_nonzero_v4(halo_out + kv * 64 + 32, f[4], f[5], f[6], f[7], has_next);
  } else {
    sts128(xch + 2048 + kv * 1024, f[0], f[1], f[2], f[3]); sts128(xch + 2048 + kv * 1024 + 512, f[4], f[5], f[6], f[7]);
  }
}
template <int N>
__device__ __forceinline__ void attn_recv(uint4* p, int first, uint32_t xch, int wg, int warp, const uint4* halo_in, bool has_prev) {
  bar_sync(NB_WG + wg, 128);
  #pragma unroll
  for (int e = 0; e < N; e++)
    asm volatile("{\n.reg .pred p, q;\nsetp.ne.b32 p, %6, 0;\nsetp.ne.b32 q, %7, 0;\n"
                 "mov.b32 %0, 0;\nmov.b32 %1, 0;\nmov.b32 %2, 0;\nmov.b32 %3, 0;\n"
                 "@p ld.shared.v4.b32 {%0,%1,%2,%3}, [%4];\n@q ld.relaxed.gpu.global.v4.u32 {%0,%1,%2,%3}, [%5];\n}"
                 : "=&r"(p[e].x), "=&r"(p[e].y), "=&r"(p[e].z), "=&r"(p[e].w)
                 : "r"(xch + (first + e) * 512), "l"(halo_in + (first + e) * 32), "r"((int)(warp > 0)), "r"((int)(warp == 0 && has_prev)) : "memory");
}
template <int N>
__device__ __forceinline__ void attn_check(uint4* p, int first, bool remote, const uint4* halo_in, uint32_t dl) {
  if (remote) {
    while (true) {
      uint32_t m = ~0u;
      #pragma unroll
      for (int e = 0; e < N; e++) m = min(m, min4(p[e]));
      if (poll_done(m != 0, dl)) break;
      #pragma unroll
      for (int e = 0; e < N; e++) p[e] = ld_rlx_v4(halo_in + (first + e) * 32);
    }
  }
}
template <int SPLIT, class F>
__device__ __forceinline__ void attn_core(const Frag8& qA, const Frag8& qB, const Frag8& kA, const Frag8& kB, const Frag8& vA, const Frag8& vB,
                                          const uint4* kP, const uint4* vP, bool noprev, int lane, float (&o)[2][5][4], F late) {
  const int g = lane >> 2, qd = lane & 3;
  const bool s0 = 2 * qd > g, s1 = 2 * qd + 1 > g;
  const uint32_t msk = (s0 ? 0xFFFFu : 0u) | (s1 ? 0xFFFF0000u : 0u);
  float s[2][3][4];
  uint32_t pr[2][2];
  auto scores = [&](int h, int nb) {
    s[h][nb][0] = s[h][nb][1] = s[h][nb][2] = s[h][nb][3] = 0.f;
    #pragma unroll
    for (int kk = 0; kk < 2; kk++) {
      const int e = 4 * h + 2 * kk;
      mma16(s[h][nb], qA[e], qB[e], qA[e + 1], qB[e + 1], nb == 1 ? kA[e] : nb == 2 ? kB[e] : kk ? kP[h].z : kP[h].x,
            nb == 1 ? kA[e + 1] : nb == 2 ? kB[e + 1] : kk ? kP[h].w : kP[h].y);
    }
  };
  auto rows = [&](int h, int y) {
    constexpr float SC = 0.17677669529663687f * 1.4426950408889634f;
    const float l0 = s0 ? (y == 0 && noprev ? -INFINITY : s[h][y][2 * y]) : s[h][y + 1][2 * y];
    const float l1 = s1 ? (y == 0 && noprev ? -INFINITY : s[h][y][2 * y + 1]) : s[h][y + 1][2 * y + 1];
    float m = fmaxf(l0, l1);
    m = fmaxf(m, __shfl_xor_sync(0xffffffffu, m, 1));
    m = fmaxf(m, __shfl_xor_sync(0xffffffffu, m, 2));
    const uint32_t p = pr[h][y] = pack_bf16(fast_ex2((l0 - m) * SC), fast_ex2((l1 - m) * SC));
    #pragma unroll
    for (int m2 = 0; m2 < 2; m2++) {
      const int e = 4 * h + 2 * m2;
      float (&d)[4] = o[h][2 * m2 + y];
      d[0] = d[1] = d[2] = d[3] = 0.f;
      if (y == 0) mma16(d, m2 ? vP[h].z : vP[h].x, m2 ? vP[h].w : vP[h].y, vA[e], vA[e + 1], p & msk, p & ~msk);
      else mma16(d, vA[e], vA[e + 1], vB[e], vB[e + 1], p & msk, p & ~msk);
    }
  };
  #pragma unroll
  for (int h = 0; h < 2; h++) { scores(h, 1); scores(h, 2); if (SPLIT == 0) scores(h, 0); }
  if (SPLIT == 2) { rows(0, 1); rows(1, 1); }
  if (SPLIT) { late(); scores(0, 0); scores(1, 0); }
  #pragma unroll
  for (int h = 0; h < 2; h++) {
    if (SPLIT < 2) rows(h, 1);
    rows(h, 0);
    o[h][4][0] = o[h][4][1] = o[h][4][2] = o[h][4][3] = 0.f;
    mma16(o[h][4], 0x3F803F80u, 0u, 0u, 0x3F803F80u, pr[h][0], pr[h][1]);
  }
}
__device__ __forceinline__ void attn_store(const float (&o)[2][5][4], int h, uint32_t sbase, const Frag4& f) {
  float r[4];
  #pragma unroll
  for (int e = 0; e < 4; e++) r[e] = fast_rcp(o[h][4][e]);
  #pragma unroll
  for (int m = 0; m < 2; m++) {
    const float (&lo)[4] = o[h][2 * m], (&hi)[4] = o[h][2 * m + 1];
    stmatrix_x4_t(sbase + SM_STG + f.o[2 * h + m], pack_bf16(lo[0] * r[0], lo[1] * r[1]), pack_bf16(hi[0] * r[2], hi[1] * r[3]),
                  pack_bf16(lo[2] * r[0], lo[3] * r[1]), pack_bf16(hi[2] * r[2], hi[3] * r[3]));
  }
}

__device__ __forceinline__ void request_store(uint32_t bar) {
  fence_proxy_async_smem();
  mbar_arrive_e(bar);
}

__device__ __forceinline__ void g_switch(float (&cur)[64], float (&prv)[64], int nrest, bool first, int n, uint32_t sbase, uint32_t wgoff,
                                         const Frag4& f, Ring& r) {
  #pragma unroll 1
  for (int i = 1; i < nrest; i++) m_step(prv, sbase, wgoff, r);
  m_step(prv, sbase, wgoff, r);
  m_step(cur, sbase, wgoff, r, first);
  mbar_wait(sbase + B_STFREE, (n - 1) & 1, r.dl);
  fence_regs(prv);
  PROF(28 + n, threadIdx.x == 0);
  #pragma unroll
  for (int jj = 0; jj < 4; jj++) {
    uint32_t p[4];
    #pragma unroll
    for (int e = 0; e < 4; e++) {
      const int i = jj * 8 + e * 2;
      p[e] = pack_bf16(swiglu(prv[i], prv[i + 32]), swiglu(prv[i + 1], prv[i + 33]));
    }
    stmatrix_x4(sbase + SM_STG + f.o[jj], p[0], p[1], p[2], p[3]);
    m_step(cur, sbase, wgoff, r);
  }
  request_store(sbase + B_STREQ);
}

__device__ __forceinline__ uint32_t bad2(uint32_t a, uint32_t b, unsigned par) {
  uint32_t d; asm("lop3.b32 %0, %1, %2, %3, 0x7E;" : "=r"(d) : "r"(a), "r"(b), "r"(par)); return d;
}
__device__ __forceinline__ uint32_t bad4(const uint4& v, unsigned par) { return bad2(v.x, v.y, par) | bad2(v.z, v.w, par); }
__device__ __forceinline__ uint32_t hi_halves(uint32_t lo, uint32_t hi) { return __byte_perm(lo, hi, 0x7632); }

__device__ __forceinline__ void gather_table(const float* src, uint32_t dst, uint32_t bar, unsigned par, uint32_t dl) {
  asm volatile("{\n.reg .pred p, e;\n.reg .b32 s<4>, c<4>, t<4>, w<4>;\n"
               "elect.sync _|e, 0xffffffff;\n"
               "LAB_POLL:\n"
               "ld.relaxed.gpu.global.v4.u32 {s0, s1, s2, s3}, [%0];\n"
               "ld.relaxed.gpu.global.v4.u32 {c0, c1, c2, c3}, [%0 + 4096];\n"
               "prmt.b32 w0, c0, c1, 0x7632;\nprmt.b32 w1, c2, c3, 0x7632;\nprmt.b32 w2, s0, s1, 0x7632;\nprmt.b32 w3, s2, s3, 0x7632;\n"
               "st.shared.v4.b32 [%1], {w0, w1, w2, w3};\n"
               "lop3.b32 t0, s0, s1, %3, 0x7E;\nlop3.b32 t1, s2, s3, %3, 0x7E;\nlop3.b32 t2, c0, c1, %3, 0x7E;\nlop3.b32 t3, c2, c3, %3, 0x7E;\n"
               "lop3.b32 t0, t0, t1, 1, 0xA8;\nlop3.b32 t2, t2, t3, 1, 0xA8;\n"
               "or.b32 t0, t0, t2;\n"
               "setp.eq.u32 p, t0, 0;\n"
               "vote.sync.all.pred p, p, 0xffffffff;\n"
               "@p bra.uni LAB_OK;\n"
               "mov.u32 t0, %%clock;\nsub.s32 t0, t0, %4;\nsetp.lt.s32 p, t0, 0;\n"
               "vote.sync.all.pred p, p, 0xffffffff;\n"
               "@p bra.uni LAB_POLL;\n"
               "LAB_OK:\n"
               "@e mbarrier.arrive.shared::cta.b64 _, [%2];\n}"
               :: "l"(src), "r"(dst), "r"(bar), "r"(par), "r"(dl) : "memory");
}

__device__ __forceinline__ int other_slot(int i, int j) { return i < 4 ? (~j & 4) + i : (j & 4) + i - 4 + (i - 4 >= (j & 3)); }

__device__ __forceinline__ int aux_col(int a, int u) { return u < 8 ? (a & 1) * 1024 + (2 * u + (a >> 1)) * 64 : 2048 + ((u - 8) * 4 + a) * 64; }
constexpr int NA = 7;
constexpr uint32_t A_FULL = SM_BAR, A_EMPTY = SM_BAR + 64, A_SUM = SM_BAR + 128, A_FREE = SM_BAR + 136, SM_RED = SM_VEC;
__device__ __forceinline__ void aux_role(const Maps& maps, const bf16* __restrict__ cvec, Mail* mail0, int zero, int a, uint32_t sbase, int wid) {
  const int tid = threadIdx.x, lane = tid & 31;
  const uint32_t dl = clock32() + 800000000u;
  int st = 0; uint32_t ph = 0;
  if (wid == 8) {
    prefetch_tmap(&maps.wmod);
    #pragma unroll
    for (int i = 0; i < 18; i++) mbar_init_e(sbase + A_FULL + 8 * i, i < 8 ? 1 : i < 17 ? 8 : 2);
    fence_proxy_async_smem();
    bar_arrive(0, 352);
    PROF(39, lane == 0);
    #pragma unroll
    for (int i = 0; i < NA; i++) {
      mbar_expect_tx_e(sbase + A_FULL + 8 * i, 32768);
      tma_load_2d(sbase + i * MSLOT, &maps.wmod, sbase + A_FULL + 8 * i, aux_col(a, i >> 2), (i & 3) * 256);
    }
    PROF(40, lane == 0);
    #pragma unroll 1
    for (int i = NA; i < 96; i++) {
      if (i >= AUX_SLOW) wait_until(clock32() + AUX_GAP);
      if (i == 8) wait_until(dl - 800000000u + AUX_HOLD);
      mbar_wait(sbase + A_EMPTY + 8 * st, ph, dl);
      mbar_expect_tx_e(sbase + A_FULL + 8 * st, 32768);
      tma_load_2d<true>(sbase + st * MSLOT, &maps.wmod, sbase + A_FULL + 8 * st, aux_col(a, i >> 2), (i & 3) * 256);
      if (++st == NA) { st = 0; ph ^= 1; }
    }
  } else if (wid < 8) {
    const int g = lane >> 2, qd = lane & 3;
    uint32_t sc[16];
    const uint2 c = *reinterpret_cast<const uint2*>(cvec + tid * 4);
    sts64(sbase + SM_RED + tid * 8, pack_bf16(silu_f(bf_lo(c.x)), silu_f(bf_hi(c.x))), pack_bf16(silu_f(bf_lo(c.y)), silu_f(bf_hi(c.y))));
    bar_sync(0, 352);
    #pragma unroll
    for (int i = 0; i < 16; i++) sc[i] = lds32(sbase + SM_RED + ((i >> 2) * 256 + wid * 32 + (i & 3) * 8 + qd * 2) * 2);
    bar_sync(NB_CONS, 256);
    PROF(38, tid == 0);
    const uint32_t aoff = (wid * 32 + (lane & 7) + (lane >> 4) * 8) * 128 + ((((lane >> 3) & 1) ^ (lane & 7)) << 4);
    uint32_t w[2][8][4];
    auto fetch = [&](uint32_t (&f)[8][4]) {
      mbar_wait(sbase + A_FULL + 8 * st, ph, dl);
      #pragma unroll
      for (int e = 0; e < 8; e++) ldmatrix_x4_t((sbase + st * MSLOT + aoff + (e >> 2) * 2048) ^ ((e & 3) << 5), f[e]);
      if (++st == NA) { st = 0; ph ^= 1; }
    };
    #pragma unroll 1
    for (int u = 0; u < 24; u++) {
      float acc[4][4];
      #pragma unroll
      for (int m = 0; m < 4; m++) acc[m][0] = acc[m][1] = acc[m][2] = acc[m][3] = 0.f;
      fetch(w[0]);
      #pragma unroll
      for (int q = 0; q < 4; q++) {
        PROF(30 + (u & 1) * 4 + q, u < 2 && tid == 0);
        const uint32_t rel = sbase + A_EMPTY + 8 * (st == 0 ? NA - 1 : st - 1);
        if (q < 3) fetch(w[(q + 1) & 1]);
        uint32_t dep = 0;
        #pragma unroll
        for (int e = 0; e < 8; e++) dep |= w[q & 1][e][0];
        mbar_arrive_e(rel + (dep & zero));
        if (q == 1) mbar_wait(sbase + A_FREE, (u & 1) ^ 1, dl);
        #pragma unroll
        for (int e = 0; e < 8; e++) {
          const uint32_t (&f)[4] = w[q & 1][e];
          mma16(acc[e & 3], f[0], f[1], f[2], f[3], sc[4 * q + 2 * (e >> 2)], sc[4 * q + 2 * (e >> 2) + 1]);
        }
      }
      const float v0 = qd & 2 ? (qd & 1 ? acc[3][0] : acc[2][0]) : (qd & 1 ? acc[1][0] : acc[0][0]);
      const float v1 = qd & 2 ? (qd & 1 ? acc[3][2] : acc[2][2]) : (qd & 1 ? acc[1][2] : acc[0][2]);
      sts64(sbase + SM_RED + wid * 256 + (qd * 8 + g) * 8, __float_as_uint(v0), __float_as_uint(v1));
      mbar_arrive_e(sbase + A_SUM);
      if (u < AUX_URG) mbar_wait(sbase + A_FREE, u & 1, dl);
    }
  } else if (wid < 11) {
    float* const mail = &mail0->mod[(wid - 9) * 4 * 6 * D_ + 2 * lane];
    unsigned par = ld_relaxed(&mail0->flags[FL_EPOCH + (lane >> 5)]);
    bar_sync(0, 352);
    par = (par + 1) & 1;
    #pragma unroll 1
    for (int u = -2; u < 24; u++) {
      if (u >= 0) {
        const int col = aux_col(a, u);
        const float add = (col >> 10) == 1 || (col >> 10) == 4 ? 1.f : 0.f;
        const float mul = col < 3 * D_ ? 1.f : col < 5 * D_ ? 0.5f : 2.f;
        mbar_wait(sbase + A_SUM, u & 1, dl);
        float2 v[8];
        #pragma unroll
        for (int w = 0; w < 8; w++) v[w] = lds64f(sbase + SM_RED + w * 256 + lane * 8);
        const float t0 = ((v[0].x + v[1].x) + (v[2].x + v[3].x)) + ((v[4].x + v[5].x) + (v[6].x + v[7].x));
        const float t1 = ((v[0].y + v[1].y) + (v[2].y + v[3].y)) + ((v[4].y + v[5].y) + (v[6].y + v[7].y));
        mbar_arrive_e(sbase + A_FREE + (__float_as_uint(t0 + t1) & zero));
        const uint32_t w = pack_bf16((add + bf16_round(t0)) * mul, (add + bf16_round(t1)) * mul), o = __shfl_xor_sync(0xffffffffu, w, 1);
        const uint32_t m0 = (lane & 1) ? (o & 0xFFFF0000u) : (w << 16), m1 = (lane & 1) ? (w & 0xFFFF0000u) : (o << 16);
        #pragma unroll
        for (int c = 0; c < 4; c++) st_rlx_v2(mail + c * 6 * D_ + col, m0 | par, m1 | par, true);
        PROF(1 + u, tid == 288);
      }
      #pragma unroll 1
      for (int v = 2 * (u + 2); v < 2 * (u + 3) && v < 24; v++)
        #pragma unroll
        for (int c = 0; c < 4; c++) st_rlx_v2(mail + c * 6 * D_ + aux_col(a, v), par ^ 1, par ^ 1, true);
    }
    const int t = a * 64 + tid - 288;
    #pragma unroll 4
    for (int i = t; i < 16 * 16 * 256; i += 256) mail0->halo[par ^ 1][i] = make_uint4(0, 0, 0, 0);
    #pragma unroll 4
    for (int i = t; i < 16 * 8 * 64; i += 256) mail0->st2[par ^ 1][i] = make_uint4(0, 0, 0, 0);
  }
}

template <int MODE>
__global__ void __launch_bounds__(384, 1)
fused_block_kernel(const bf16* __restrict__ x, const bf16* __restrict__ cvec, const bf16* __restrict__ wmod, Mail* mail0, int zero,
                   const __grid_constant__ Maps maps) {
  extern __shared__ __align__(1024) uint8_t smem_raw[];
  const uint32_t sbase = smem_u32(smem_raw);
  const int tid = threadIdx.x, lane = tid & 31;
  PROFN(0, tid == 0);
  const int wid = __shfl_sync(0xffffffffu, tid >> 5, 0);
  const int b = cta_role<MODE>();
  if (b >= NCTA) { aux_role(maps, cvec, mail0, zero, b - NCTA, sbase, wid); return; }
  const int jg = b >> 6, mb = jg ? 31 - (b >> 2) : (b >> 2), j = 4 * jg + (b & 3);
  const uint32_t dl = clock32() + 800000000u;
  unsigned* const flags = &mail0->flags[mb * 32];
  const int row0 = mb * 128;

  if (wid >= 8) {
    if (wid == 8) {
      #pragma unroll
      for (int i = 0; i < 8; i++) mbar_init_e(sbase + B_X + 8 * i, 1);
      fence_proxy_async_smem();
      mbar_expect_tx_e(sbase + B_X, 4096);
      bulk_load(sbase + SM_XR, x + (size_t)(row0 + j * 16) * D_, 4096, sbase + B_X);
    } else if (wid == 11) {
      #pragma unroll
      for (int i = 0; i < 12; i++) prefetch_tmap(&maps.x + i);
    } else if (wid == 9) {
      #pragma unroll
      for (uint32_t bar = B_EQ; bar < B_FM; bar += 8) mbar_init_e(sbase + bar, bar < B_FQ ? 8 : bar == B_FQ + 8 || bar == B_FQ + 24 ? 2 : 1);
      fence_proxy_async_smem();
    } else {
      #pragma unroll
      for (uint32_t bar = B_FM; bar < B_END; bar += 8) mbar_init_e(sbase + bar, 1);
      fence_proxy_async_smem();
    }
    bar_sync(0, 384);
    reg_dealloc<40>();
    PROF(92, tid == 256);
    if (wid == 8) {
      uint32_t tnext = clock32();
      #pragma unroll 1
      for (int q = 1; q < 8; q++) {
        wait_until(tnext);
        mbar_expect_tx_e(sbase + B_X + 8 * q, 4096);
        bulk_load(sbase + SM_XR + q * 4096, x + (size_t)(row0 + j * 16 + 2 * q) * D_, 4096, sbase + B_X + 8 * q);
        tnext += X_GAP;
      }
      #pragma unroll 1
      for (int u = 0; u < 16; u++) {
        const int st = u & 3;
        if (u == 1) mbar_wait(sbase + B_X + 56, 0, dl);
        if (u == 2) { mbar_wait(sbase + B_GATE, 0, dl); PROFN(60, lane == 0); }
        if (u == 3) mbar_wait(sbase + B_EQ, 0, dl);
        mbar_wait(sbase + B_EQ + 8 * st, ((u >> 2) & 1) ^ 1, dl);
        const uint32_t slot = sbase + st * QSLOT, fb = sbase + B_FQ + 8 * st;
        mbar_expect_tx_e(fb, u == 0 ? 65536 : u == 15 ? 32768 : 49152);
        if ((u & 1) && (u < MSEP || u == 15)) mbar_arrive_e(fb);
        if (u == 0) tma_load_3d(sbase + SM_X0, &maps.x, fb, 0, mb * 64, 0);
        tma_load_4d<true>(slot + 16384, &maps.wqk, fb, 0, u * 64, j, 0);
        tma_load_4d<true>(slot + 32768, &maps.wvv, fb, 0, u * 64, j, 0);
        if (u < 15) tma_load_3d(slot, &maps.x, fb, u * 64 + 64, mb * 64, 0);
      }
      const unsigned e1 = 1 + ld_relaxed(flags + FO_EPOCH);
      Ring r{0, 1, 0, dl};
      uint32_t slot, fb;
      auto acquire = [&](uint32_t bytes) {
        mbar_wait(sbase + B_EM + 8 * r.st, r.ph, dl);
        slot = sbase + r.st * MSLOT; fb = sbase + B_FM + 8 * r.st;
        mbar_expect_tx_e(fb, bytes);
        ring_next(r);
      };
      #pragma unroll 1
      for (int kt = 0; kt < 16; kt++) {
        if (kt < 5) mbar_wait(sbase + B_EQ + 8 * (kt - (kt >= 2)), 1, dl);
        if ((kt & 7) == 0) { PROF(46, lane == 0 && kt == 8); mbar_wait(sbase + B_FLG + kt, 0, dl); PROF(47, lane == 0 && kt == 8); }
        acquire(32768);
        tma_load_4d<true>(slot + 16384, &maps.wq1, fb, (j + 8) * 64, (kt & 1) * 64 + (kt & 6) * 8, (kt >> 3) * 4, 0);
        tma_load_3d(slot, &maps.hh, fb, (kt & 7) * 64, row0, kt >> 3);
      }
      PROF(82, lane == 0);
      mbar_wait(sbase + B_FLG + 16, 0, dl);
      PROF(83, lane == 0);
      #pragma unroll 1
      for (int kt = 0; kt < 8; kt++) {
        if (kt == 4) {
          acquire(32768);
          tma_load_3d(slot, &maps.x, fb, j * 128, mb * 64, 0);
          tma_load_3d(slot + 16384, &maps.x, fb, j * 128 + 64, mb * 64, 0);
        }
        acquire(32768);
        tma_load_3d<true>(slot + 16384, &maps.wo, fb, 0, kt * 64, 2 * j);
        tma_load_2d(slot, &maps.o, fb, kt * 64, row0);
      }
      acquire(16384);
      tma_load_3d<true>(slot + 16384, &maps.wo, fb, 0, (8 + j) * 64, 2 * j);
      auto deferred = [&](const CUtensorMap* map, const unsigned* flag, Ring ra, int n, int col0, int step) {
        uint32_t dst = sbase + ra.st * MSLOT, bar = sbase + B_FM + 8 * ra.st, col = col0 + other_slot(0, j) * step;
        asm volatile("" : "+r"(dst), "+r"(bar), "+r"(col));
        wait_flag(flag, e1 * NCTA, dl);
        tma_load_2d(dst, map, bar, col, row0);
        #pragma unroll 1
        for (int i = 1; i < n; i++) { ring_next(ra); tma_load_2d(sbase + ra.st * MSLOT, map, sbase + B_FM + 8 * ra.st, col0 + other_slot(i, j) * step, row0); }
      };
      {
        const Ring ra = r;
        #pragma unroll 1
        for (int i = 0; i < 7; i++) {
          const int kt = 8 + other_slot(i, j);
          acquire(32768);
          tma_load_3d<true>(slot + 16384, &maps.wo, fb, 0, kt * 64, 2 * j);
          if (i == WPRE - 1) { deferred(&maps.o, &mail0->flags[FL_O], ra, WPRE, 512, 64); PROFN(61, lane == 0); }
          if (i >= WPRE) tma_load_2d(slot, &maps.o, fb, kt * 64, row0);
        }
      }
      #pragma unroll 1
      for (int t = 0; t < 2; t++) {
        acquire(32768);
        tma_load_2d<true>(slot, &maps.w1, fb, j * 64, (2 * j + t) * 64);
        tma_load_2d<true>(slot + 8192, &maps.w3, fb, j * 64, (2 * j + t) * 64);
        tma_load_2d<true>(slot + 16384, &maps.w1, fb, (8 + j) * 64, (2 * j + t) * 64);
        tma_load_2d<true>(slot + 24576, &maps.w3, fb, (8 + j) * 64, (2 * j + t) * 64);
      }
      {
        const Ring ra = r;
        #pragma unroll 1
        for (int i = 0; i < GPRE; i++) {
          const int kt = 2 * other_slot(i, j);
          acquire(32768);
          tma_load_2d<true>(slot + 16384, &maps.w1, fb, j * 64, kt * 64);
          tma_load_2d<true>(slot + 24576, &maps.w3, fb, j * 64, kt * 64);
        }
        deferred(&maps.h2, &mail0->flags[FL_H2], ra, GPRE, 0, 128);
        PROFN(62, lane == 0);
        mbar_arrive_e(sbase + B_H2A);
      }
      #pragma unroll 1
      for (int gt = 0; gt < 7; gt++) {
        const int ncol = (8 * gt + j) * 64;
        #pragma unroll 1
        for (int i = (gt == 0 ? GPRE : 0); i < (gt < 2 ? 14 : 16); i++) {
          const int kt = gt >= 2 ? i : i < 7 ? 2 * other_slot(i, j) : 2 * other_slot(i - 7, j) + 1;
          if (gt == 0 && i == 7) mbar_wait(sbase + B_FLG + 32, 0, dl);
          acquire(32768);
          tma_load_2d<true>(slot + 16384, &maps.w1, fb, ncol, kt * 64);
          tma_load_2d<true>(slot + 24576, &maps.w3, fb, ncol, kt * 64);
          tma_load_2d(slot, &maps.h2, fb, kt * 64, row0);
        }
      }
      #pragma unroll 1
      for (int kt = 0; kt < 56; kt++) {
        if ((kt & 7) == 0) mbar_wait(sbase + B_FLG + 40 + kt, 0, dl);
        acquire(32768);
        tma_load_3d(slot + 16384, &maps.w2, fb, 0, kt * 64, 2 * j);
        tma_load_3d(slot, &maps.hh, fb, (kt & 7) * 64, row0, kt >> 3);
      }
    } else {
      const unsigned e1 = 1 + ld_relaxed(wid == 9 ? flags + FO_EPOCH : &mail0->flags[FL_EPOCH]), par = e1 & 1;
      if (wid == 9) {
        #pragma unroll 1
        for (int n = 0; n < 12; n++) {
          if (n == 4) {
            mbar_wait(sbase + B_STH, 0, dl);
            tma_store_2d(&maps.h2, sbase + SM_STG, j * 128, row0);
            bulk_commit();
            bulk_wait0();
            red_add_e(&mail0->flags[FL_H2], 1);
            PROF(84, lane == 0);
            mbar_wait(sbase + B_H2A, 0, dl);
          }
          if (n >= 1 && n <= 4) mbar_wait(sbase + B_STREQ, n & 1, dl); else mbar_sleep(sbase + B_STREQ, n & 1, dl);
          if (n == 0) fence_proxy_async_smem();
          if (n == 2 || n == 3) tma_store_2d(&maps.o, sbase + SM_STG, (j + 8 * (n - 2)) * 64, row0);
          else if (n == 4) tma_store_2d(&maps.h2, sbase + SM_STG + 16384, j * 128 + 64, row0);
          else tma_store_3d(&maps.hh, sbase + SM_STG + (n == 1 ? 16384 : 0), j * 64, row0, n < 2 ? n : n - 5);
          bulk_commit();
          bulk_wait0();
          red_add_e(n == 3 ? &mail0->flags[FL_O] : flags + FO_CNT + n, 1);
          mbar_arrive_e(sbase + B_STFREE);
          PROFN(70 + n, lane == 0 && n > 0); PROF(85, lane == 0 && n == 0);
          if (n != 3) { wait_flag(flags + FO_CNT + n, e1 * 8, dl); mbar_arrive_e(sbase + B_FLG + 8 * n); }
        }
      } else {
        mbar_wait(sbase + B_X + 24, 0, dl);
        const float* const mail = &mail0->mod[(b & 7) * 6 * D_ + lane * 4];
        if (wid == 10) {
          #pragma unroll 1
          for (int p = 0; p < 8; p++) {
            if (p >= 2) mbar_wait(p == 2 ? q_empty(0, sbase) : q_empty(2 * p - 5, sbase), p == 2 ? 0 : ((2 * p - 5) >> 2) & 1, dl);
            gather_table(mail + p * 128, sbase + SM_MODT + (p & 3) * 512 + ((lane * 16) ^ ((j >> 1) << 6)), 2 * p - 1 < MSEP ? sbase + B_MOD + 8 * p : sbase + B_FQ + 8 * ((2 * p - 1) & 3), par, dl);
            PROF(63 + p, lane == 0 && p < 7);
          }
          const uint32_t vdst = sbase + SM_VEC + (lane >> 3) * 64 + (lane & 3) * 16 + ((lane >> 2) & 1) * 8;
          #pragma unroll 1
          for (int v = 0; v < 2; v++) {
            mbar_sleep(sbase + B_FLG + 16 + 24 * v, 0, dl);
            uint4 m[3];
            while (true) {
              #pragma unroll
              for (int e = 0; e < 3; e++) m[e] = ld_rlx_v4(mail + (2 + v + e) * 1024 + j * 128);
              if (poll_done(((bad4(m[0], par) | bad4(m[1], par) | bad4(m[2], par)) & 1) == 0, dl)) break;
              __nanosleep(200);
            }
            #pragma unroll
            for (int e = 0; e < 3; e++) sts64(vdst + (v + e) * 256, hi_halves(m[e].x, m[e].y), hi_halves(m[e].z, m[e].w));
            mbar_arrive_e(sbase + B_VEC + 8 * v);
            PROF(70, lane == 0 && v == 0);
          }
        } else {
          mbar_wait(sbase + B_LN, 0, dl);
          red_add_e(&mail0->flags[FL_LN1], 1);
          wait_flag(&mail0->flags[FL_LN1], e1 * NCTA, dl);
          mbar_arrive_e(sbase + B_GATE);
          PROF(41, lane == 0);
        }
      }
    }
  } else {
    const int wg = wid >> 2, warp = wid & 3;
    const int g = lane >> 2, qd = lane & 3;
    bulk_prefetch(wmod + (size_t)(b * 8 + wid) * (6 * D_), PF_BYTES);
    bulk_prefetch(wmod + (size_t)(b * 8 + wid) * (6 * D_) + D_, PF_BYTES);
    bar_sync(0, 384);
    bulk_prefetch(wmod + (size_t)(b * 8 + wid) * (6 * D_) + PF_BYTES / 2, PF_BYTES);
    bulk_prefetch(wmod + (size_t)(b * 8 + wid) * (6 * D_) + PF_BYTES / 2 + D_, PF_BYTES);
    const unsigned e1 = 1 + ld_relaxed(flags + FO_EPOCH), par = e1 & 1;
    reg_alloc<232>();
    PROF(1, tid == 0);
    const uint32_t wgoff = wg * 8192;
    const uint32_t frag0 = wid * 2048 + (lane & 15) * 128 + (((lane >> 4) ^ (lane & 7)) << 4);
    const uint32_t slab = sbase + SM_STG + wid * 2048;

    LnRow ln;
    {
      uint2* const lmail = &mail0->ln1[(mb * 8 + (wid & 1) * 4 + (j >> 1)) * 16 + (j & 1) * 8 + (wid >> 1) + (lane & 1) * 4];
      st_rlx_v2(lmail, par ^ 1, par ^ 1, lane < 2);
      float s[2][2] = {{0.f, 0.f}, {0.f, 0.f}}, q2[2][2] = {{0.f, 0.f}, {0.f, 0.f}};
      #pragma unroll
      for (int c = 0; c < 8; c++) {
        if (c == 4) asm volatile("" : "+f"(s[0][0]), "+f"(s[0][1]), "+f"(q2[0][0]), "+f"(q2[0][1]));
        if ((c & 3) == 0) mbar_wait(sbase + B_X + 8 * (c + (wid >> 1)), 0, dl);
        if (c == 4) { PROF(3, tid == 224); PROF(93, tid == 0); }
        const uint4 v = lds128(sbase + SM_XR + (c >> 2) * 16384 + wid * 2048 + (c & 3) * 512 + lane * 16);
        const uint32_t vv[4] = {v.x, v.y, v.z, v.w};
        #pragma unroll
        for (int e = 0; e < 4; e++) {
          const float lo = bf_lo(vv[e]), hi = bf_hi(vv[e]);
          s[c >> 2][0] += lo; s[c >> 2][1] += hi; q2[c >> 2][0] = fmaf(lo, lo, q2[c >> 2][0]); q2[c >> 2][1] = fmaf(hi, hi, q2[c >> 2][1]);
        }
      }
      const bool odd = lane & 1;
      float sm = (s[0][0] + s[0][1]), so = (s[1][0] + s[1][1]), qm = (q2[0][0] + q2[0][1]), qo = (q2[1][0] + q2[1][1]);
      { const float a = odd ? so : sm, c = odd ? qo : qm;
        sm = a + __shfl_xor_sync(0xffffffffu, odd ? sm : so, 1); qm = c + __shfl_xor_sync(0xffffffffu, odd ? qm : qo, 1); }
      #pragma unroll
      for (int o = 2; o < 32; o <<= 1) { sm += __shfl_xor_sync(0xffffffffu, sm, o); qm += __shfl_xor_sync(0xffffffffu, qm, o); }
      sm *= (1.f / D_);
      ln_row(ln, 0, sm, fast_rsqrt(fmaxf(qm * (1.f / D_) - sm * sm, 0.f) + 1e-5f));
      st_rlx_v2(lmail, (ln.rs[0] << 16) | par, (ln.nb[0] << 16) | par, lane < 2);
      mbar_arrive_e(sbase + B_LN);
      PROF(4, tid == 224);
    }

    uint4* const halo_out = mail0->halo[par] + ((mb * 16 + j) * 2 + wg) * 128 + lane;
    const uint4* const halo_in = halo_out - 16 * 256;
    const uint32_t xch = sbase + SM_XCH + (tid >> 5) * 2048 + lane * 16;
    const bool noprev = mb == 0 && warp == 0, remote = mb > 0 && warp == 0;
    float a0[64], a1[64];
    uint32_t x2[32];
    Ring r{zero, 0, 0, dl};
    Frag8 qA, qB, kA, kB, vA, vB, wA, wB;
    {
      float acc[128];
      uint32_t A0[16], A1[16];
      undef_regs(acc);
      const uint32_t tab = sbase + SM_MODT + qd * 16;
      uint4 p[4];
      const uint32_t rot = j >> 1;
      Frag4 fq;
      #pragma unroll
      for (int q = 0; q < 4; q++) fq.o[q] = frag0 ^ ((q ^ rot) << 5);
      mbar_wait(sbase + B_LN, 0, dl);
      const uint2* const lin = &mail0->ln1[(mb * 8 + wid) * 16 + g];
      uint2 v0, v1;
      q_wait(0, sbase, dl);
      #pragma unroll
      for (int kk = 0; kk < 4; kk++) ldmatrix_x4(sbase + SM_X0 + fq.o[kk], A0[4 * kk], A0[4 * kk + 1], A0[4 * kk + 2], A0[4 * kk + 3]);
      do { v0 = ld_rlx_v2(lin); v1 = ld_rlx_v2(lin + 8); } while (!poll_done(((bad2(v0.x, v0.y, par) | bad2(v1.x, v1.y, par)) & 1) == 0, dl));
      ln.rs[0] = hi_halves(v0.x, v0.x); ln.nb[0] = hi_halves(v0.y, v0.y); ln.rs[1] = hi_halves(v1.x, v1.x); ln.nb[1] = hi_halves(v1.y, v1.y);
      mbar_wait(sbase + B_MOD, 0, dl);
      #pragma unroll
      for (int kk = 0; kk < 4; kk++) p[kk] = lds128(tab + kk * 64);
      PROF(5, tid == 0);
      q_step_rs<true>(acc, A0, A1, p, 0, sbase, fq, tab, ln, rot, !(j & 1), true, dl, wg, zero);
      #pragma unroll
      for (int u = 1; u < 15; u += 2) {
        q_step_rs<true>(acc, A1, A0, p, u, sbase, fq, tab, ln, rot, j & 1, false, dl, wg, zero);
        q_step_rs<true>(acc, A0, A1, p, u + 1, sbase, fq, tab, ln, rot, !(j & 1), false, dl, wg, zero);
        if (u == 7) mbar_arrive_e(sbase + B_STREQ);
      }
      q_step_rs<false>(acc, A1, A0, p, 15, sbase, fq, tab, ln, rot, j & 1, false, dl, wg, zero);
      PROF(7, tid == 0);
      mbar_wait(sbase + B_STFREE, 0, dl);
      request_store(sbase + B_STREQ);
      wgmma_wait<0>();
      undef_regs(a0);
      { const uint32_t slot = m_wait(sbase, r); mma_step(a0, slot + wgoff, slot + 16384, true, q_empty(15, sbase)); m_next(r); }
      fence_regs(acc);
      PROF(8, tid == 0);
      sched_fence(zero);
      pack_half(vB, acc, 64, 1); transpose8(vB);
      m_step(a0, sbase, wgoff, r);
      sched_fence(zero);
      pack_half(kB, acc, 32, 1);
      attn_send(vB, 1, xch - 16384, warp, halo_out, mb < 15); attn_send(kB, 0, xch - 16384, warp, halo_out, mb < 15);
      m_step(a0, sbase, wgoff, r);
      sched_fence(zero);
      pack_half(qA, acc, 0, 0); pack_half(qB, acc, 0, 1); pack_half(kA, acc, 32, 0); pack_half(wB, acc, 96, 1); pack_half(wA, acc, 96, 0);
      m_step(a0, sbase, wgoff, r);
      sched_fence(zero);
      pack_half(vA, acc, 64, 0); transpose8(vA);
    }
    uint4 wP[2];
    Frag4 frag;
    #pragma unroll
    for (int q = 0; q < 4; q++) frag.o[q] = frag0 ^ (q << 5);
    {
      m_step(a0, sbase, wgoff, r);
      uint4 pv[4];
      attn_recv<4>(pv, 0, xch - 16384, wg, warp, halo_in, mb > 0);
      m_step(a0, sbase, wgoff, r);
      mbar_wait(sbase + B_STFREE, 1, dl);
      transpose8(wB);
      m_step(a0, sbase, wgoff, r);
      attn_check<4>(pv, 0, remote, halo_in, dl);
      wgmma_wait<0>();
      PROF(9, tid == 0);
      float o[2][5][4];
      sched_fence(zero);
      attn_core<0>(qA, qB, kA, kB, vA, vB, pv, pv + 2, noprev, lane, o, Nop());
      attn_store(o, 0, sbase, frag);
      attn_store(o, 1, sbase, frag);
      request_store(sbase + B_STREQ);
      bar_sync(NB_CONS, 256);
      PROF(10, tid == 0);
      m_step(a0, sbase, wgoff, r);
      sched_fence(zero);
      attn_send(wB, 1, xch, warp, halo_out + 8 * 256, mb < 15);
      m_step(a0, sbase, wgoff, r);
      sched_fence(zero);
      transpose8(wA);
      #pragma unroll 1
      for (int i = 9; i < 15; i++) m_step(a0, sbase, wgoff, r);
      attn_recv<2>(wP, 2, xch, wg, warp, halo_in + 8 * 256, mb > 0);
      m_step(a0, sbase, wgoff, r);
    }
    {
      undef_regs(a1);
      {
        const uint32_t slot = m_wait(sbase, r);
        mma_step(a1, slot + wgoff, slot + 16384, true, m_prev(sbase, r), [&] {
          fence_regs(a0);
          pack_half(kB, a0, 32, 1);
          attn_send(kB, 0, xch, warp, halo_out + 8 * 256, mb < 15);
        });
        m_next(r);
      }
      PROF(14, tid == 0);
      sched_fence(zero);
      pack_half(kA, a0, 32, 0); pack_half(qA, a0, 0, 0); pack_half(qB, a0, 0, 1);
      m_step(a1, sbase, wgoff, r);
      attn_check<2>(wP, 2, remote, halo_in + 8 * 256, dl);
      uint4 kP[2];
      attn_recv<2>(kP, 0, xch, wg, warp, halo_in + 8 * 256, mb > 0);
      m_step(a1, sbase, wgoff, r);
      if (ASPLIT == 0) attn_check<2>(kP, 0, remote, halo_in + 8 * 256, dl);
      wgmma_wait<0>();
      PROF(15, tid == 0);
      float o[2][5][4];
      mbar_wait(sbase + B_STFREE, 0, dl);
      attn_core<ASPLIT>(qA, qB, kA, kB, wA, wB, kP, wP, noprev, lane, o, [&] { attn_check<2>(kP, 0, remote, halo_in + 8 * 256, dl); });
      attn_store(o, 0, sbase, frag);
      attn_store(o, 1, sbase, frag);
      request_store(sbase + B_STREQ);
      bar_sync(NB_CONS, 256);
      PROF(16, tid == 0);
      auto residual = [&] {
        const uint32_t xs = m_wait(sbase, r), xe = sbase + B_EM + 8 * r.st;
        ring_next(r);
        #pragma unroll
        for (int t = 0; t < 2; t++) {
          #pragma unroll
          for (int jj = 4 * t; jj < 4 * t + 4; jj++) ldmatrix_x4(xs + t * 16384 + frag.o[jj & 3], x2[4 * jj], x2[4 * jj + 1], x2[4 * jj + 2], x2[4 * jj + 3]);
          if (t == 1) {
            uint32_t dep = 0;
            #pragma unroll
            for (int jj = 0; jj < 8; jj++) dep |= x2[4 * jj];
            mbar_arrive_e(xe + (dep & zero));
          }
          m_step(a1, sbase, wgoff, r);
        }
      };
      m_step(a1, sbase, wgoff, r);
      residual();
      #pragma unroll 1
      for (int i = 6; i < 8; i++) m_step(a1, sbase, wgoff, r);
      mma_step(a1, sbase + SM_STG + wgoff, m_wait(sbase, r) + 16384, false, m_prev(sbase, r));
      m_next(r);
      PROF(17, tid == 0);
      uint4* const sm = mail0->st2[par] + (mb * 8 + wid) * 64 + g;
      st_rlx_v4(sm + j * 8, 0, 0, 0, 0, qd == (g >> 1));
      #pragma unroll 1
      for (int i = 0; i < 7; i++) { m_step(a1, sbase, wgoff, r); PROF(42, tid == 0 && i == 0); }
      PROF(45, tid == 0);
      mbar_wait(sbase + B_VEC, 0, dl);
      mbar_wait(sbase + B_STFREE, 1, dl);
      const uint32_t vec = sbase + SM_VEC + qd * 16;
      uint4 ga[4];
      #pragma unroll
      for (int q = 0; q < 4; q++) ga[q] = lds128(vec + q * 64);
      wgmma_wait<0>();
      mbar_arrive_e(m_prev(sbase, r));
      fence_regs(a1);
      PROF(18, tid == 0);
      float gl[4] = {0.f, 0.f, 0.f, 0.f}, gh[4] = {0.f, 0.f, 0.f, 0.f};
      #pragma unroll
      for (int jj = 0; jj < 8; jj++) {
        uint32_t* v = &x2[4 * jj];
        const uint32_t wl = (jj & 1) ? ga[jj >> 1].z : ga[jj >> 1].x, wh = (jj & 1) ? ga[jj >> 1].w : ga[jj >> 1].y;
        #pragma unroll
        for (int e = 0; e < 4; e++) v[e] = fma_bf2(e & 2 ? wh : wl, pack_bf16(a1[8 * jj + 2 * e], a1[8 * jj + 2 * e + 1]), v[e]);
        mma16(gl, v[0], 0x3F803F80u, v[2], 0x3F803F80u, v[0], v[2]);
        mma16(gh, v[1], 0x3F803F80u, v[3], 0x3F803F80u, v[1], v[3]);
      }
      st_nonzero_v4(sm + j * 8, __float_as_uint(g & 1 ? gl[3] : gl[2]), __float_as_uint(g & 1 ? gl[1] : gl[0]),
                __float_as_uint(g & 1 ? gh[3] : gh[2]), __float_as_uint(g & 1 ? gh[1] : gh[0]), qd == (g >> 1));
      float s[2], q2[2];
      PROF(19, tid == 0);
      uint4 sb[4], cb[4];
      #pragma unroll
      for (int q = 0; q < 4; q++) { sb[q] = lds128(vec + 256 + q * 64); cb[q] = lds128(vec + 512 + q * 64); }
      uint4 p0, p1;
      while (true) {
        p0 = ld_rlx_v4(sm + qd * 16); p1 = ld_rlx_v4(sm + qd * 16 + 8);
        if (poll_done(min(min4(p0), min4(p1)) != 0, dl)) break;
      }
      PROF(20, tid == 0);
      s[0] = __uint_as_float(p0.x) + __uint_as_float(p1.x); q2[0] = __uint_as_float(p0.y) + __uint_as_float(p1.y);
      s[1] = __uint_as_float(p0.z) + __uint_as_float(p1.z); q2[1] = __uint_as_float(p0.w) + __uint_as_float(p1.w);
      #pragma unroll
      for (int o2 = 1; o2 <= 2; o2 <<= 1)
        #pragma unroll
        for (int h = 0; h < 2; h++) { s[h] += __shfl_xor_sync(0xffffffffu, s[h], o2); q2[h] += __shfl_xor_sync(0xffffffffu, q2[h], o2); }
      #pragma unroll
      for (int h = 0; h < 2; h++) {
        const float m = s[h] * (1.f / D_);
        ln_row(ln, h, m, fast_rsqrt(fmaxf(q2[h] * (1.f / D_) - m * m, 0.f) + 1e-5f));
      }
      #pragma unroll
      for (int jj = 0; jj < 8; jj++) {
        const uint32_t cl = (jj & 1) ? cb[jj >> 1].z : cb[jj >> 1].x, ch = (jj & 1) ? cb[jj >> 1].w : cb[jj >> 1].y;
        const uint32_t sl = (jj & 1) ? sb[jj >> 1].z : sb[jj >> 1].x, sh = (jj & 1) ? sb[jj >> 1].w : sb[jj >> 1].y;
        stmatrix_x4(sbase + SM_STG + (jj >> 2) * 16384 + frag.o[jj & 3], ln_mod(x2[4 * jj], ln, 0, cl, sl), ln_mod(x2[4 * jj + 1], ln, 1, cl, sl),
                    ln_mod(x2[4 * jj + 2], ln, 0, ch, sh), ln_mod(x2[4 * jj + 3], ln, 1, ch, sh));
        if (jj == 3) { request_store(sbase + B_STH); sched_fence(zero); }
      }
      request_store(sbase + B_STREQ);
      bar_sync(NB_WG + wg, 128);
      PROF(21, tid == 0);
    }

    undef_regs(a0);
    #pragma unroll
    for (int t = 0; t < 2; t++) {
      const uint32_t slot = m_wait(sbase, r);
      if (t == 0) mma_step<false>(a0, sbase + SM_STG + wgoff, slot, true, 0);
      else mma_step(a0, sbase + SM_STG + 16384 + wgoff, slot, false, m_prev(sbase, r));
      mma_step<false>(a1, sbase + SM_STG + t * 16384 + wgoff, slot + 16384, t == 0, 0);
      m_next(r);
    }
    PROF(22, tid == 0);
    #pragma unroll 1
    for (int t = 0; t < 7; t += 2) {
      g_switch(a1, a0, t == 0 ? 14 : 11, t > 0, 5 + t, sbase, wgoff, frag, r);
      if (t == 6) break;
      g_switch(a0, a1, t == 0 ? 9 : 11, true, 6 + t, sbase, wgoff, frag, r);
    }
    #pragma unroll 1
    for (int i = 5; i < 56 - DTAIL; i++) m_step(a1, sbase, wgoff, r);
    if (DTAIL) {
      if (wg == 1) { wgmma_wait<0>(); mbar_arrive_e(m_prev(sbase, r)); bar_sync(NB_ORD, 256); }
      #pragma unroll
      for (int i = 0; i < DTAIL; i++) {
        const uint32_t slot = m_wait(sbase, r);
        const uint32_t alo = ((slot + wgoff) >> 4) + (1u << 16), blo = ((slot + 16384) >> 4) + (512u << 16);
        wgmma_fence();
        #pragma unroll
        for (int k = 0; k < 4; k++) wgmma_m64n128k16_ss(a1, desc_from_lo(alo + k * 2), desc_from_lo(blo + k * 128), true);
        wgmma_commit();
        ring_next(r);
      }
      if (wg == 0) bar_arrive(NB_ORD, 256);
    }
    {
      mbar_wait(sbase + B_STFREE, 1, dl);
      mbar_wait(sbase + B_VEC + 8, 0, dl);
      uint4 gb[4];
      #pragma unroll
      for (int q = 0; q < 4; q++) gb[q] = lds128(sbase + SM_VEC + 768 + qd * 16 + q * 64);
      wgmma_wait<0>();
      fence_regs(a1);
      PROF(50, tid == 128);
      #pragma unroll
      for (int t = 0; t < 2; t++) {
        #pragma unroll
        for (int jj = 4 * t; jj < 4 * t + 4; jj++) {
          const uint32_t gl = (jj & 1) ? gb[jj >> 1].z : gb[jj >> 1].x, gh = (jj & 1) ? gb[jj >> 1].w : gb[jj >> 1].y;
          const int i = 8 * jj;
          stmatrix_x4(sbase + SM_STG + t * 16384 + frag.o[jj & 3],
                      fma_bf2(gl, pack_bf16(a1[i], a1[i + 1]), x2[4 * jj]), fma_bf2(gl, pack_bf16(a1[i + 2], a1[i + 3]), x2[4 * jj + 1]),
                      fma_bf2(gh, pack_bf16(a1[i + 4], a1[i + 5]), x2[4 * jj + 2]), fma_bf2(gh, pack_bf16(a1[i + 6], a1[i + 7]), x2[4 * jj + 3]));
        }
        fence_proxy_async_smem();
        tma_store_3d(&maps.out, slab + t * 16384, j * 128 + t * 64, mb * 64 + warp * 16, wg);
      }
      bulk_commit();
      st_rlx(tid == 0 ? flags + FO_EPOCH : &mail0->flags[FL_EPOCH], e1, j == 0 && (tid == 0 || (tid == 1 && mb == 0)));
      bulk_wait_read0();
      PROFN(51, tid == 128);
    }
  }
}

typedef CUresult (*PFN_encodeTiled)(CUtensorMap*, CUtensorMapDataType, cuuint32_t, void*, const cuuint64_t*, const cuuint64_t*,
                                    const cuuint32_t*, const cuuint32_t*, CUtensorMapInterleave, CUtensorMapSwizzle,
                                    CUtensorMapL2promotion, CUtensorMapFloatOOBfill);

void encode(PFN_encodeTiled fn, CUtensorMap* m, const void* ptr, int rank, const cuuint64_t* dims, const cuuint64_t* strides,
            const cuuint32_t* box) {
  const cuuint32_t es[5] = {1, 1, 1, 1, 1};
  fn(m, CU_TENSOR_MAP_DATA_TYPE_BFLOAT16, rank, const_cast<void*>(ptr), dims, strides, box, es, CU_TENSOR_MAP_INTERLEAVE_NONE,
     CU_TENSOR_MAP_SWIZZLE_128B, CU_TENSOR_MAP_L2_PROMOTION_L2_256B, CU_TENSOR_MAP_FLOAT_OOB_FILL_NONE);
}
void map2d(PFN_encodeTiled fn, CUtensorMap* m, const void* ptr, int cols, int rows, int boxrows) {
  const cuuint64_t dims[2] = {(cuuint64_t)cols, (cuuint64_t)rows}, strides[1] = {(cuuint64_t)cols * 2};
  const cuuint32_t box[2] = {64, (cuuint32_t)boxrows};
  encode(fn, m, ptr, 2, dims, strides, box);
}
void map_w2chunk(PFN_encodeTiled fn, CUtensorMap* m, const void* ptr, int cols, int rows) {
  const cuuint64_t dims[3] = {64, (cuuint64_t)rows, (cuuint64_t)cols / 64}, strides[2] = {(cuuint64_t)cols * 2, 128};
  const cuuint32_t box[3] = {64, 64, 2};
  encode(fn, m, ptr, 3, dims, strides, box);
}
void map_parity(PFN_encodeTiled fn, CUtensorMap* m, const void* ptr, int boxpairs, int boxpar) {
  const cuuint64_t dims[3] = {D_, S_ / 2, 2}, strides[2] = {D_ * 4, D_ * 2};
  const cuuint32_t box[3] = {64, (cuuint32_t)boxpairs, (cuuint32_t)boxpar};
  encode(fn, m, ptr, 3, dims, strides, box);
}

}

extern "C" void kernel_launch(void* const* d_in, const int* in_sizes, int n_in, void* d_out, int out_size) {
  (void)in_sizes; (void)n_in; (void)out_size;
  const bf16* x = (const bf16*)d_in[0];
  const bf16* wqkv = (const bf16*)d_in[1];
  const bf16* wo = (const bf16*)d_in[2];
  const bf16* w1 = (const bf16*)d_in[4];
  const bf16* w3 = (const bf16*)d_in[5];
  const bf16* w2 = (const bf16*)d_in[6];
  const bf16* cvec = (const bf16*)d_in[7];
  const bf16* w_mod = (const bf16*)d_in[8];

  static PFN_encodeTiled fn = nullptr;
  static Maps maps;
  static const void* cached[8] = {};
  static int sms = 0;
  static void* mail = nullptr;
  if (!fn) {
    void* p = nullptr; cudaDriverEntryPointQueryResult st;
    cudaGetDriverEntryPoint("cuTensorMapEncodeTiled", &p, cudaEnableDefault, &st);
    fn = (PFN_encodeTiled)p;
    cudaFuncSetAttribute(fused_block_kernel<0>, cudaFuncAttributeMaxDynamicSharedMemorySize, SM_TOTAL + SM_PROF);
    cudaFuncSetAttribute(fused_block_kernel<1>, cudaFuncAttributeMaxDynamicSharedMemorySize, SM_TOTAL + SM_PROF);
    cudaFuncSetAttribute(fused_block_kernel<2>, cudaFuncAttributeMaxDynamicSharedMemorySize, SM_TOTAL + SM_PROF);
    cudaGetSymbolAddress(&mail, g_mail);
    int dev = 0;
    cudaGetDevice(&dev);
    cudaDeviceGetAttribute(&sms, cudaDevAttrMultiProcessorCount, dev);
  }
  const void* cur[8] = {x, wqkv, wo, w1, w3, w2, d_out, w_mod};
  bool same = true;
  for (int i = 0; i < 8; i++) same = same && cached[i] == cur[i];
  if (!same) {
    void *o, *h2, *hh;
    cudaGetSymbolAddress(&hh, g_hh); cudaGetSymbolAddress(&o, g_o);
    h2 = o;
    map_parity(fn, &maps.x, x, 64, 2); map_parity(fn, &maps.out, d_out, 16, 1);
    map2d(fn, &maps.o, o, D_, S_, 128); map2d(fn, &maps.h2, h2, D_, S_, 128);
    {
      const cuuint64_t dims[3] = {512, (cuuint64_t)S_, 7}, strides[2] = {1024, (cuuint64_t)S_ * 1024};
      const cuuint32_t box[3] = {64, 128, 1};
      encode(fn, &maps.hh, hh, 3, dims, strides, box);
    }
    {
      const cuuint64_t dims[4] = {64, 1024, 16, 2}, strides[3] = {3072 * 2, 128, 2048};
      const cuuint64_t dimv[4] = {64, 1024, 8, 2}, stridev[3] = {3072 * 2, 128, 1024};
      const cuuint32_t box[4] = {64, 64, 1, 2};
      encode(fn, &maps.wqk, wqkv, 4, dims, strides, box);
      encode(fn, &maps.wvv, wqkv + 2048, 4, dimv, stridev, box);
      const cuuint64_t dim1[4] = {1024, 128, 8, 2}, stride1[3] = {3072 * 2, 128 * 3072 * 2, 2048};
      const cuuint32_t box1[4] = {64, 16, 4, 2};
      encode(fn, &maps.wq1, wqkv, 4, dim1, stride1, box1);
    }
    map_w2chunk(fn, &maps.wo, wo, D_, D_); map_w2chunk(fn, &maps.w2, w2, D_, F_);
    map2d(fn, &maps.w1, w1, F_, D_, 64); map2d(fn, &maps.w3, w3, F_, D_, 64);
    map2d(fn, &maps.wmod, w_mod, 6 * D_, D_, 256);
    for (int i = 0; i < 8; i++) cached[i] = cur[i];
  }
  if (sms == NCTA + NAUX) {
    fused_block_kernel<0><<<NCTA + NAUX, 384, SM_TOTAL + SM_PROF>>>(x, cvec, w_mod, (Mail*)mail, 0, maps);
  } else {
    fused_block_kernel<1><<<NAUX, 384, SM_TOTAL + SM_PROF>>>(x, cvec, w_mod, (Mail*)mail, 0, maps);
    fused_block_kernel<2><<<NCTA, 384, SM_TOTAL + SM_PROF>>>(x, cvec, w_mod, (Mail*)mail, 0, maps);
  }
}
```

```cpp
#include <cuda.h>
#include <cuda_runtime.h>
#include <cuda_bf16.h>
#include <stdint.h>

namespace {

typedef __nv_bfloat16 bf16;

constexpr int S_ = 2048, D_ = 1024, F_ = 3584;
constexpr int NCTA = 128, NAUX = 4;

__device__ __align__(1024) bf16 g_o[S_ * D_];
__device__ __align__(1024) bf16 g_hh[S_ * F_];
constexpr int FO_EPOCH = 0, FO_CNT = 1;
constexpr int FL_EPOCH = 16 * 32, FL_LN1 = FL_EPOCH + 2, FL_H2 = FL_EPOCH + 3, FL_O = FL_EPOCH + 4;
struct Mail {
  unsigned flags[32 * 32];
  float mod[8 * 6 * D_];
  uint2 ln1[16 * 8 * 16];
  uint4 halo[2][16 * 16 * 2 * 4 * 32];
  uint4 st2[2][16 * 8 * 8 * 8];
};
__device__ __align__(1024) Mail g_mail;

template <int mode>
__device__ __forceinline__ int cta_role() {
  if (mode) return mode == 1 ? NCTA + (blockIdx.x & 3) : blockIdx.x & 127;
  uint32_t sm;
  asm("mov.u32 %0, %%smid;" : "=r"(sm));
  sm = (sm & ~3u) == 12 ? sm + 108 : (sm & ~3u) == 120 ? sm - 108 : sm;
  const int t = sm >> 1;
  int r;
  if (t < 32) r = (t & 7) * 16 + (t >> 3) * 2 + (sm & 1);
  else if (t < 60) r = (1 + (t - 32) % 7) * 16 + 8 + ((t - 32) / 7) * 2 + (sm & 1);
  else if (t < 62) r = NCTA + sm - 120;
  else r = sm - 116;
  return r;
}
#define PROF(slot, on) do {} while (0)
#define PROFN(slot, on) do {} while (0)
#define PROF_OUT(role, t) do {} while (0)
constexpr uint32_t SM_PROF = 0;

__device__ __forceinline__ uint32_t smem_u32(const void* p) { return (uint32_t)__cvta_generic_to_shared(p); }
#define ELECT "{\n.reg .pred p;\nelect.sync _|p, 0xffffffff;\n@p "
__device__ __forceinline__ void mbar_init_e(uint32_t bar, uint32_t count) {
  asm volatile(ELECT "mbarrier.init.shared::cta.b64 [%0], %1;\n}" :: "r"(bar), "r"(count) : "memory");
}
__device__ __forceinline__ void mbar_expect_tx_e(uint32_t bar, uint32_t bytes) {
  asm volatile(ELECT "mbarrier.arrive.expect_tx.shared::cta.b64 _, [%0], %1;\n}" :: "r"(bar), "r"(bytes) : "memory");
}
__device__ __forceinline__ void mbar_arrive_e(uint32_t bar) {
  asm volatile(ELECT "mbarrier.arrive.shared::cta.b64 _, [%0];\n}" :: "r"(bar) : "memory");
}
__device__ __forceinline__ uint32_t clock32() { uint32_t t; asm volatile("mov.u32 %0, %%clock;" : "=r"(t)); return t; }
__device__ __forceinline__ void mbar_wait(uint32_t bar, uint32_t parity, uint32_t dl) {
  asm volatile("{\n.reg .pred p, q;\n.reg .b32 t;\n"
               "mbarrier.try_wait.parity.shared::cta.b64 p, [%0], %1;\n"
               "@p bra LAB_DONE;\n"
               "LAB_WAIT:\n"
               "mbarrier.try_wait.parity.shared::cta.b64 p, [%0], %1;\n"
               "mov.u32 t, %%clock;\n"
               "sub.s32 t, t, %2;\n"
               "setp.lt.and.s32 q, t, 0, !p;\n"
               "@q bra LAB_WAIT;\n"
               "LAB_DONE:\n}" :: "r"(bar), "r"(parity), "r"(dl) : "memory");
}
__device__ __forceinline__ void mbar_sleep(uint32_t bar, uint32_t parity, uint32_t dl) {
  asm volatile("{\n.reg .pred p;\n.reg .b32 t;\n"
               "LAB_WAIT:\n"
               "mbarrier.try_wait.parity.shared::cta.b64 p, [%0], %1, 20000;\n"
               "@p bra LAB_DONE;\n"
               "mov.u32 t, %%clock;\n"
               "sub.s32 t, t, %2;\n"
               "setp.lt.s32 p, t, 0;\n"
               "@p bra LAB_WAIT;\n"
               "LAB_DONE:\n}" :: "r"(bar), "r"(parity), "r"(dl) : "memory");
}
__device__ __forceinline__ bool poll_done(bool ok, uint32_t dl) {
  return __all_sync(0xffffffffu, ok || (int)(clock32() - dl) >= 0);
}
__device__ __forceinline__ unsigned ld_relaxed(const unsigned* p) {
  unsigned v; asm volatile("ld.relaxed.gpu.global.u32 %0, [%1];" : "=r"(v) : "l"(p) : "memory"); return v;
}
__device__ __forceinline__ void red_add_e(unsigned* p, unsigned v) {
  asm volatile(ELECT "red.relaxed.gpu.global.add.u32 [%0], %1;\n}" :: "l"(p), "r"(v) : "memory");
}
__device__ __forceinline__ void wait_flag(const unsigned* p, unsigned target, uint32_t dl) {
  asm volatile("{\n.reg .pred p;\n.reg .b32 t;\n"
               "LAB_WAIT:\n"
               "ld.relaxed.gpu.global.u32 t, [%0];\n"
               "sub.s32 t, t, %1;\n"
               "setp.ge.s32 p, t, 0;\n"
               "@p bra LAB_DONE;\n"
               "mov.u32 t, %%clock;\n"
               "sub.s32 t, t, %2;\n"
               "setp.lt.s32 p, t, 0;\n"
               "@p bra LAB_WAIT;\n"
               "LAB_DONE:\n}" :: "l"(p), "r"(target), "r"(dl) : "memory");
}
__device__ __forceinline__ void wait_until(uint32_t t) { while ((int)(clock32() - t) < 0) {} }
__device__ __forceinline__ void fence_proxy_async_smem() { asm volatile("fence.proxy.async.shared::cta;" ::: "memory"); }

constexpr uint64_t EVICT_FIRST = 0x12F0000000000000ull;
template <bool STREAM = false>
__device__ __forceinline__ void tma_load_2d(uint32_t dst, const CUtensorMap* m, uint32_t bar, int c0, int c1) {
  if (STREAM)
    asm volatile(ELECT "cp.async.bulk.tensor.2d.shared::cluster.global.mbarrier::complete_tx::bytes.L2::cache_hint [%0], [%1, {%3, %4}], [%2], %5;\n}"
                 :: "r"(dst), "l"(m), "r"(bar), "r"(c0), "r"(c1), "l"(EVICT_FIRST) : "memory");
  else
    asm volatile(ELECT "cp.async.bulk.tensor.2d.shared::cluster.global.mbarrier::complete_tx::bytes [%0], [%1, {%3, %4}], [%2];\n}"
                 :: "r"(dst), "l"(m), "r"(bar), "r"(c0), "r"(c1) : "memory");
}
template <bool STREAM = false>
__device__ __forceinline__ void tma_load_3d(uint32_t dst, const CUtensorMap* m, uint32_t bar, int c0, int c1, int c2) {
  if (STREAM)
    asm volatile(ELECT "cp.async.bulk.tensor.3d.shared::cluster.global.mbarrier::complete_tx::bytes.L2::cache_hint [%0], [%1, {%3, %4, %5}], [%2], %6;\n}"
                 :: "r"(dst), "l"(m), "r"(bar), "r"(c0), "r"(c1), "r"(c2), "l"(EVICT_FIRST) : "memory");
  else
    asm volatile(ELECT "cp.async.bulk.tensor.3d.shared::cluster.global.mbarrier::complete_tx::bytes [%0], [%1, {%3, %4, %5}], [%2];\n}"
                 :: "r"(dst), "l"(m), "r"(bar), "r"(c0), "r"(c1), "r"(c2) : "memory");
}
template <bool STREAM = false>
__device__ __forceinline__ void tma_load_4d(uint32_t dst, const CUtensorMap* m, uint32_t bar, int c0, int c1, int c2, int c3) {
  if (STREAM)
    asm volatile(ELECT "cp.async.bulk.tensor.4d.shared::cluster.global.mbarrier::complete_tx::bytes.L2::cache_hint [%0], [%1, {%3, %4, %5, %6}], [%2], %7;\n}"
                 :: "r"(dst), "l"(m), "r"(bar), "r"(c0), "r"(c1), "r"(c2), "r"(c3), "l"(EVICT_FIRST) : "memory");
  else
    asm volatile(ELECT "cp.async.bulk.tensor.4d.shared::cluster.global.mbarrier::complete_tx::bytes [%0], [%1, {%3, %4, %5, %6}], [%2];\n}"
                 :: "r"(dst), "l"(m), "r"(bar), "r"(c0), "r"(c1), "r"(c2), "r"(c3) : "memory");
}
__device__ __forceinline__ void tma_store_2d(const CUtensorMap* m, uint32_t src, int c0, int c1) {
  asm volatile(ELECT "cp.async.bulk.tensor.2d.global.shared::cta.bulk_group [%0, {%2, %3}], [%1];\n}"
               :: "l"(m), "r"(src), "r"(c0), "r"(c1) : "memory");
}
__device__ __forceinline__ void tma_store_3d(const CUtensorMap* m, uint32_t src, int c0, int c1, int c2) {
  asm volatile(ELECT "cp.async.bulk.tensor.3d.global.shared::cta.bulk_group [%0, {%2, %3, %4}], [%1];\n}"
               :: "l"(m), "r"(src), "r"(c0), "r"(c1), "r"(c2) : "memory");
}
__device__ __forceinline__ void bulk_load(uint32_t dst, const void* src, uint32_t bytes, uint32_t bar) {
  asm volatile(ELECT "cp.async.bulk.shared::cluster.global.mbarrier::complete_tx::bytes [%0], [%1], %2, [%3];\n}"
               :: "r"(dst), "l"(src), "r"(bytes), "r"(bar) : "memory");
}
__device__ __forceinline__ void bulk_prefetch(const void* src, uint32_t bytes) {
  asm volatile(ELECT "cp.async.bulk.prefetch.L2.global [%0], %1;\n}" :: "l"(src), "r"(bytes) : "memory");
}
__device__ __forceinline__ void bulk_commit() { asm volatile("cp.async.bulk.commit_group;" ::: "memory"); }
__device__ __forceinline__ void bulk_wait0() { asm volatile("cp.async.bulk.wait_group 0;" ::: "memory"); }
__device__ __forceinline__ void bulk_wait_read0() { asm volatile("cp.async.bulk.wait_group.read 0;" ::: "memory"); }
__device__ __forceinline__ void prefetch_tmap(const CUtensorMap* m) { asm volatile(ELECT "prefetch.tensormap [%0];\n}" :: "l"(m) : "memory"); }
__device__ __forceinline__ void wgmma_fence() { asm volatile("wgmma.fence.sync.aligned;" ::: "memory"); }
__device__ __forceinline__ void wgmma_commit() { asm volatile("wgmma.commit_group.sync.aligned;" ::: "memory"); }
template <int N> __device__ __forceinline__ void wgmma_wait() { asm volatile("wgmma.wait_group.sync.aligned %0;" :: "n"(N) : "memory"); }
template <int R> __device__ __forceinline__ void reg_alloc() { asm volatile("setmaxnreg.inc.sync.aligned.u32 %0;" :: "n"(R)); }
template <int R> __device__ __forceinline__ void reg_dealloc() { asm volatile("setmaxnreg.dec.sync.aligned.u32 %0;" :: "n"(R)); }
__device__ __forceinline__ void bar_sync(int id, int n) { asm volatile("bar.sync %0, %1;" :: "r"(id), "r"(n) : "memory"); }
__device__ __forceinline__ void bar_arrive(int id, int n) { asm volatile("bar.arrive %0, %1;" :: "r"(id), "r"(n) : "memory"); }
__device__ __forceinline__ void sched_fence(int zero) {
  asm volatile("{\n.reg .pred p;\n.reg .b32 t;\nsetp.eq.s32 p, %0, 0;\n@p bra.uni LAB_S;\n"
               "LAB_F:\nmov.u32 t, %%clock;\nsetp.eq.u32 p, t, 0;\n@p bra LAB_F;\nLAB_S:\n}" :: "r"(zero) : "memory");
}
template <int N> __device__ __forceinline__ void fence_regs(float (&a)[N]) {
  #pragma unroll
  for (int i = 0; i < N; i++) asm volatile("" : "+f"(a[i]) :: "memory");
}
template <int N> __device__ __forceinline__ void undef_regs(float (&a)[N]) {
  #pragma unroll
  for (int i = 0; i < N; i++) asm volatile("" : "=f"(a[i]));
}

__device__ __forceinline__ uint64_t desc_from_lo(uint32_t lo) { return (uint64_t)lo | ((uint64_t)0x40000040u << 32); }
__device__ __forceinline__ uint32_t pack_bf16(float lo, float hi) {
  uint32_t r; asm("cvt.rn.bf16x2.f32 %0, %1, %2;" : "=r"(r) : "f"(hi), "f"(lo)); return r;
}
__device__ __forceinline__ uint32_t fma_bf2(uint32_t a, uint32_t b, uint32_t c) {
  uint32_t d; asm("fma.rn.bf16x2 %0, %1, %2, %3;" : "=r"(d) : "r"(a), "r"(b), "r"(c)); return d;
}
__device__ __forceinline__ float bf_lo(uint32_t v) { return __uint_as_float(v << 16); }
__device__ __forceinline__ float bf_hi(uint32_t v) { return __uint_as_float(v & 0xFFFF0000u); }
__device__ __forceinline__ float bf16_round(float x) { return bf_lo(pack_bf16(x, 0.f)); }
__device__ __forceinline__ void stmatrix_x4(uint32_t addr, uint32_t r0, uint32_t r1, uint32_t r2, uint32_t r3) {
  asm volatile("stmatrix.sync.aligned.m8n8.x4.shared.b16 [%0], {%1, %2, %3, %4};" :: "r"(addr), "r"(r0), "r"(r1), "r"(r2), "r"(r3) : "memory");
}
__device__ __forceinline__ void stmatrix_x4_t(uint32_t addr, uint32_t r0, uint32_t r1, uint32_t r2, uint32_t r3) {
  asm volatile("stmatrix.sync.aligned.m8n8.x4.trans.shared.b16 [%0], {%1, %2, %3, %4};" :: "r"(addr), "r"(r0), "r"(r1), "r"(r2), "r"(r3) : "memory");
}
__device__ __forceinline__ void stmatrix_x4_if(uint32_t addr, uint32_t r0, uint32_t r1, uint32_t r2, uint32_t r3, bool on) {
  asm volatile("{\n.reg .pred p;\nsetp.ne.b32 p, %5, 0;\n@p stmatrix.sync.aligned.m8n8.x4.shared.b16 [%0], {%1, %2, %3, %4};\n}"
               :: "r"(addr), "r"(r0), "r"(r1), "r"(r2), "r"(r3), "r"((int)on) : "memory");
}
__device__ __forceinline__ void ldmatrix_x4(uint32_t addr, uint32_t& r0, uint32_t& r1, uint32_t& r2, uint32_t& r3) {
  asm volatile("ldmatrix.sync.aligned.m8n8.x4.shared.b16 {%0, %1, %2, %3}, [%4];" : "=r"(r0), "=r"(r1), "=r"(r2), "=r"(r3) : "r"(addr) : "memory");
}
__device__ __forceinline__ void ldmatrix_x4_t(uint32_t addr, uint32_t (&r)[4]) {
  asm volatile("ldmatrix.sync.aligned.m8n8.x4.trans.shared.b16 {%0, %1, %2, %3}, [%4];" : "=r"(r[0]), "=r"(r[1]), "=r"(r[2]), "=r"(r[3]) : "r"(addr) : "memory");
}
__device__ __forceinline__ void st_rlx(void* p, uint32_t a, bool on) {
  asm volatile("{\n.reg .pred p;\nsetp.ne.b32 p, %2, 0;\n@p st.relaxed.gpu.global.u32 [%0], %1;\n}" :: "l"(p), "r"(a), "r"((int)on) : "memory");
}
__device__ __forceinline__ void st_rlx_v2(void* p, uint32_t a, uint32_t b, bool on) {
  asm volatile("{\n.reg .pred p;\nsetp.ne.b32 p, %3, 0;\n@p st.relaxed.gpu.global.v2.u32 [%0], {%1, %2};\n}" :: "l"(p), "r"(a), "r"(b), "r"((int)on) : "memory");
}
__device__ __forceinline__ uint2 ld_rlx_v2(const void* p) {
  uint2 v; asm volatile("ld.relaxed.gpu.global.v2.u32 {%0,%1}, [%2];" : "=r"(v.x), "=r"(v.y) : "l"(p) : "memory"); return v;
}
__device__ __forceinline__ void st_rlx_v4(void* p, uint32_t a, uint32_t b, uint32_t c, uint32_t d, bool on) {
  asm volatile("{\n.reg .pred p;\nsetp.ne.b32 p, %5, 0;\n@p st.relaxed.gpu.global.v4.u32 [%0], {%1, %2, %3, %4};\n}"
               :: "l"(p), "r"(a), "r"(b), "r"(c), "r"(d), "r"((int)on) : "memory");
}
__device__ __forceinline__ void st_nonzero_v4(void* p, uint32_t a, uint32_t b, uint32_t c, uint32_t d, bool on) {
  st_rlx_v4(p, max(a, 1u), max(b, 1u), max(c, 1u), max(d, 1u), on);
}
__device__ __forceinline__ uint32_t min4(const uint4& v) { return min(min(v.x, v.y), min(v.z, v.w)); }
__device__ __forceinline__ uint4 ld_rlx_v4(const void* p) {
  uint4 v; asm volatile("ld.relaxed.gpu.global.v4.u32 {%0,%1,%2,%3}, [%4];" : "=r"(v.x), "=r"(v.y), "=r"(v.z), "=r"(v.w) : "l"(p) : "memory"); return v;
}
__device__ __forceinline__ uint32_t movmatrix_t(uint32_t a) {
  uint32_t d; asm volatile("movmatrix.sync.aligned.m8n8.trans.b16 %0, %1;" : "=r"(d) : "r"(a)); return d;
}
__device__ __forceinline__ void mma16(float (&c)[4], uint32_t a0, uint32_t a1, uint32_t a2, uint32_t a3, uint32_t b0, uint32_t b1) {
  asm volatile("mma.sync.aligned.m16n8k16.row.col.f32.bf16.bf16.f32 {%0,%1,%2,%3}, {%4,%5,%6,%7}, {%8,%9}, {%0,%1,%2,%3};"
               : "+f"(c[0]), "+f"(c[1]), "+f"(c[2]), "+f"(c[3]) : "r"(a0), "r"(a1), "r"(a2), "r"(a3), "r"(b0), "r"(b1));
}
__device__ __forceinline__ void sts128(uint32_t addr, uint32_t a, uint32_t b, uint32_t c, uint32_t d) {
  asm volatile("st.shared.v4.b32 [%0], {%1,%2,%3,%4};" :: "r"(addr), "r"(a), "r"(b), "r"(c), "r"(d) : "memory");
}
__device__ __forceinline__ uint4 lds128(uint32_t addr) {
  uint4 v; asm volatile("ld.shared.v4.b32 {%0,%1,%2,%3}, [%4];" : "=r"(v.x), "=r"(v.y), "=r"(v.z), "=r"(v.w) : "r"(addr) : "memory"); return v;
}
__device__ __forceinline__ uint32_t lds32(uint32_t addr) {
  uint32_t v; asm volatile("ld.shared.b32 %0, [%1];" : "=r"(v) : "r"(addr) : "memory"); return v;
}
__device__ __forceinline__ float2 lds64f(uint32_t addr) {
  float2 v; asm volatile("ld.shared.v2.f32 {%0,%1}, [%2];" : "=f"(v.x), "=f"(v.y) : "r"(addr) : "memory"); return v;
}
__device__ __forceinline__ void sts64(uint32_t addr, uint32_t a, uint32_t b) {
  asm volatile("st.shared.v2.b32 [%0], {%1, %2};" :: "r"(addr), "r"(a), "r"(b) : "memory");
}
__device__ __forceinline__ float fast_ex2(float x) { float y; asm("ex2.approx.ftz.f32 %0, %1;" : "=f"(y) : "f"(x)); return y; }
__device__ __forceinline__ float fast_rcp(float x) { float y; asm("rcp.approx.ftz.f32 %0, %1;" : "=f"(y) : "f"(x)); return y; }
__device__ __forceinline__ float fast_rsqrt(float x) { float y; asm("rsqrt.approx.ftz.f32 %0, %1;" : "=f"(y) : "f"(x)); return y; }
__device__ __forceinline__ float silu_f(float g) { return g * fast_rcp(1.f + fast_ex2(g * -1.4426950408889634f)); }
__device__ __forceinline__ float swiglu(float h, float v) {
  float t; asm("tanh.approx.f32 %0, %1;" : "=f"(t) : "f"(h));
  const float p = h * v;
  return fmaf(p, t, p);
}

__device__ __forceinline__ void wgmma_m64n128k16_ss(float (&d)[64], uint64_t descA, uint64_t descB, int scaleD) {
  asm volatile("{\n.reg .pred p;\nsetp.ne.b32 p, %66, 0;\n"
    "wgmma.mma_async.sync.aligned.m64n128k16.f32.bf16.bf16 "
    "{%0, %1, %2, %3, %4, %5, %6, %7, %8, %9, %10, %11, %12, %13, %14, %15, "
    "%16, %17, %18, %19, %20, %21, %22, %23, %24, %25, %26, %27, %28, %29, %30, %31, "
    "%32, %33, %34, %35, %36, %37, %38, %39, %40, %41, %42, %43, %44, %45, %46, %47, "
    "%48, %49, %50, %51, %52, %53, %54, %55, %56, %57, %58, %59, %60, %61, %62, %63}, "
    "%64, %65, p, 1, 1, 0, 1;\n}\n"
    : "+f"(d[0]), "+f"(d[1]), "+f"(d[2]), "+f"(d[3]), "+f"(d[4]), "+f"(d[5]), "+f"(d[6]), "+f"(d[7]),
      "+f"(d[8]), "+f"(d[9]), "+f"(d[10]), "+f"(d[11]), "+f"(d[12]), "+f"(d[13]), "+f"(d[14]), "+f"(d[15]),
      "+f"(d[16]), "+f"(d[17]), "+f"(d[18]), "+f"(d[19]), "+f"(d[20]), "+f"(d[21]), "+f"(d[22]), "+f"(d[23]),
      "+f"(d[24]), "+f"(d[25]), "+f"(d[26]), "+f"(d[27]), "+f"(d[28]), "+f"(d[29]), "+f"(d[30]), "+f"(d[31]),
      "+f"(d[32]), "+f"(d[33]), "+f"(d[34]), "+f"(d[35]), "+f"(d[36]), "+f"(d[37]), "+f"(d[38]), "+f"(d[39]),
      "+f"(d[40]), "+f"(d[41]), "+f"(d[42]), "+f"(d[43]), "+f"(d[44]), "+f"(d[45]), "+f"(d[46]), "+f"(d[47]),
      "+f"(d[48]), "+f"(d[49]), "+f"(d[50]), "+f"(d[51]), "+f"(d[52]), "+f"(d[53]), "+f"(d[54]), "+f"(d[55]),
      "+f"(d[56]), "+f"(d[57]), "+f"(d[58]), "+f"(d[59]), "+f"(d[60]), "+f"(d[61]), "+f"(d[62]), "+f"(d[63])
    : "l"(descA), "l"(descB), "r"(scaleD));
}
__device__ __forceinline__ void wgmma_m64n256k16_rs(float (&d)[128], uint32_t a0, uint32_t a1, uint32_t a2, uint32_t a3, uint64_t descB, int scaleD) {
  asm volatile("{\n.reg .pred p;\nsetp.ne.b32 p, %133, 0;\n"
    "wgmma.mma_async.sync.aligned.m64n256k16.f32.bf16.bf16 "
    "{%0, %1, %2, %3, %4, %5, %6, %7, %8, %9, %10, %11, %12, %13, %14, %15, "
    "%16, %17, %18, %19, %20, %21, %22, %23, %24, %25, %26, %27, %28, %29, %30, %31, "
    "%32, %33, %34, %35, %36, %37, %38, %39, %40, %41, %42, %43, %44, %45, %46, %47, "
    "%48, %49, %50, %51, %52, %53, %54, %55, %56, %57, %58, %59, %60, %61, %62, %63, "
    "%64, %65, %66, %67, %68, %69, %70, %71, %72, %73, %74, %75, %76, %77, %78, %79, "
    "%80, %81, %82, %83, %84, %85, %86, %87, %88, %89, %90, %91, %92, %93, %94, %95, "
    "%96, %97, %98, %99, %100, %101, %102, %103, %104, %105, %106, %107, %108, %109, %110, %111, "
    "%112, %113, %114, %115, %116, %117, %118, %119, %120, %121, %122, %123, %124, %125, %126, %127}, "
    "{%128, %129, %130, %131}, %132, p, 1, 1, 1;\n}\n"
    : "+f"(d[0]), "+f"(d[1]), "+f"(d[2]), "+f"(d[3]), "+f"(d[4]), "+f"(d[5]), "+f"(d[6]), "+f"(d[7]),
      "+f"(d[8]), "+f"(d[9]), "+f"(d[10]), "+f"(d[11]), "+f"(d[12]), "+f"(d[13]), "+f"(d[14]), "+f"(d[15]),
      "+f"(d[16]), "+f"(d[17]), "+f"(d[18]), "+f"(d[19]), "+f"(d[20]), "+f"(d[21]), "+f"(d[22]), "+f"(d[23]),
      "+f"(d[24]), "+f"(d[25]), "+f"(d[26]), "+f"(d[27]), "+f"(d[28]), "+f"(d[29]), "+f"(d[30]), "+f"(d[31]),
      "+f"(d[32]), "+f"(d[33]), "+f"(d[34]), "+f"(d[35]), "+f"(d[36]), "+f"(d[37]), "+f"(d[38]), "+f"(d[39]),
      "+f"(d[40]), "+f"(d[41]), "+f"(d[42]), "+f"(d[43]), "+f"(d[44]), "+f"(d[45]), "+f"(d[46]), "+f"(d[47]),
      "+f"(d[48]), "+f"(d[49]), "+f"(d[50]), "+f"(d[51]), "+f"(d[52]), "+f"(d[53]), "+f"(d[54]), "+f"(d[55]),
      "+f"(d[56]), "+f"(d[57]), "+f"(d[58]), "+f"(d[59]), "+f"(d[60]), "+f"(d[61]), "+f"(d[62]), "+f"(d[63]),
      "+f"(d[64]), "+f"(d[65]), "+f"(d[66]), "+f"(d[67]), "+f"(d[68]), "+f"(d[69]), "+f"(d[70]), "+f"(d[71]),
      "+f"(d[72]), "+f"(d[73]), "+f"(d[74]), "+f"(d[75]), "+f"(d[76]), "+f"(d[77]), "+f"(d[78]), "+f"(d[79]),
      "+f"(d[80]), "+f"(d[81]), "+f"(d[82]), "+f"(d[83]), "+f"(d[84]), "+f"(d[85]), "+f"(d[86]), "+f"(d[87]),
      "+f"(d[88]), "+f"(d[89]), "+f"(d[90]), "+f"(d[91]), "+f"(d[92]), "+f"(d[93]), "+f"(d[94]), "+f"(d[95]),
      "+f"(d[96]), "+f"(d[97]), "+f"(d[98]), "+f"(d[99]), "+f"(d[100]), "+f"(d[101]), "+f"(d[102]), "+f"(d[103]),
      "+f"(d[104]), "+f"(d[105]), "+f"(d[106]), "+f"(d[107]), "+f"(d[108]), "+f"(d[109]), "+f"(d[110]), "+f"(d[111]),
      "+f"(d[112]), "+f"(d[113]), "+f"(d[114]), "+f"(d[115]), "+f"(d[116]), "+f"(d[117]), "+f"(d[118]), "+f"(d[119]),
      "+f"(d[120]), "+f"(d[121]), "+f"(d[122]), "+f"(d[123]), "+f"(d[124]), "+f"(d[125]), "+f"(d[126]), "+f"(d[127])
    : "r"(a0), "r"(a1), "r"(a2), "r"(a3), "l"(descB), "r"(scaleD));
}

constexpr uint32_t MSLOT = 32768, QSLOT = 49152;
constexpr int NM = 6;
constexpr uint32_t SM_X0 = 3 * QSLOT;
constexpr uint32_t SM_XR = SM_X0 + 16384;
constexpr uint32_t SM_STG = 196608;
constexpr uint32_t SM_XCH = SM_STG + 16384;
constexpr uint32_t SM_BAR = SM_STG + 32768;
constexpr uint32_t SM_VEC = SM_BAR + 512;
constexpr uint32_t SM_MODT = SM_VEC;
constexpr uint32_t SM_TOTAL = SM_VEC + 2048;
constexpr uint32_t B_X = SM_BAR  , B_EQ = B_X + 64, B_EM = B_EQ + 32, B_STREQ = B_EM + 48, B_STH = B_STREQ + 8, B_HREQ = B_STH + 8  , B_LN = B_HREQ + 16,
                   B_FQ = B_LN + 8, B_FM = B_FQ + 32, B_MOD = B_FM + 48  , B_GATE = B_MOD + 64, B_STFREE = B_GATE + 8, B_VEC = B_STFREE + 8  ,
                   B_FLG = B_VEC + 16  , B_H2A = B_FLG + 24, B_HFREE = B_FLG + 96  ,
                   B_END = B_HFREE + 16;
constexpr int NB_WG = 1  , NB_CONS = 3, NB_ORD = 4  ;
#define TUNE(name, value) constexpr int name = value
TUNE(PF_BYTES, 256);
TUNE(X_GAP, 250);
TUNE(AUX_HOLD, 3200);
TUNE(AUX_URG, 4);
TUNE(AUX_SLOW, 84);
TUNE(AUX_GAP, 500);
TUNE(MSEP, 6);
TUNE(ASPLIT, 2);
TUNE(WPRE, 2);
TUNE(GPRE, 5);
TUNE(DTAIL, 4);

struct Maps {
  CUtensorMap x, out;
  CUtensorMap o, h2, hh;
  CUtensorMap wqk, wvv, wq1, wo, w1, w3, w2;
  CUtensorMap wmod;
};

struct Ring { int st; uint32_t ph; int prev; uint32_t dl;
};
__device__ __forceinline__ void ring_next(Ring& r) { if (++r.st == NM) { r.st = 0; r.ph ^= 1; } }

__device__ __forceinline__ void retire_prev(uint32_t rel, bool on) {
  wgmma_commit();
  wgmma_wait<1>();
  if (on) mbar_arrive_e(rel);
}
struct Nop { __device__ __forceinline__ void operator()() const {} };
template <bool REL = true, class F = Nop>
__device__ __forceinline__ void mma_step(float (&acc)[64], uint32_t a, uint32_t b, bool first, uint32_t rel, F urgent = F()) {
  const uint32_t alo = (a >> 4) + (1u << 16), blo = (b >> 4) + (512u << 16);
  wgmma_fence();
  #pragma unroll
  for (int k = 0; k < 4; k++) {
    wgmma_m64n128k16_ss(acc, desc_from_lo(alo + k * 2), desc_from_lo(blo + k * 128), k > 0 || !first);
    if (k == 0) { retire_prev(rel, REL); urgent(); }
  }
  wgmma_commit();
}
__device__ __forceinline__ uint32_t m_wait(uint32_t sbase, const Ring& r) {
  mbar_wait(sbase + B_FM + 8 * r.st, r.ph, r.dl);
  return sbase + r.st * MSLOT;
}
__device__ __forceinline__ uint32_t m_prev(uint32_t sbase, const Ring& r) { return sbase + B_EM + 8 * r.prev; }
__device__ __forceinline__ void m_next(Ring& r) {
  r.prev = r.st; ring_next(r);
}
__device__ __forceinline__ void m_step(float (&acc)[64], uint32_t sbase, uint32_t wgoff, Ring& r, bool first = false) {
  const uint32_t slot = m_wait(sbase, r);
  mma_step(acc, slot + wgoff, slot + 16384, first, m_prev(sbase, r));
  m_next(r);
}

struct LnRow { uint32_t rs[2], nb[2]; };
__device__ __forceinline__ void ln_row(LnRow& l, int h, float mean, float rstd) {
  l.rs[h] = pack_bf16(rstd, rstd);
  const float nb = -mean * bf_lo(l.rs[h]);
  l.nb[h] = pack_bf16(nb, nb);
}
__device__ __forceinline__ uint32_t ln_mod(uint32_t x, const LnRow& l, int h, uint32_t c1, uint32_t s) {
  return fma_bf2(fma_bf2(x, l.rs[h], l.nb[h]), c1, s);
}

__device__ __forceinline__ uint32_t q_wait(int u, uint32_t sbase, uint32_t dl) {
  mbar_wait(sbase + B_FQ + 8 * (u & 3), (u >> 2) & 1, dl);
  return sbase + (u & 3) * QSLOT;
}
__device__ __forceinline__ uint32_t q_empty(int u, uint32_t sbase) { return sbase + B_EQ + 8 * (u & 3); }
struct Frag4 { uint32_t o[4]; };
__device__ __forceinline__ void q_load(uint32_t (&A)[16], uint4 (&p)[4], int kk, uint32_t tile, const Frag4& f, uint32_t t) {
  ldmatrix_x4(tile + f.o[kk], A[4 * kk], A[4 * kk + 1], A[4 * kk + 2], A[4 * kk + 3]);
  p[kk] = lds128(t + kk * 64);
}
__device__ __forceinline__ void q_norm(uint32_t (&A)[16], const uint4 (&p)[4], int kk, const LnRow& l) {
  A[4 * kk + 0] = ln_mod(A[4 * kk + 0], l, 0, p[kk].x, p[kk].z); A[4 * kk + 1] = ln_mod(A[4 * kk + 1], l, 1, p[kk].x, p[kk].z);
  A[4 * kk + 2] = ln_mod(A[4 * kk + 2], l, 0, p[kk].y, p[kk].w); A[4 * kk + 3] = ln_mod(A[4 * kk + 3], l, 1, p[kk].y, p[kk].w);
}
template <bool NEXT>
__device__ __forceinline__ void q_step_rs(float (&acc)[128], uint32_t (&A)[16], uint32_t (&N)[16], uint4 (&p)[4], int u, uint32_t sbase,
                                          const Frag4& f, uint32_t tab, const LnRow& l, uint32_t rot, bool keep, bool first, uint32_t dl, int wg, int zero) {
  const uint32_t slot = first ? sbase : q_wait(u, sbase, dl);
  const uint32_t blo = ((slot + 16384) >> 4) + (512u << 16) + rot * 128 + (zero << (u >> 2)), t = tab + ((u + 1) & 7) * 256;
  #pragma unroll
  for (int kk = 0; kk < 4; kk++) q_norm(A, p, kk, l);
  #pragma unroll
  for (int i = 0; i < 16; i++) asm volatile("" : "+r"(A[i]));
  if (!first) sched_fence(zero);
  if (first) {
    mbar_wait(sbase + B_GATE, 0, dl);
    PROF(6, threadIdx.x == 0);
  }
  if (!(first && wg == 0)) bar_sync(NB_ORD + wg, 256);
  wgmma_fence();
  #pragma unroll
  for (int kk = 0; kk < 4; kk++) {
    wgmma_m64n256k16_rs(acc, A[4 * kk], A[4 * kk + 1], A[4 * kk + 2], A[4 * kk + 3], desc_from_lo(blo ^ (kk * 128)), kk > 0 || !first);
    if (kk == 0) retire_prev(q_empty(u - 1, sbase), !first);
    if (NEXT && kk == 1) {
      if ((u & 1) && u < MSEP) mbar_wait(sbase + B_MOD + 4 * (u + 1), 0, dl);
      #pragma unroll
      for (int q = 0; q < 4; q++) q_load(N, p, q, slot, f, t);
    }
    if (kk == 3 && (NEXT || wg == 0)) bar_arrive(NB_ORD + (wg ^ 1), 256);
    if (kk == 1) stmatrix_x4_if(sbase + SM_STG + (u >> 3) * 16384 + (f.o[0] ^ (((u >> 1 & 3) ^ rot) << 5)), A[0], A[1], A[2], A[3], keep);
  }
  wgmma_commit();
}

typedef uint32_t Frag8[8];
template <int N> __device__ __forceinline__ void pack_half(Frag8& f, const float (&acc)[N], int off, int half) {
  #pragma unroll
  for (int e = 0; e < 8; e++) { f[e] = pack_bf16(acc[off + 4 * e + 2 * half], acc[off + 4 * e + 2 * half + 1]); asm volatile("" : "+r"(f[e])); }
}
__device__ __forceinline__ void transpose8(Frag8& f) {
  #pragma unroll
  for (int e = 0; e < 8; e++) f[e] = movmatrix_t(f[e]);
}
__device__ __forceinline__ void attn_send(const Frag8& f, int kv, uint32_t xch, int warp, uint4* halo_out, bool has_next) {
  if (warp == 3) {
    st_nonzero_v4(halo_out + kv * 64, f[0], f[1], f[2], f[3], has_next); st_nonzero_v4(halo_out + kv * 64 + 32, f[4], f[5], f[6], f[7], has_next);
  } else {
    sts128(xch + 2048 + kv * 1024, f[0], f[1], f[2], f[3]); sts128(xch + 2048 + kv * 1024 + 512, f[4], f[5], f[6], f[7]);
  }
}
template <int N>
__device__ __forceinline__ void attn_recv(uint4* p, int first, uint32_t xch, int wg, int warp, const uint4* halo_in, bool has_prev) {
  bar_sync(NB_WG + wg, 128);
  #pragma unroll
  for (int e = 0; e < N; e++)
    asm volatile("{\n.reg .pred p, q;\nsetp.ne.b32 p, %6, 0;\nsetp.ne.b32 q, %7, 0;\n"
                 "mov.b32 %0, 0;\nmov.b32 %1, 0;\nmov.b32 %2, 0;\nmov.b32 %3, 0;\n"
                 "@p ld.shared.v4.b32 {%0,%1,%2,%3}, [%4];\n@q ld.relaxed.gpu.global.v4.u32 {%0,%1,%2,%3}, [%5];\n}"
                 : "=&r"(p[e].x), "=&r"(p[e].y), "=&r"(p[e].z), "=&r"(p[e].w)
                 : "r"(xch + (first + e) * 512), "l"(halo_in + (first + e) * 32), "r"((int)(warp > 0)), "r"((int)(warp == 0 && has_prev)) : "memory");
}
template <int N>
__device__ __forceinline__ void attn_check(uint4* p, int first, bool remote, const uint4* halo_in, uint32_t dl) {
  if (remote) {
    while (true) {
      uint32_t m = ~0u;
      #pragma unroll
      for (int e = 0; e < N; e++) m = min(m, min4(p[e]));
      if (poll_done(m != 0, dl)) break;
      #pragma unroll
      for (int e = 0; e < N; e++) p[e] = ld_rlx_v4(halo_in + (first + e) * 32);
    }
  }
}
template <int SPLIT, class F>
__device__ __forceinline__ void attn_core(const Frag8& qA, const Frag8& qB, const Frag8& kA, const Frag8& kB, const Frag8& vA, const Frag8& vB,
                                          const uint4* kP, const uint4* vP, bool noprev, int lane, float (&o)[2][5][4], F late) {
  const int g = lane >> 2, qd = lane & 3;
  const bool s0 = 2 * qd > g, s1 = 2 * qd + 1 > g;
  const uint32_t msk = (s0 ? 0xFFFFu : 0u) | (s1 ? 0xFFFF0000u : 0u);
  float s[2][3][4];
  uint32_t pr[2][2];
  auto scores = [&](int h, int nb) {
    s[h][nb][0] = s[h][nb][1] = s[h][nb][2] = s[h][nb][3] = 0.f;
    #pragma unroll
    for (int kk = 0; kk < 2; kk++) {
      const int e = 4 * h + 2 * kk;
      mma16(s[h][nb], qA[e], qB[e], qA[e + 1], qB[e + 1], nb == 1 ? kA[e] : nb == 2 ? kB[e] : kk ? kP[h].z : kP[h].x,
            nb == 1 ? kA[e + 1] : nb == 2 ? kB[e + 1] : kk ? kP[h].w : kP[h].y);
    }
  };
  auto rows = [&](int h, int y) {
    constexpr float SC = 0.17677669529663687f * 1.4426950408889634f;
    const float l0 = s0 ? (y == 0 && noprev ? -INFINITY : s[h][y][2 * y]) : s[h][y + 1][2 * y];
    const float l1 = s1 ? (y == 0 && noprev ? -INFINITY : s[h][y][2 * y + 1]) : s[h][y + 1][2 * y + 1];
    float m = fmaxf(l0, l1);
    m = fmaxf(m, __shfl_xor_sync(0xffffffffu, m, 1));
    m = fmaxf(m, __shfl_xor_sync(0xffffffffu, m, 2));
    const uint32_t p = pr[h][y] = pack_bf16(fast_ex2((l0 - m) * SC), fast_ex2((l1 - m) * SC));
    #pragma unroll
    for (int m2 = 0; m2 < 2; m2++) {
      const int e = 4 * h + 2 * m2;
      float (&d)[4] = o[h][2 * m2 + y];
      d[0] = d[1] = d[2] = d[3] = 0.f;
      if (y == 0) mma16(d, m2 ? vP[h].z : vP[h].x, m2 ? vP[h].w : vP[h].y, vA[e], vA[e + 1], p & msk, p & ~msk);
      else mma16(d, vA[e], vA[e + 1], vB[e], vB[e + 1], p & msk, p & ~msk);
    }
  };
  #pragma unroll
  for (int h = 0; h < 2; h++) { scores(h, 1); scores(h, 2); if (SPLIT == 0) scores(h, 0); }
  if (SPLIT == 2) { rows(0, 1); rows(1, 1); }
  if (SPLIT) { late(); scores(0, 0); scores(1, 0); }
  #pragma unroll
  for (int h = 0; h < 2; h++) {
    if (SPLIT < 2) rows(h, 1);
    rows(h, 0);
    o[h][4][0] = o[h][4][1] = o[h][4][2] = o[h][4][3] = 0.f;
    mma16(o[h][4], 0x3F803F80u, 0u, 0u, 0x3F803F80u, pr[h][0], pr[h][1]);
  }
}
__device__ __forceinline__ void attn_store(const float (&o)[2][5][4], int h, uint32_t sbase, const Frag4& f) {
  float r[4];
  #pragma unroll
  for (int e = 0; e < 4; e++) r[e] = fast_rcp(o[h][4][e]);
  #pragma unroll
  for (int m = 0; m < 2; m++) {
    const float (&lo)[4] = o[h][2 * m], (&hi)[4] = o[h][2 * m + 1];
    stmatrix_x4_t(sbase + SM_STG + f.o[2 * h + m], pack_bf16(lo[0] * r[0], lo[1] * r[1]), pack_bf16(hi[0] * r[2], hi[1] * r[3]),
                  pack_bf16(lo[2] * r[0], lo[3] * r[1]), pack_bf16(hi[2] * r[2], hi[3] * r[3]));
  }
}

__device__ __forceinline__ void request_store(uint32_t bar) {
  fence_proxy_async_smem();
  mbar_arrive_e(bar);
}

__device__ __forceinline__ void g_quad(float (&a0)[64], float (&a1)[64], bool first1, uint32_t sbase, uint32_t wgoff, Ring& r) {
  const uint32_t x = m_wait(sbase, r);
  mma_step(a0, x + wgoff, x + 16384, false, m_prev(sbase, r));
  m_next(r);
  const uint32_t xe = m_prev(sbase, r), y = m_wait(sbase, r);
  mma_step<false>(a1, x + wgoff, y, first1, 0);
  m_next(r);
  const uint32_t z = m_wait(sbase, r);
  mma_step(a1, z + wgoff, y + 16384, false, xe);
  mma_step(a0, z + wgoff, z + 16384, false, m_prev(sbase, r));
  m_next(r);
}
template <int T>
__device__ __forceinline__ void g_singles(float (&cur)[64], float (&prv)[64], bool first, int use, uint32_t sbase, uint32_t wgoff,
                                          const Frag4& f, Ring& r) {
  #pragma unroll
  for (int jj = 0; jj < 4; jj++) {
    m_step(cur, sbase, wgoff, r, first && jj == 0);
    if (jj == 0) { mbar_wait(sbase + B_HFREE + 8 * T, use & 1, r.dl); fence_regs(prv); PROF(33 + 2 * use + T, threadIdx.x == 0); }
    uint32_t p[4];
    #pragma unroll
    for (int e = 0; e < 4; e++) {
      const int i = jj * 8 + e * 2;
      p[e] = pack_bf16(swiglu(prv[i], prv[i + 32]), swiglu(prv[i + 1], prv[i + 33]));
    }
    stmatrix_x4(sbase + SM_STG + T * 16384 + f.o[jj], p[0], p[1], p[2], p[3]);
  }
  request_store(sbase + B_HREQ + 8 * T);
}

__device__ __forceinline__ uint32_t bad2(uint32_t a, uint32_t b, unsigned par) {
  uint32_t d; asm("lop3.b32 %0, %1, %2, %3, 0x7E;" : "=r"(d) : "r"(a), "r"(b), "r"(par)); return d;
}
__device__ __forceinline__ uint32_t bad4(const uint4& v, unsigned par) { return bad2(v.x, v.y, par) | bad2(v.z, v.w, par); }
__device__ __forceinline__ uint32_t hi_halves(uint32_t lo, uint32_t hi) { return __byte_perm(lo, hi, 0x7632); }

__device__ __forceinline__ void gather_table(const float* src, uint32_t dst, uint32_t bar, unsigned par, uint32_t dl) {
  asm volatile("{\n.reg .pred p, e;\n.reg .b32 s<4>, c<4>, t<4>, w<4>;\n"
               "elect.sync _|e, 0xffffffff;\n"
               "LAB_POLL:\n"
               "ld.relaxed.gpu.global.v4.u32 {s0, s1, s2, s3}, [%0];\n"
               "ld.relaxed.gpu.global.v4.u32 {c0, c1, c2, c3}, [%0 + 4096];\n"
               "prmt.b32 w0, c0, c1, 0x7632;\nprmt.b32 w1, c2, c3, 0x7632;\nprmt.b32 w2, s0, s1, 0x7632;\nprmt.b32 w3, s2, s3, 0x7632;\n"
               "st.shared.v4.b32 [%1], {w0, w1, w2, w3};\n"
               "lop3.b32 t0, s0, s1, %3, 0x7E;\nlop3.b32 t1, s2, s3, %3, 0x7E;\nlop3.b32 t2, c0, c1, %3, 0x7E;\nlop3.b32 t3, c2, c3, %3, 0x7E;\n"
               "lop3.b32 t0, t0, t1, 1, 0xA8;\nlop3.b32 t2, t2, t3, 1, 0xA8;\n"
               "or.b32 t0, t0, t2;\n"
               "setp.eq.u32 p, t0, 0;\n"
               "vote.sync.all.pred p, p, 0xffffffff;\n"
               "@p bra.uni LAB_OK;\n"
               "mov.u32 t0, %%clock;\nsub.s32 t0, t0, %4;\nsetp.lt.s32 p, t0, 0;\n"
               "vote.sync.all.pred p, p, 0xffffffff;\n"
               "@p bra.uni LAB_POLL;\n"
               "LAB_OK:\n"
               "@e mbarrier.arrive.shared::cta.b64 _, [%2];\n}"
               :: "l"(src), "r"(dst), "r"(bar), "r"(par), "r"(dl) : "memory");
}

__device__ __forceinline__ int other_slot(int i, int j) { return i < 4 ? (~j & 4) + i : (j & 4) + i - 4 + (i - 4 >= (j & 3)); }

__device__ __forceinline__ int aux_col(int a, int u) { return u < 8 ? (a & 1) * 1024 + (2 * u + (a >> 1)) * 64 : 2048 + ((u - 8) * 4 + a) * 64; }
constexpr int NA = 7;
constexpr uint32_t A_FULL = SM_BAR, A_EMPTY = SM_BAR + 64, A_SUM = SM_BAR + 128, A_FREE = SM_BAR + 136, SM_RED = SM_VEC;
__device__ __forceinline__ void aux_role(const Maps& maps, const bf16* __restrict__ cvec, Mail* mail0, int zero, int a, uint32_t sbase, int wid) {
  const int tid = threadIdx.x, lane = tid & 31;
  const uint32_t dl = clock32() + 800000000u;
  int st = 0; uint32_t ph = 0;
  if (wid == 8) {
    prefetch_tmap(&maps.wmod);
    #pragma unroll
    for (int i = 0; i < 18; i++) mbar_init_e(sbase + A_FULL + 8 * i, i < 8 ? 1 : i < 17 ? 8 : 2);
    fence_proxy_async_smem();
    bar_arrive(0, 352);
    PROF(39, lane == 0);
    #pragma unroll
    for (int i = 0; i < NA; i++) {
      mbar_expect_tx_e(sbase + A_FULL + 8 * i, 32768);
      tma_load_2d(sbase + i * MSLOT, &maps.wmod, sbase + A_FULL + 8 * i, aux_col(a, i >> 2), (i & 3) * 256);
    }
    PROF(40, lane == 0);
    #pragma unroll 1
    for (int i = NA; i < 96; i++) {
      if (i >= AUX_SLOW) wait_until(clock32() + AUX_GAP);
      if (i == 8) wait_until(dl - 800000000u + AUX_HOLD);
      mbar_wait(sbase + A_EMPTY + 8 * st, ph, dl);
      mbar_expect_tx_e(sbase + A_FULL + 8 * st, 32768);
      tma_load_2d<true>(sbase + st * MSLOT, &maps.wmod, sbase + A_FULL + 8 * st, aux_col(a, i >> 2), (i & 3) * 256);
      if (++st == NA) { st = 0; ph ^= 1; }
    }
  } else if (wid < 8) {
    const int g = lane >> 2, qd = lane & 3;
    uint32_t sc[16];
    const uint2 c = *reinterpret_cast<const uint2*>(cvec + tid * 4);
    sts64(sbase + SM_RED + tid * 8, pack_bf16(silu_f(bf_lo(c.x)), silu_f(bf_hi(c.x))), pack_bf16(silu_f(bf_lo(c.y)), silu_f(bf_hi(c.y))));
    bar_sync(0, 352);
    #pragma unroll
    for (int i = 0; i < 16; i++) sc[i] = lds32(sbase + SM_RED + ((i >> 2) * 256 + wid * 32 + (i & 3) * 8 + qd * 2) * 2);
    bar_sync(NB_CONS, 256);
    PROF(38, tid == 0);
    const uint32_t aoff = (wid * 32 + (lane & 7) + (lane >> 4) * 8) * 128 + ((((lane >> 3) & 1) ^ (lane & 7)) << 4);
    uint32_t w[2][8][4];
    auto fetch = [&](uint32_t (&f)[8][4]) {
      mbar_wait(sbase + A_FULL + 8 * st, ph, dl);
      #pragma unroll
      for (int e = 0; e < 8; e++) ldmatrix_x4_t((sbase + st * MSLOT + aoff + (e >> 2) * 2048) ^ ((e & 3) << 5), f[e]);
      if (++st == NA) { st = 0; ph ^= 1; }
    };
    #pragma unroll 1
    for (int u = 0; u < 24; u++) {
      float acc[4][4];
      #pragma unroll
      for (int m = 0; m < 4; m++) acc[m][0] = acc[m][1] = acc[m][2] = acc[m][3] = 0.f;
      fetch(w[0]);
      #pragma unroll
      for (int q = 0; q < 4; q++) {
        PROF(30 + (u & 1) * 4 + q, u < 2 && tid == 0);
        const uint32_t rel = sbase + A_EMPTY + 8 * (st == 0 ? NA - 1 : st - 1);
        if (q < 3) fetch(w[(q + 1) & 1]);
        uint32_t dep = 0;
        #pragma unroll
        for (int e = 0; e < 8; e++) dep |= w[q & 1][e][0];
        mbar_arrive_e(rel + (dep & zero));
        if (q == 1) mbar_wait(sbase + A_FREE, (u & 1) ^ 1, dl);
        #pragma unroll
        for (int e = 0; e < 8; e++) {
          const uint32_t (&f)[4] = w[q & 1][e];
          mma16(acc[e & 3], f[0], f[1], f[2], f[3], sc[4 * q + 2 * (e >> 2)], sc[4 * q + 2 * (e >> 2) + 1]);
        }
      }
      const float v0 = qd & 2 ? (qd & 1 ? acc[3][0] : acc[2][0]) : (qd & 1 ? acc[1][0] : acc[0][0]);
      const float v1 = qd & 2 ? (qd & 1 ? acc[3][2] : acc[2][2]) : (qd & 1 ? acc[1][2] : acc[0][2]);
      sts64(sbase + SM_RED + wid * 256 + (qd * 8 + g) * 8, __float_as_uint(v0), __float_as_uint(v1));
      mbar_arrive_e(sbase + A_SUM);
      if (u < AUX_URG) mbar_wait(sbase + A_FREE, u & 1, dl);
    }
  } else if (wid < 11) {
    float* const mail = &mail0->mod[(wid - 9) * 4 * 6 * D_ + 2 * lane];
    unsigned par = ld_relaxed(&mail0->flags[FL_EPOCH + (lane >> 5)]);
    bar_sync(0, 352);
    par = (par + 1) & 1;
    #pragma unroll 1
    for (int u = -2; u < 24; u++) {
      if (u >= 0) {
        const int col = aux_col(a, u);
        const float add = (col >> 10) == 1 || (col >> 10) == 4 ? 1.f : 0.f;
        const float mul = col < 3 * D_ ? 1.f : col < 5 * D_ ? 0.5f : 2.f;
        mbar_wait(sbase + A_SUM, u & 1, dl);
        float2 v[8];
        #pragma unroll
        for (int w = 0; w < 8; w++) v[w] = lds64f(sbase + SM_RED + w * 256 + lane * 8);
        const float t0 = ((v[0].x + v[1].x) + (v[2].x + v[3].x)) + ((v[4].x + v[5].x) + (v[6].x + v[7].x));
        const float t1 = ((v[0].y + v[1].y) + (v[2].y + v[3].y)) + ((v[4].y + v[5].y) + (v[6].y + v[7].y));
        mbar_arrive_e(sbase + A_FREE + (__float_as_uint(t0 + t1) & zero));
        const uint32_t w = pack_bf16((add + bf16_round(t0)) * mul, (add + bf16_round(t1)) * mul), o = __shfl_xor_sync(0xffffffffu, w, 1);
        const uint32_t m0 = (lane & 1) ? (o & 0xFFFF0000u) : (w << 16), m1 = (lane & 1) ? (w & 0xFFFF0000u) : (o << 16);
        #pragma unroll
        for (int c = 0; c < 4; c++) st_rlx_v2(mail + c * 6 * D_ + col, m0 | par, m1 | par, true);
        PROF(1 + u, tid == 288);
      }
      #pragma unroll 1
      for (int v = 2 * (u + 2); v < 2 * (u + 3) && v < 24; v++)
        #pragma unroll
        for (int c = 0; c < 4; c++) st_rlx_v2(mail + c * 6 * D_ + aux_col(a, v), par ^ 1, par ^ 1, true);
    }
    const int t = a * 64 + tid - 288;
    #pragma unroll 4
    for (int i = t; i < 16 * 16 * 256; i += 256) mail0->halo[par ^ 1][i] = make_uint4(0, 0, 0, 0);
    #pragma unroll 4
    for (int i = t; i < 16 * 8 * 64; i += 256) mail0->st2[par ^ 1][i] = make_uint4(0, 0, 0, 0);
  }
}

template <int MODE>
__global__ void __launch_bounds__(384, 1)
fused_block_kernel(const bf16* __restrict__ x, const bf16* __restrict__ cvec, const bf16* __restrict__ wmod, Mail* mail0, int zero,
                   const __grid_constant__ Maps maps) {
  extern __shared__ __align__(1024) uint8_t smem_raw[];
  const uint32_t sbase = smem_u32(smem_raw);
  const int tid = threadIdx.x, lane = tid & 31;
  PROFN(0, tid == 0);
  const int wid = __shfl_sync(0xffffffffu, tid >> 5, 0);
  const int b = cta_role<MODE>();
  if (b >= NCTA) { aux_role(maps, cvec, mail0, zero, b - NCTA, sbase, wid); return; }
  const int jg = b >> 6, mb = jg ? 31 - (b >> 2) : (b >> 2), j = 4 * jg + (b & 3);
  const uint32_t dl = clock32() + 800000000u;
  unsigned* const flags = &mail0->flags[mb * 32];
  const int row0 = mb * 128;

  if (wid >= 8) {
    if (wid == 8) {
      #pragma unroll
      for (int i = 0; i < 8; i++) mbar_init_e(sbase + B_X + 8 * i, 1);
      fence_proxy_async_smem();
      mbar_expect_tx_e(sbase + B_X, 4096);
      bulk_load(sbase + SM_XR, x + (size_t)(row0 + j * 16) * D_, 4096, sbase + B_X);
    } else if (wid == 11) {
      #pragma unroll
      for (int i = 0; i < 12; i++) prefetch_tmap(&maps.x + i);
    } else if (wid == 9) {
      #pragma unroll
      for (uint32_t bar = B_EQ; bar < B_FM; bar += 8) mbar_init_e(sbase + bar, bar < B_FQ ? 8 : bar == B_FQ + 8 || bar == B_FQ + 24 ? 2 : 1);
      fence_proxy_async_smem();
    } else {
      #pragma unroll
      for (uint32_t bar = B_FM; bar < B_END; bar += 8) mbar_init_e(sbase + bar, 1);
      fence_proxy_async_smem();
    }
    bar_sync(0, 384);
    reg_dealloc<40>();
    PROF(92, tid == 256);
    if (wid == 8) {
      uint32_t tnext = clock32();
      #pragma unroll 1
      for (int q = 1; q < 8; q++) {
        wait_until(tnext);
        mbar_expect_tx_e(sbase + B_X + 8 * q, 4096);
        bulk_load(sbase + SM_XR + q * 4096, x + (size_t)(row0 + j * 16 + 2 * q) * D_, 4096, sbase + B_X + 8 * q);
        tnext += X_GAP;
      }
      #pragma unroll 1
      for (int u = 0; u < 16; u++) {
        const int st = u & 3;
        if (u == 1) mbar_wait(sbase + B_X + 56, 0, dl);
        if (u == 2) { mbar_wait(sbase + B_GATE, 0, dl); PROFN(60, lane == 0); }
        if (u == 3) mbar_wait(sbase + B_EQ, 0, dl);
        mbar_wait(sbase + B_EQ + 8 * st, ((u >> 2) & 1) ^ 1, dl);
        const uint32_t slot = sbase + st * QSLOT, fb = sbase + B_FQ + 8 * st;
        mbar_expect_tx_e(fb, u == 0 ? 65536 : u == 15 ? 32768 : 49152);
        if ((u & 1) && (u < MSEP || u == 15)) mbar_arrive_e(fb);
        if (u == 0) tma_load_3d(sbase + SM_X0, &maps.x, fb, 0, mb * 64, 0);
        tma_load_4d<true>(slot + 16384, &maps.wqk, fb, 0, u * 64, j, 0);
        tma_load_4d<true>(slot + 32768, &maps.wvv, fb, 0, u * 64, j, 0);
        if (u < 15) tma_load_3d(slot, &maps.x, fb, u * 64 + 64, mb * 64, 0);
      }
      const unsigned e1 = 1 + ld_relaxed(flags + FO_EPOCH);
      Ring r{0, 1, 0, dl};
      uint32_t slot, fb;
      auto acquire = [&](uint32_t bytes) {
        mbar_wait(sbase + B_EM + 8 * r.st, r.ph, dl);
        slot = sbase + r.st * MSLOT; fb = sbase + B_FM + 8 * r.st;
        mbar_expect_tx_e(fb, bytes);
        ring_next(r);
      };
      #pragma unroll 1
      for (int kt = 0; kt < 16; kt++) {
        if (kt < 5) mbar_wait(sbase + B_EQ + 8 * (kt - (kt >= 2)), 1, dl);
        if ((kt & 7) == 0) { PROF(46, lane == 0 && kt == 8); mbar_wait(sbase + B_FLG + kt, 0, dl); PROF(47, lane == 0 && kt == 8); }
        acquire(32768);
        tma_load_4d<true>(slot + 16384, &maps.wq1, fb, (j + 8) * 64, (kt & 1) * 64 + (kt & 6) * 8, (kt >> 3) * 4, 0);
        tma_load_3d(slot, &maps.hh, fb, (kt & 7) * 64, row0, kt >> 3);
      }
      PROF(82, lane == 0);
      mbar_wait(sbase + B_FLG + 16, 0, dl);
      PROF(83, lane == 0);
      #pragma unroll 1
      for (int kt = 0; kt < 8; kt++) {
        if (kt == 4) {
          acquire(32768);
          tma_load_3d(slot, &maps.x, fb, j * 128, mb * 64, 0);
          tma_load_3d(slot + 16384, &maps.x, fb, j * 128 + 64, mb * 64, 0);
        }
        acquire(32768);
        tma_load_3d<true>(slot + 16384, &maps.wo, fb, 0, kt * 64, 2 * j);
        tma_load_2d(slot, &maps.o, fb, kt * 64, row0);
      }
      acquire(16384);
      tma_load_3d<true>(slot + 16384, &maps.wo, fb, 0, (8 + j) * 64, 2 * j);
      auto deferred = [&](const CUtensorMap* map, const unsigned* flag, Ring ra, int n, int col0, int step) {
        uint32_t dst = sbase + ra.st * MSLOT, bar = sbase + B_FM + 8 * ra.st, col = col0 + other_slot(0, j) * step;
        asm volatile("" : "+r"(dst), "+r"(bar), "+r"(col));
        wait_flag(flag, e1 * NCTA, dl);
        tma_load_2d(dst, map, bar, col, row0);
        #pragma unroll 1
        for (int i = 1; i < n; i++) { ring_next(ra); tma_load_2d(sbase + ra.st * MSLOT, map, sbase + B_FM + 8 * ra.st, col0 + other_slot(i, j) * step, row0); }
      };
      {
        const Ring ra = r;
        #pragma unroll 1
        for (int i = 0; i < 7; i++) {
          const int kt = 8 + other_slot(i, j);
          acquire(32768);
          tma_load_3d<true>(slot + 16384, &maps.wo, fb, 0, kt * 64, 2 * j);
          if (i == WPRE - 1) { deferred(&maps.o, &mail0->flags[FL_O], ra, WPRE, 512, 64); PROFN(61, lane == 0); }
          if (i >= WPRE) tma_load_2d(slot, &maps.o, fb, kt * 64, row0);
        }
      }
      #pragma unroll 1
      for (int t = 0; t < 2; t++) {
        acquire(32768);
        tma_load_2d<true>(slot, &maps.w1, fb, j * 64, (2 * j + t) * 64);
        tma_load_2d<true>(slot + 8192, &maps.w3, fb, j * 64, (2 * j + t) * 64);
        tma_load_2d<true>(slot + 16384, &maps.w1, fb, (8 + j) * 64, (2 * j + t) * 64);
        tma_load_2d<true>(slot + 24576, &maps.w3, fb, (8 + j) * 64, (2 * j + t) * 64);
      }
      {
        const Ring ra = r;
        #pragma unroll 1
        for (int i = 0; i < GPRE; i++) {
          const int kt = 2 * other_slot(i, j);
          acquire(32768);
          tma_load_2d<true>(slot + 16384, &maps.w1, fb, j * 64, kt * 64);
          tma_load_2d<true>(slot + 24576, &maps.w3, fb, j * 64, kt * 64);
        }
        deferred(&maps.h2, &mail0->flags[FL_H2], ra, GPRE, 0, 128);
        PROFN(62, lane == 0);
        mbar_arrive_e(sbase + B_H2A);
      }
      auto load_b = [&](uint32_t dst, int col, int kt) {
        tma_load_2d<true>(dst, &maps.w1, fb, col, kt * 64);
        tma_load_2d<true>(dst + 8192, &maps.w3, fb, col, kt * 64);
      };
      #pragma unroll 1
      for (int pr = 0; pr < 4; pr++) {
        const int col = (16 * pr + j) * 64, nk = pr == 0 ? 14 : 16;
        auto ktile = [&](int i) { return pr > 0 ? i : i < 7 ? 2 * other_slot(i, j) : 2 * other_slot(i - 7, j) + 1; };
        #pragma unroll 1
        for (int i = (pr == 0 ? GPRE : 0); i < (pr == 3 ? nk : nk + 4); i++) {
          const int kt = ktile(i < nk ? i : i - nk);
          if (pr < 3 && i > 4 && i < nk && (i & 1)) {
            acquire(32768);
            load_b(slot, col + 512, ktile(i - 1));
            load_b(slot + 16384, col + 512, kt);
          }
          if (pr == 0 && i == 7) mbar_wait(sbase + B_FLG + 32, 0, dl);
          acquire(32768);
          load_b(slot + 16384, i < nk ? col : col + 512, kt);
          tma_load_2d(slot, &maps.h2, fb, kt * 64, row0);
        }
      }
      #pragma unroll 1
      for (int kt = 0; kt < 56; kt++) {
        if ((kt & 7) == 0) mbar_wait(sbase + B_FLG + 40 + kt, 0, dl);
        acquire(32768);
        tma_load_3d(slot + 16384, &maps.w2, fb, 0, kt * 64, 2 * j);
        tma_load_3d(slot, &maps.hh, fb, (kt & 7) * 64, row0, kt >> 3);
      }
    } else {
      const unsigned e1 = 1 + ld_relaxed(wid == 9 ? flags + FO_EPOCH : &mail0->flags[FL_EPOCH]), par = e1 & 1;
      if (wid == 9) {
        #pragma unroll 1
        for (int n = 0; n < 12; n++) {
          if (n == 4) {
            mbar_wait(sbase + B_STH, 0, dl);
            tma_store_2d(&maps.h2, sbase + SM_STG, j * 128, row0);
            bulk_commit();
            bulk_wait0();
            red_add_e(&mail0->flags[FL_H2], 1);
            PROF(84, lane == 0);
            mbar_wait(sbase + B_H2A, 0, dl);
          }
          const int ht = (n - 5) & 1;
          if (n >= 1 && n <= 4) mbar_wait(sbase + B_STREQ, n & 1, dl);
          else mbar_sleep(n == 0 ? sbase + B_STREQ : sbase + B_HREQ + 8 * ht, n == 0 ? 0 : ((n - 5) >> 1) & 1, dl);
          if (n == 0) fence_proxy_async_smem();
          if (n == 2 || n == 3) tma_store_2d(&maps.o, sbase + SM_STG, (j + 8 * (n - 2)) * 64, row0);
          else if (n == 4) tma_store_2d(&maps.h2, sbase + SM_STG + 16384, j * 128 + 64, row0);
          else tma_store_3d(&maps.hh, sbase + SM_STG + (n < 2 ? n : ht) * 16384, j * 64, row0, n < 2 ? n : n - 5);
          bulk_commit();
          bulk_wait0();
          red_add_e(n == 3 ? &mail0->flags[FL_O] : flags + FO_CNT + n, 1);
          mbar_arrive_e(n < 4 ? sbase + B_STFREE : sbase + B_HFREE + 8 * ht);
          if (n == 4) mbar_arrive_e(sbase + B_HFREE);
          PROFN(70 + n, lane == 0 && n > 0); PROF(85, lane == 0 && n == 0);
          if (n != 3) { wait_flag(flags + FO_CNT + n, e1 * 8, dl); mbar_arrive_e(sbase + B_FLG + 8 * n); }
        }
      } else {
        mbar_wait(sbase + B_X + 24, 0, dl);
        const float* const mail = &mail0->mod[(b & 7) * 6 * D_ + lane * 4];
        if (wid == 10) {
          #pragma unroll 1
          for (int p = 0; p < 8; p++) {
            if (p >= 2) mbar_wait(p == 2 ? q_empty(0, sbase) : q_empty(2 * p - 5, sbase), p == 2 ? 0 : ((2 * p - 5) >> 2) & 1, dl);
            gather_table(mail + p * 128, sbase + SM_MODT + (p & 3) * 512 + ((lane * 16) ^ ((j >> 1) << 6)), 2 * p - 1 < MSEP ? sbase + B_MOD + 8 * p : sbase + B_FQ + 8 * ((2 * p - 1) & 3), par, dl);
            PROF(63 + p, lane == 0 && p < 7);
          }
          const uint32_t vdst = sbase + SM_VEC + (lane >> 3) * 64 + (lane & 3) * 16 + ((lane >> 2) & 1) * 8;
          #pragma unroll 1
          for (int v = 0; v < 2; v++) {
            mbar_sleep(sbase + B_FLG + 16 + 24 * v, 0, dl);
            uint4 m[3];
            while (true) {
              #pragma unroll
              for (int e = 0; e < 3; e++) m[e] = ld_rlx_v4(mail + (2 + v + e) * 1024 + j * 128);
              if (poll_done(((bad4(m[0], par) | bad4(m[1], par) | bad4(m[2], par)) & 1) == 0, dl)) break;
              __nanosleep(200);
            }
            #pragma unroll
            for (int e = 0; e < 3; e++) sts64(vdst + (v + e) * 256, hi_halves(m[e].x, m[e].y), hi_halves(m[e].z, m[e].w));
            mbar_arrive_e(sbase + B_VEC + 8 * v);
            PROF(70, lane == 0 && v == 0);
          }
        } else {
          mbar_wait(sbase + B_LN, 0, dl);
          red_add_e(&mail0->flags[FL_LN1], 1);
          wait_flag(&mail0->flags[FL_LN1], e1 * NCTA, dl);
          mbar_arrive_e(sbase + B_GATE);
          PROF(41, lane == 0);
        }
      }
    }
  } else {
    const int wg = wid >> 2, warp = wid & 3;
    const int g = lane >> 2, qd = lane & 3;
    bulk_prefetch(wmod + (size_t)(b * 8 + wid) * (6 * D_), PF_BYTES);
    bulk_prefetch(wmod + (size_t)(b * 8 + wid) * (6 * D_) + D_, PF_BYTES);
    bar_sync(0, 384);
    bulk_prefetch(wmod + (size_t)(b * 8 + wid) * (6 * D_) + PF_BYTES / 2, PF_BYTES);
    bulk_prefetch(wmod + (size_t)(b * 8 + wid) * (6 * D_) + PF_BYTES / 2 + D_, PF_BYTES);
    const unsigned e1 = 1 + ld_relaxed(flags + FO_EPOCH), par = e1 & 1;
    reg_alloc<232>();
    PROF(1, tid == 0);
    const uint32_t wgoff = wg * 8192;
    const uint32_t frag0 = wid * 2048 + (lane & 15) * 128 + (((lane >> 4) ^ (lane & 7)) << 4);
    const uint32_t slab = sbase + SM_STG + wid * 2048;

    LnRow ln;
    {
      uint2* const lmail = &mail0->ln1[(mb * 8 + (wid & 1) * 4 + (j >> 1)) * 16 + (j & 1) * 8 + (wid >> 1) + (lane & 1) * 4];
      st_rlx_v2(lmail, par ^ 1, par ^ 1, lane < 2);
      float s[2][2] = {{0.f, 0.f}, {0.f, 0.f}}, q2[2][2] = {{0.f, 0.f}, {0.f, 0.f}};
      #pragma unroll
      for (int c = 0; c < 8; c++) {
        if (c == 4) asm volatile("" : "+f"(s[0][0]), "+f"(s[0][1]), "+f"(q2[0][0]), "+f"(q2[0][1]));
        if ((c & 3) == 0) mbar_wait(sbase + B_X + 8 * (c + (wid >> 1)), 0, dl);
        if (c == 4) { PROF(3, tid == 224); PROF(93, tid == 0); }
        const uint4 v = lds128(sbase + SM_XR + (c >> 2) * 16384 + wid * 2048 + (c & 3) * 512 + lane * 16);
        const uint32_t vv[4] = {v.x, v.y, v.z, v.w};
        #pragma unroll
        for (int e = 0; e < 4; e++) {
          const float lo = bf_lo(vv[e]), hi = bf_hi(vv[e]);
          s[c >> 2][0] += lo; s[c >> 2][1] += hi; q2[c >> 2][0] = fmaf(lo, lo, q2[c >> 2][0]); q2[c >> 2][1] = fmaf(hi, hi, q2[c >> 2][1]);
        }
      }
      const bool odd = lane & 1;
      float sm = (s[0][0] + s[0][1]), so = (s[1][0] + s[1][1]), qm = (q2[0][0] + q2[0][1]), qo = (q2[1][0] + q2[1][1]);
      { const float a = odd ? so : sm, c = odd ? qo : qm;
        sm = a + __shfl_xor_sync(0xffffffffu, odd ? sm : so, 1); qm = c + __shfl_xor_sync(0xffffffffu, odd ? qm : qo, 1); }
      #pragma unroll
      for (int o = 2; o < 32; o <<= 1) { sm += __shfl_xor_sync(0xffffffffu, sm, o); qm += __shfl_xor_sync(0xffffffffu, qm, o); }
      sm *= (1.f / D_);
      ln_row(ln, 0, sm, fast_rsqrt(fmaxf(qm * (1.f / D_) - sm * sm, 0.f) + 1e-5f));
      st_rlx_v2(lmail, (ln.rs[0] << 16) | par, (ln.nb[0] << 16) | par, lane < 2);
      mbar_arrive_e(sbase + B_LN);
      PROF(4, tid == 224);
    }

    uint4* const halo_out = mail0->halo[par] + ((mb * 16 + j) * 2 + wg) * 128 + lane;
    const uint4* const halo_in = halo_out - 16 * 256;
    const uint32_t xch = sbase + SM_XCH + (tid >> 5) * 2048 + lane * 16;
    const bool noprev = mb == 0 && warp == 0, remote = mb > 0 && warp == 0;
    float a0[64], a1[64];
    uint32_t x2[32];
    Ring r{zero, 0, 0, dl};
    Frag8 qA, qB, kA, kB, vA, vB, wA, wB;
    {
      float acc[128];
      uint32_t A0[16], A1[16];
      undef_regs(acc);
      const uint32_t tab = sbase + SM_MODT + qd * 16;
      uint4 p[4];
      const uint32_t rot = j >> 1;
      Frag4 fq;
      #pragma unroll
      for (int q = 0; q < 4; q++) fq.o[q] = frag0 ^ ((q ^ rot) << 5);
      mbar_wait(sbase + B_LN, 0, dl);
      const uint2* const lin = &mail0->ln1[(mb * 8 + wid) * 16 + g];
      uint2 v0, v1;
      q_wait(0, sbase, dl);
      #pragma unroll
      for (int kk = 0; kk < 4; kk++) ldmatrix_x4(sbase + SM_X0 + fq.o[kk], A0[4 * kk], A0[4 * kk + 1], A0[4 * kk + 2], A0[4 * kk + 3]);
      do { v0 = ld_rlx_v2(lin); v1 = ld_rlx_v2(lin + 8); } while (!poll_done(((bad2(v0.x, v0.y, par) | bad2(v1.x, v1.y, par)) & 1) == 0, dl));
      ln.rs[0] = hi_halves(v0.x, v0.x); ln.nb[0] = hi_halves(v0.y, v0.y); ln.rs[1] = hi_halves(v1.x, v1.x); ln.nb[1] = hi_halves(v1.y, v1.y);
      mbar_wait(sbase + B_MOD, 0, dl);
      #pragma unroll
      for (int kk = 0; kk < 4; kk++) p[kk] = lds128(tab + kk * 64);
      PROF(5, tid == 0);
      q_step_rs<true>(acc, A0, A1, p, 0, sbase, fq, tab, ln, rot, !(j & 1), true, dl, wg, zero);
      #pragma unroll
      for (int u = 1; u < 15; u += 2) {
        q_step_rs<true>(acc, A1, A0, p, u, sbase, fq, tab, ln, rot, j & 1, false, dl, wg, zero);
        q_step_rs<true>(acc, A0, A1, p, u + 1, sbase, fq, tab, ln, rot, !(j & 1), false, dl, wg, zero);
        if (u == 7) mbar_arrive_e(sbase + B_STREQ);
      }
      q_step_rs<false>(acc, A1, A0, p, 15, sbase, fq, tab, ln, rot, j & 1, false, dl, wg, zero);
      PROF(7, tid == 0);
      mbar_wait(sbase + B_STFREE, 0, dl);
      request_store(sbase + B_STREQ);
      wgmma_wait<0>();
      undef_regs(a0);
      { const uint32_t slot = m_wait(sbase, r); mma_step(a0, slot + wgoff, slot + 16384, true, q_empty(15, sbase)); m_next(r); }
      fence_regs(acc);
      PROF(8, tid == 0);
      sched_fence(zero);
      pack_half(vB, acc, 64, 1); transpose8(vB);
      m_step(a0, sbase, wgoff, r);
      sched_fence(zero);
      pack_half(kB, acc, 32, 1);
      attn_send(vB, 1, xch - 16384, warp, halo_out, mb < 15); attn_send(kB, 0, xch - 16384, warp, halo_out, mb < 15);
      m_step(a0, sbase, wgoff, r);
      sched_fence(zero);
      pack_half(qA, acc, 0, 0); pack_half(qB, acc, 0, 1); pack_half(kA, acc, 32, 0); pack_half(wB, acc, 96, 1); pack_half(wA, acc, 96, 0);
      m_step(a0, sbase, wgoff, r);
      sched_fence(zero);
      pack_half(vA, acc, 64, 0); transpose8(vA);
    }
    uint4 wP[2];
    Frag4 frag;
    #pragma unroll
    for (int q = 0; q < 4; q++) frag.o[q] = frag0 ^ (q << 5);
    {
      m_step(a0, sbase, wgoff, r);
      uint4 pv[4];
      attn_recv<4>(pv, 0, xch - 16384, wg, warp, halo_in, mb > 0);
      m_step(a0, sbase, wgoff, r);
      mbar_wait(sbase + B_STFREE, 1, dl);
      transpose8(wB);
      m_step(a0, sbase, wgoff, r);
      attn_check<4>(pv, 0, remote, halo_in, dl);
      wgmma_wait<0>();
      PROF(9, tid == 0);
      float o[2][5][4];
      sched_fence(zero);
      attn_core<0>(qA, qB, kA, kB, vA, vB, pv, pv + 2, noprev, lane, o, Nop());
      attn_store(o, 0, sbase, frag);
      attn_store(o, 1, sbase, frag);
      request_store(sbase + B_STREQ);
      bar_sync(NB_CONS, 256);
      PROF(10, tid == 0);
      m_step(a0, sbase, wgoff, r);
      sched_fence(zero);
      attn_send(wB, 1, xch, warp, halo_out + 8 * 256, mb < 15);
      m_step(a0, sbase, wgoff, r);
      sched_fence(zero);
      transpose8(wA);
      #pragma unroll 1
      for (int i = 9; i < 15; i++) m_step(a0, sbase, wgoff, r);
      attn_recv<2>(wP, 2, xch, wg, warp, halo_in + 8 * 256, mb > 0);
      m_step(a0, sbase, wgoff, r);
    }
    {
      undef_regs(a1);
      {
        const uint32_t slot = m_wait(sbase, r);
        mma_step(a1, slot + wgoff, slot + 16384, true, m_prev(sbase, r), [&] {
          fence_regs(a0);
          pack_half(kB, a0, 32, 1);
          attn_send(kB, 0, xch, warp, halo_out + 8 * 256, mb < 15);
        });
        m_next(r);
      }
      PROF(14, tid == 0);
      sched_fence(zero);
      pack_half(kA, a0, 32, 0); pack_half(qA, a0, 0, 0); pack_half(qB, a0, 0, 1);
      m_step(a1, sbase, wgoff, r);
      attn_check<2>(wP, 2, remote, halo_in + 8 * 256, dl);
      uint4 kP[2];
      attn_recv<2>(kP, 0, xch, wg, warp, halo_in + 8 * 256, mb > 0);
      m_step(a1, sbase, wgoff, r);
      if (ASPLIT == 0) attn_check<2>(kP, 0, remote, halo_in + 8 * 256, dl);
      wgmma_wait<0>();
      PROF(15, tid == 0);
      float o[2][5][4];
      mbar_wait(sbase + B_STFREE, 0, dl);
      attn_core<ASPLIT>(qA, qB, kA, kB, wA, wB, kP, wP, noprev, lane, o, [&] { attn_check<2>(kP, 0, remote, halo_in + 8 * 256, dl); });
      attn_store(o, 0, sbase, frag);
      attn_store(o, 1, sbase, frag);
      request_store(sbase + B_STREQ);
      bar_sync(NB_CONS, 256);
      PROF(16, tid == 0);
      auto residual = [&] {
        const uint32_t xs = m_wait(sbase, r), xe = sbase + B_EM + 8 * r.st;
        ring_next(r);
        #pragma unroll
        for (int t = 0; t < 2; t++) {
          #pragma unroll
          for (int jj = 4 * t; jj < 4 * t + 4; jj++) ldmatrix_x4(xs + t * 16384 + frag.o[jj & 3], x2[4 * jj], x2[4 * jj + 1], x2[4 * jj + 2], x2[4 * jj + 3]);
          if (t == 1) {
            uint32_t dep = 0;
            #pragma unroll
            for (int jj = 0; jj < 8; jj++) dep |= x2[4 * jj];
            mbar_arrive_e(xe + (dep & zero));
          }
          m_step(a1, sbase, wgoff, r);
        }
      };
      m_step(a1, sbase, wgoff, r);
      residual();
      #pragma unroll 1
      for (int i = 6; i < 8; i++) m_step(a1, sbase, wgoff, r);
      mma_step(a1, sbase + SM_STG + wgoff, m_wait(sbase, r) + 16384, false, m_prev(sbase, r));
      m_next(r);
      PROF(17, tid == 0);
      uint4* const sm = mail0->st2[par] + (mb * 8 + wid) * 64 + g;
      st_rlx_v4(sm + j * 8, 0, 0, 0, 0, qd == (g >> 1));
      #pragma unroll 1
      for (int i = 0; i < 7; i++) { m_step(a1, sbase, wgoff, r); PROF(42, tid == 0 && i == 0); }
      PROF(45, tid == 0);
      mbar_wait(sbase + B_VEC, 0, dl);
      mbar_wait(sbase + B_STFREE, 1, dl);
      const uint32_t vec = sbase + SM_VEC + qd * 16;
      uint4 ga[4];
      #pragma unroll
      for (int q = 0; q < 4; q++) ga[q] = lds128(vec + q * 64);
      wgmma_wait<0>();
      mbar_arrive_e(m_prev(sbase, r));
      fence_regs(a1);
      PROF(18, tid == 0);
      float gl[4] = {0.f, 0.f, 0.f, 0.f}, gh[4] = {0.f, 0.f, 0.f, 0.f};
      #pragma unroll
      for (int jj = 0; jj < 8; jj++) {
        uint32_t* v = &x2[4 * jj];
        const uint32_t wl = (jj & 1) ? ga[jj >> 1].z : ga[jj >> 1].x, wh = (jj & 1) ? ga[jj >> 1].w : ga[jj >> 1].y;
        #pragma unroll
        for (int e = 0; e < 4; e++) v[e] = fma_bf2(e & 2 ? wh : wl, pack_bf16(a1[8 * jj + 2 * e], a1[8 * jj + 2 * e + 1]), v[e]);
        mma16(gl, v[0], 0x3F803F80u, v[2], 0x3F803F80u, v[0], v[2]);
        mma16(gh, v[1], 0x3F803F80u, v[3], 0x3F803F80u, v[1], v[3]);
      }
      st_nonzero_v4(sm + j * 8, __float_as_uint(g & 1 ? gl[3] : gl[2]), __float_as_uint(g & 1 ? gl[1] : gl[0]),
                __float_as_uint(g & 1 ? gh[3] : gh[2]), __float_as_uint(g & 1 ? gh[1] : gh[0]), qd == (g >> 1));
      float s[2], q2[2];
      PROF(19, tid == 0);
      uint4 sb[4], cb[4];
      #pragma unroll
      for (int q = 0; q < 4; q++) { sb[q] = lds128(vec + 256 + q * 64); cb[q] = lds128(vec + 512 + q * 64); }
      uint4 p0, p1;
      while (true) {
        p0 = ld_rlx_v4(sm + qd * 16); p1 = ld_rlx_v4(sm + qd * 16 + 8);
        if (poll_done(min(min4(p0), min4(p1)) != 0, dl)) break;
      }
      PROF(20, tid == 0);
      s[0] = __uint_as_float(p0.x) + __uint_as_float(p1.x); q2[0] = __uint_as_float(p0.y) + __uint_as_float(p1.y);
      s[1] = __uint_as_float(p0.z) + __uint_as_float(p1.z); q2[1] = __uint_as_float(p0.w) + __uint_as_float(p1.w);
      #pragma unroll
      for (int o2 = 1; o2 <= 2; o2 <<= 1)
        #pragma unroll
        for (int h = 0; h < 2; h++) { s[h] += __shfl_xor_sync(0xffffffffu, s[h], o2); q2[h] += __shfl_xor_sync(0xffffffffu, q2[h], o2); }
      #pragma unroll
      for (int h = 0; h < 2; h++) {
        const float m = s[h] * (1.f / D_);
        ln_row(ln, h, m, fast_rsqrt(fmaxf(q2[h] * (1.f / D_) - m * m, 0.f) + 1e-5f));
      }
      #pragma unroll
      for (int jj = 0; jj < 8; jj++) {
        const uint32_t cl = (jj & 1) ? cb[jj >> 1].z : cb[jj >> 1].x, ch = (jj & 1) ? cb[jj >> 1].w : cb[jj >> 1].y;
        const uint32_t sl = (jj & 1) ? sb[jj >> 1].z : sb[jj >> 1].x, sh = (jj & 1) ? sb[jj >> 1].w : sb[jj >> 1].y;
        stmatrix_x4(sbase + SM_STG + (jj >> 2) * 16384 + frag.o[jj & 3], ln_mod(x2[4 * jj], ln, 0, cl, sl), ln_mod(x2[4 * jj + 1], ln, 1, cl, sl),
                    ln_mod(x2[4 * jj + 2], ln, 0, ch, sh), ln_mod(x2[4 * jj + 3], ln, 1, ch, sh));
        if (jj == 3) { request_store(sbase + B_STH); sched_fence(zero); }
      }
      request_store(sbase + B_STREQ);
      bar_sync(NB_WG + wg, 128);
      PROF(21, tid == 0);
    }

    undef_regs(a0);
    #pragma unroll
    for (int t = 0; t < 2; t++) {
      const uint32_t slot = m_wait(sbase, r);
      if (t == 0) mma_step<false>(a0, sbase + SM_STG + wgoff, slot, true, 0);
      else mma_step(a0, sbase + SM_STG + 16384 + wgoff, slot, false, m_prev(sbase, r));
      mma_step<false>(a1, sbase + SM_STG + t * 16384 + wgoff, slot + 16384, t == 0, 0);
      m_next(r);
    }
    PROF(22, tid == 0);
    #pragma unroll 1
    for (int i = 0; i < 4; i++) m_step(a0, sbase, wgoff, r);
    #pragma unroll 1
    for (int pr = 0; pr < 3; pr++) {
      #pragma unroll 1
      for (int i = (pr == 0); i < 5; i++) g_quad(a0, a1, i == 0, sbase, wgoff, r);
      g_quad(a0, a1, false, sbase, wgoff, r);
      g_singles<0>(a1, a0, false, pr, sbase, wgoff, frag, r);
      g_singles<1>(a0, a1, true, pr, sbase, wgoff, frag, r);
    }
    #pragma unroll 1
    for (int i = 4; i < 15; i++) m_step(a0, sbase, wgoff, r);
    m_step(a0, sbase, wgoff, r);
    g_singles<0>(a1, a0, true, 3, sbase, wgoff, frag, r);
    #pragma unroll 1
    for (int i = 4; i < 56 - DTAIL; i++) m_step(a1, sbase, wgoff, r);
    if (DTAIL) {
      if (wg == 1) { wgmma_wait<0>(); mbar_arrive_e(m_prev(sbase, r)); bar_sync(NB_ORD, 256); }
      #pragma unroll
      for (int i = 0; i < DTAIL; i++) {
        const uint32_t slot = m_wait(sbase, r);
        const uint32_t alo = ((slot + wgoff) >> 4) + (1u << 16), blo = ((slot + 16384) >> 4) + (512u << 16);
        wgmma_fence();
        #pragma unroll
        for (int k = 0; k < 4; k++) wgmma_m64n128k16_ss(a1, desc_from_lo(alo + k * 2), desc_from_lo(blo + k * 128), true);
        wgmma_commit();
        ring_next(r);
      }
      if (wg == 0) bar_arrive(NB_ORD, 256);
    }
    {
      mbar_wait(sbase + B_HFREE, 0, dl);
      mbar_wait(sbase + B_HFREE + 8, 1, dl);
      mbar_wait(sbase + B_VEC + 8, 0, dl);
      uint4 gb[4];
      #pragma unroll
      for (int q = 0; q < 4; q++) gb[q] = lds128(sbase + SM_VEC + 768 + qd * 16 + q * 64);
      wgmma_wait<0>();
      fence_regs(a1);
      PROF(50, tid == 128);
      #pragma unroll
      for (int t = 0; t < 2; t++) {
        #pragma unroll
        for (int jj = 4 * t; jj < 4 * t + 4; jj++) {
          const uint32_t gl = (jj & 1) ? gb[jj >> 1].z : gb[jj >> 1].x, gh = (jj & 1) ? gb[jj >> 1].w : gb[jj >> 1].y;
          const int i = 8 * jj;
          stmatrix_x4(sbase + SM_STG + t * 16384 + frag.o[jj & 3],
                      fma_bf2(gl, pack_bf16(a1[i], a1[i + 1]), x2[4 * jj]), fma_bf2(gl, pack_bf16(a1[i + 2], a1[i + 3]), x2[4 * jj + 1]),
                      fma_bf2(gh, pack_bf16(a1[i + 4], a1[i + 5]), x2[4 * jj + 2]), fma_bf2(gh, pack_bf16(a1[i + 6], a1[i + 7]), x2[4 * jj + 3]));
        }
        fence_proxy_async_smem();
        tma_store_3d(&maps.out, slab + t * 16384, j * 128 + t * 64, mb * 64 + warp * 16, wg);
      }
      bulk_commit();
      st_rlx(tid == 0 ? flags + FO_EPOCH : &mail0->flags[FL_EPOCH], e1, j == 0 && (tid == 0 || (tid == 1 && mb == 0)));
      bulk_wait_read0();
      PROFN(51, tid == 128);
    }
  }
}

typedef CUresult (*PFN_encodeTiled)(CUtensorMap*, CUtensorMapDataType, cuuint32_t, void*, const cuuint64_t*, const cuuint64_t*,
                                    const cuuint32_t*, const cuuint32_t*, CUtensorMapInterleave, CUtensorMapSwizzle,
                                    CUtensorMapL2promotion, CUtensorMapFloatOOBfill);

void encode(PFN_encodeTiled fn, CUtensorMap* m, const void* ptr, int rank, const cuuint64_t* dims, const cuuint64_t* strides,
            const cuuint32_t* box) {
  const cuuint32_t es[5] = {1, 1, 1, 1, 1};
  fn(m, CU_TENSOR_MAP_DATA_TYPE_BFLOAT16, rank, const_cast<void*>(ptr), dims, strides, box, es, CU_TENSOR_MAP_INTERLEAVE_NONE,
     CU_TENSOR_MAP_SWIZZLE_128B, CU_TENSOR_MAP_L2_PROMOTION_L2_256B, CU_TENSOR_MAP_FLOAT_OOB_FILL_NONE);
}
void map2d(PFN_encodeTiled fn, CUtensorMap* m, const void* ptr, int cols, int rows, int boxrows) {
  const cuuint64_t dims[2] = {(cuuint64_t)cols, (cuuint64_t)rows}, strides[1] = {(cuuint64_t)cols * 2};
  const cuuint32_t box[2] = {64, (cuuint32_t)boxrows};
  encode(fn, m, ptr, 2, dims, strides, box);
}
void map_w2chunk(PFN_encodeTiled fn, CUtensorMap* m, const void* ptr, int cols, int rows) {
  const cuuint64_t dims[3] = {64, (cuuint64_t)rows, (cuuint64_t)cols / 64}, strides[2] = {(cuuint64_t)cols * 2, 128};
  const cuuint32_t box[3] = {64, 64, 2};
  encode(fn, m, ptr, 3, dims, strides, box);
}
void map_parity(PFN_encodeTiled fn, CUtensorMap* m, const void* ptr, int boxpairs, int boxpar) {
  const cuuint64_t dims[3] = {D_, S_ / 2, 2}, strides[2] = {D_ * 4, D_ * 2};
  const cuuint32_t box[3] = {64, (cuuint32_t)boxpairs, (cuuint32_t)boxpar};
  encode(fn, m, ptr, 3, dims, strides, box);
}

}

extern "C" void kernel_launch(void* const* d_in, const int* in_sizes, int n_in, void* d_out, int out_size) {
  (void)in_sizes; (void)n_in; (void)out_size;
  const bf16* x = (const bf16*)d_in[0];
  const bf16* wqkv = (const bf16*)d_in[1];
  const bf16* wo = (const bf16*)d_in[2];
  const bf16* w1 = (const bf16*)d_in[4];
  const bf16* w3 = (const bf16*)d_in[5];
  const bf16* w2 = (const bf16*)d_in[6];
  const bf16* cvec = (const bf16*)d_in[7];
  const bf16* w_mod = (const bf16*)d_in[8];

  static PFN_encodeTiled fn = nullptr;
  static Maps maps;
  static const void* cached[8] = {};
  static int sms = 0;
  static void* mail = nullptr;
  if (!fn) {
    void* p = nullptr; cudaDriverEntryPointQueryResult st;
    cudaGetDriverEntryPoint("cuTensorMapEncodeTiled", &p, cudaEnableDefault, &st);
    fn = (PFN_encodeTiled)p;
    cudaFuncSetAttribute(fused_block_kernel<0>, cudaFuncAttributeMaxDynamicSharedMemorySize, SM_TOTAL + SM_PROF);
    cudaFuncSetAttribute(fused_block_kernel<1>, cudaFuncAttributeMaxDynamicSharedMemorySize, SM_TOTAL + SM_PROF);
    cudaFuncSetAttribute(fused_block_kernel<2>, cudaFuncAttributeMaxDynamicSharedMemorySize, SM_TOTAL + SM_PROF);
    cudaGetSymbolAddress(&mail, g_mail);
    int dev = 0;
    cudaGetDevice(&dev);
    cudaDeviceGetAttribute(&sms, cudaDevAttrMultiProcessorCount, dev);
  }
  const void* cur[8] = {x, wqkv, wo, w1, w3, w2, d_out, w_mod};
  bool same = true;
  for (int i = 0; i < 8; i++) same = same && cached[i] == cur[i];
  if (!same) {
    void *o, *h2, *hh;
    cudaGetSymbolAddress(&hh, g_hh); cudaGetSymbolAddress(&o, g_o);
    h2 = o;
    map_parity(fn, &maps.x, x, 64, 2); map_parity(fn, &maps.out, d_out, 16, 1);
    map2d(fn, &maps.o, o, D_, S_, 128); map2d(fn, &maps.h2, h2, D_, S_, 128);
    {
      const cuuint64_t dims[3] = {512, (cuuint64_t)S_, 7}, strides[2] = {1024, (cuuint64_t)S_ * 1024};
      const cuuint32_t box[3] = {64, 128, 1};
      encode(fn, &maps.hh, hh, 3, dims, strides, box);
    }
    {
      const cuuint64_t dims[4] = {64, 1024, 16, 2}, strides[3] = {3072 * 2, 128, 2048};
      const cuuint64_t dimv[4] = {64, 1024, 8, 2}, stridev[3] = {3072 * 2, 128, 1024};
      const cuuint32_t box[4] = {64, 64, 1, 2};
      encode(fn, &maps.wqk, wqkv, 4, dims, strides, box);
      encode(fn, &maps.wvv, wqkv + 2048, 4, dimv, stridev, box);
      const cuuint64_t dim1[4] = {1024, 128, 8, 2}, stride1[3] = {3072 * 2, 128 * 3072 * 2, 2048};
      const cuuint32_t box1[4] = {64, 16, 4, 2};
      encode(fn, &maps.wq1, wqkv, 4, dim1, stride1, box1);
    }
    map_w2chunk(fn, &maps.wo, wo, D_, D_); map_w2chunk(fn, &maps.w2, w2, D_, F_);
    map2d(fn, &maps.w1, w1, F_, D_, 64); map2d(fn, &maps.w3, w3, F_, D_, 64);
    map2d(fn, &maps.wmod, w_mod, 6 * D_, D_, 256);
    for (int i = 0; i < 8; i++) cached[i] = cur[i];
  }
  if (sms == NCTA + NAUX) {
    fused_block_kernel<0><<<NCTA + NAUX, 384, SM_TOTAL + SM_PROF>>>(x, cvec, w_mod, (Mail*)mail, 0, maps);
  } else {
    fused_block_kernel<1><<<NAUX, 384, SM_TOTAL + SM_PROF>>>(x, cvec, w_mod, (Mail*)mail, 0, maps);
    fused_block_kernel<2><<<NCTA, 384, SM_TOTAL + SM_PROF>>>(x, cvec, w_mod, (Mail*)mail, 0, maps);
  }
}
```

```cpp
#include <cuda.h>
#include <cuda_runtime.h>
#include <cuda_bf16.h>
#include <stdint.h>

namespace {

typedef __nv_bfloat16 bf16;

constexpr int S_ = 2048, D_ = 1024, F_ = 3584;
constexpr int NCTA = 128, NAUX = 4;

__device__ __align__(1024) bf16 g_o[S_ * D_];
__device__ __align__(1024) bf16 g_hh[S_ * F_];
constexpr int FO_EPOCH = 0, FO_CNT = 1;
constexpr int FL_EPOCH = 16 * 32, FL_LN1 = FL_EPOCH + 2, FL_H2 = FL_EPOCH + 3, FL_O = FL_EPOCH + 4;
struct Mail {
  unsigned flags[32 * 32];
  float mod[8 * 6 * D_];
  uint2 ln1[16 * 8 * 16];
  uint4 halo[2][16 * 16 * 2 * 4 * 32];
  uint4 st2[2][16 * 8 * 8 * 8];
};
__device__ __align__(1024) Mail g_mail;

template <int mode>
__device__ __forceinline__ int cta_role() {
  if (mode) return mode == 1 ? NCTA + (blockIdx.x & 3) : blockIdx.x & 127;
  uint32_t sm;
  asm("mov.u32 %0, %%smid;" : "=r"(sm));
  sm = (sm & ~3u) == 12 ? sm + 108 : (sm & ~3u) == 120 ? sm - 108 : sm;
  const int t = sm >> 1;
  int r;
  if (t < 32) r = (t & 7) * 16 + (t >> 3) * 2 + (sm & 1);
  else if (t < 60) r = (1 + (t - 32) % 7) * 16 + 8 + ((t - 32) / 7) * 2 + (sm & 1);
  else if (t < 62) r = NCTA + sm - 120;
  else r = sm - 116;
  return r;
}
#define PROF(slot, on) do {} while (0)
#define PROFN(slot, on) do {} while (0)
#define PROF_OUT(role, t) do {} while (0)
constexpr uint32_t SM_PROF = 0;

__device__ __forceinline__ uint32_t smem_u32(const void* p) { return (uint32_t)__cvta_generic_to_shared(p); }
#define ELECT "{\n.reg .pred p;\nelect.sync _|p, 0xffffffff;\n@p "
__device__ __forceinline__ void mbar_init_e(uint32_t bar, uint32_t count) {
  asm volatile(ELECT "mbarrier.init.shared::cta.b64 [%0], %1;\n}" :: "r"(bar), "r"(count) : "memory");
}
__device__ __forceinline__ void mbar_expect_tx_e(uint32_t bar, uint32_t bytes) {
  asm volatile(ELECT "mbarrier.arrive.expect_tx.shared::cta.b64 _, [%0], %1;\n}" :: "r"(bar), "r"(bytes) : "memory");
}
__device__ __forceinline__ void mbar_arrive_e(uint32_t bar) {
  asm volatile(ELECT "mbarrier.arrive.shared::cta.b64 _, [%0];\n}" :: "r"(bar) : "memory");
}
__device__ __forceinline__ uint32_t clock32() { uint32_t t; asm volatile("mov.u32 %0, %%clock;" : "=r"(t)); return t; }
#define WAIT_TAIL "setp.ne.and.u32 p, %2, 0, !p;\n@p bra LAB_WAIT;\n}"
__device__ __forceinline__ void mbar_wait(uint32_t bar, uint32_t parity, uint32_t dl) {
  asm volatile("{\n.reg .pred p;\n.reg .b32 t;\nLAB_WAIT:\nmbarrier.try_wait.parity.shared::cta.b64 p, [%0], %1;\n" WAIT_TAIL
               :: "r"(bar), "r"(parity), "r"(dl) : "memory");
}
__device__ __forceinline__ void mbar_sleep(uint32_t bar, uint32_t parity, uint32_t dl) {
  asm volatile("{\n.reg .pred p;\n.reg .b32 t;\nLAB_WAIT:\nmbarrier.try_wait.parity.shared::cta.b64 p, [%0], %1, 20000;\n" WAIT_TAIL
               :: "r"(bar), "r"(parity), "r"(dl) : "memory");
}
__device__ __forceinline__ bool poll_done(bool ok, uint32_t dl) {
  return __all_sync(0xffffffffu, ok || (int)(clock32() - dl) >= 0);
}
__device__ __forceinline__ unsigned ld_relaxed(const unsigned* p) {
  unsigned v; asm volatile("ld.relaxed.gpu.global.u32 %0, [%1];" : "=r"(v) : "l"(p) : "memory"); return v;
}
__device__ __forceinline__ void red_add_e(unsigned* p, unsigned v) {
  asm volatile(ELECT "red.relaxed.gpu.global.add.u32 [%0], %1;\n}" :: "l"(p), "r"(v) : "memory");
}
__device__ __forceinline__ void wait_flag(const unsigned* p, unsigned target, uint32_t dl) {
  asm volatile("{\n.reg .pred p;\n.reg .b32 t;\n"
               "LAB_WAIT:\n"
               "ld.relaxed.gpu.global.u32 t, [%0];\n"
               "sub.s32 t, t, %1;\n"
               "setp.ge.s32 p, t, 0;\n"
               "@p bra LAB_DONE;\n"
               "mov.u32 t, %%clock;\n"
               "sub.s32 t, t, %2;\n"
               "setp.lt.s32 p, t, 0;\n"
               "@p bra LAB_WAIT;\n"
               "LAB_DONE:\n}" :: "l"(p), "r"(target), "r"(dl) : "memory");
}
__device__ __forceinline__ void wait_until(uint32_t t) { while ((int)(clock32() - t) < 0) {} }
__device__ __forceinline__ void fence_proxy_async_smem() { asm volatile("fence.proxy.async.shared::cta;" ::: "memory"); }

constexpr uint64_t EVICT_FIRST = 0x12F0000000000000ull;
template <bool STREAM = false>
__device__ __forceinline__ void tma_load_2d(uint32_t dst, const CUtensorMap* m, uint32_t bar, int c0, int c1) {
  if (STREAM)
    asm volatile(ELECT "cp.async.bulk.tensor.2d.shared::cluster.global.mbarrier::complete_tx::bytes.L2::cache_hint [%0], [%1, {%3, %4}], [%2], %5;\n}"
                 :: "r"(dst), "l"(m), "r"(bar), "r"(c0), "r"(c1), "l"(EVICT_FIRST) : "memory");
  else
    asm volatile(ELECT "cp.async.bulk.tensor.2d.shared::cluster.global.mbarrier::complete_tx::bytes [%0], [%1, {%3, %4}], [%2];\n}"
                 :: "r"(dst), "l"(m), "r"(bar), "r"(c0), "r"(c1) : "memory");
}
template <bool STREAM = false>
__device__ __forceinline__ void tma_load_3d(uint32_t dst, const CUtensorMap* m, uint32_t bar, int c0, int c1, int c2) {
  if (STREAM)
    asm volatile(ELECT "cp.async.bulk.tensor.3d.shared::cluster.global.mbarrier::complete_tx::bytes.L2::cache_hint [%0], [%1, {%3, %4, %5}], [%2], %6;\n}"
                 :: "r"(dst), "l"(m), "r"(bar), "r"(c0), "r"(c1), "r"(c2), "l"(EVICT_FIRST) : "memory");
  else
    asm volatile(ELECT "cp.async.bulk.tensor.3d.shared::cluster.global.mbarrier::complete_tx::bytes [%0], [%1, {%3, %4, %5}], [%2];\n}"
                 :: "r"(dst), "l"(m), "r"(bar), "r"(c0), "r"(c1), "r"(c2) : "memory");
}
template <bool STREAM = false>
__device__ __forceinline__ void tma_load_4d(uint32_t dst, const CUtensorMap* m, uint32_t bar, int c0, int c1, int c2, int c3) {
  if (STREAM)
    asm volatile(ELECT "cp.async.bulk.tensor.4d.shared::cluster.global.mbarrier::complete_tx::bytes.L2::cache_hint [%0], [%1, {%3, %4, %5, %6}], [%2], %7;\n}"
                 :: "r"(dst), "l"(m), "r"(bar), "r"(c0), "r"(c1), "r"(c2), "r"(c3), "l"(EVICT_FIRST) : "memory");
  else
    asm volatile(ELECT "cp.async.bulk.tensor.4d.shared::cluster.global.mbarrier::complete_tx::bytes [%0], [%1, {%3, %4, %5, %6}], [%2];\n}"
                 :: "r"(dst), "l"(m), "r"(bar), "r"(c0), "r"(c1), "r"(c2), "r"(c3) : "memory");
}
__device__ __forceinline__ void tma_store_2d(const CUtensorMap* m, uint32_t src, int c0, int c1) {
  asm volatile(ELECT "cp.async.bulk.tensor.2d.global.shared::cta.bulk_group [%0, {%2, %3}], [%1];\n}"
               :: "l"(m), "r"(src), "r"(c0), "r"(c1) : "memory");
}
__device__ __forceinline__ void tma_store_3d(const CUtensorMap* m, uint32_t src, int c0, int c1, int c2) {
  asm volatile(ELECT "cp.async.bulk.tensor.3d.global.shared::cta.bulk_group [%0, {%2, %3, %4}], [%1];\n}"
               :: "l"(m), "r"(src), "r"(c0), "r"(c1), "r"(c2) : "memory");
}
__device__ __forceinline__ void bulk_load(uint32_t dst, const void* src, uint32_t bytes, uint32_t bar) {
  asm volatile(ELECT "cp.async.bulk.shared::cluster.global.mbarrier::complete_tx::bytes [%0], [%1], %2, [%3];\n}"
               :: "r"(dst), "l"(src), "r"(bytes), "r"(bar) : "memory");
}
__device__ __forceinline__ void bulk_prefetch(const void* src, uint32_t bytes) {
  asm volatile(ELECT "cp.async.bulk.prefetch.L2.global [%0], %1;\n}" :: "l"(src), "r"(bytes) : "memory");
}
__device__ __forceinline__ void bulk_commit() { asm volatile("cp.async.bulk.commit_group;" ::: "memory"); }
__device__ __forceinline__ void bulk_wait0() { asm volatile("cp.async.bulk.wait_group 0;" ::: "memory"); }
__device__ __forceinline__ void bulk_wait_read0() { asm volatile("cp.async.bulk.wait_group.read 0;" ::: "memory"); }
__device__ __forceinline__ void prefetch_tmap(const CUtensorMap* m) { asm volatile(ELECT "prefetch.tensormap [%0];\n}" :: "l"(m) : "memory"); }
__device__ __forceinline__ void wgmma_fence() { asm volatile("wgmma.fence.sync.aligned;" ::: "memory"); }
__device__ __forceinline__ void wgmma_commit() { asm volatile("wgmma.commit_group.sync.aligned;" ::: "memory"); }
template <int N> __device__ __forceinline__ void wgmma_wait() { asm volatile("wgmma.wait_group.sync.aligned %0;" :: "n"(N) : "memory"); }
template <int R> __device__ __forceinline__ void reg_alloc() { asm volatile("setmaxnreg.inc.sync.aligned.u32 %0;" :: "n"(R)); }
template <int R> __device__ __forceinline__ void reg_dealloc() { asm volatile("setmaxnreg.dec.sync.aligned.u32 %0;" :: "n"(R)); }
__device__ __forceinline__ void bar_sync(int id, int n) { asm volatile("bar.sync %0, %1;" :: "r"(id), "r"(n) : "memory"); }
__device__ __forceinline__ void bar_arrive(int id, int n) { asm volatile("bar.arrive %0, %1;" :: "r"(id), "r"(n) : "memory"); }
__device__ __forceinline__ void sched_fence(int zero) {
  asm volatile("{\n.reg .pred p;\n.reg .b32 t;\nsetp.eq.s32 p, %0, 0;\n@p bra.uni LAB_S;\n"
               "LAB_F:\nmov.u32 t, %%clock;\nsetp.eq.u32 p, t, 0;\n@p bra LAB_F;\nLAB_S:\n}" :: "r"(zero) : "memory");
}
template <int N> __device__ __forceinline__ void fence_regs(float (&a)[N]) {
  #pragma unroll
  for (int i = 0; i < N; i++) asm volatile("" : "+f"(a[i]) :: "memory");
}
template <int N> __device__ __forceinline__ void undef_regs(float (&a)[N]) {
  #pragma unroll
  for (int i = 0; i < N; i++) asm volatile("" : "=f"(a[i]));
}

__device__ __forceinline__ uint64_t desc_from_lo(uint32_t lo) { return (uint64_t)lo | ((uint64_t)0x40000040u << 32); }
__device__ __forceinline__ uint32_t pack_bf16(float lo, float hi) {
  uint32_t r; asm("cvt.rn.bf16x2.f32 %0, %1, %2;" : "=r"(r) : "f"(hi), "f"(lo)); return r;
}
__device__ __forceinline__ uint32_t fma_bf2(uint32_t a, uint32_t b, uint32_t c) {
  uint32_t d; asm("fma.rn.bf16x2 %0, %1, %2, %3;" : "=r"(d) : "r"(a), "r"(b), "r"(c)); return d;
}
__device__ __forceinline__ float bf_lo(uint32_t v) { return __uint_as_float(v << 16); }
__device__ __forceinline__ float bf_hi(uint32_t v) { return __uint_as_float(v & 0xFFFF0000u); }
__device__ __forceinline__ float bf16_round(float x) { return bf_lo(pack_bf16(x, 0.f)); }
__device__ __forceinline__ void stmatrix_x4(uint32_t addr, uint32_t r0, uint32_t r1, uint32_t r2, uint32_t r3) {
  asm volatile("stmatrix.sync.aligned.m8n8.x4.shared.b16 [%0], {%1, %2, %3, %4};" :: "r"(addr), "r"(r0), "r"(r1), "r"(r2), "r"(r3) : "memory");
}
__device__ __forceinline__ void stmatrix_x4_t(uint32_t addr, uint32_t r0, uint32_t r1, uint32_t r2, uint32_t r3) {
  asm volatile("stmatrix.sync.aligned.m8n8.x4.trans.shared.b16 [%0], {%1, %2, %3, %4};" :: "r"(addr), "r"(r0), "r"(r1), "r"(r2), "r"(r3) : "memory");
}
__device__ __forceinline__ void stmatrix_x4_if(uint32_t addr, uint32_t r0, uint32_t r1, uint32_t r2, uint32_t r3, bool on) {
  asm volatile("{\n.reg .pred p;\nsetp.ne.b32 p, %5, 0;\n@p stmatrix.sync.aligned.m8n8.x4.shared.b16 [%0], {%1, %2, %3, %4};\n}"
               :: "r"(addr), "r"(r0), "r"(r1), "r"(r2), "r"(r3), "r"((int)on) : "memory");
}
__device__ __forceinline__ void ldmatrix_x4(uint32_t addr, uint32_t& r0, uint32_t& r1, uint32_t& r2, uint32_t& r3) {
  asm volatile("ldmatrix.sync.aligned.m8n8.x4.shared.b16 {%0, %1, %2, %3}, [%4];" : "=r"(r0), "=r"(r1), "=r"(r2), "=r"(r3) : "r"(addr) : "memory");
}
__device__ __forceinline__ void ldmatrix_x4_t(uint32_t addr, uint32_t (&r)[4]) {
  asm volatile("ldmatrix.sync.aligned.m8n8.x4.trans.shared.b16 {%0, %1, %2, %3}, [%4];" : "=r"(r[0]), "=r"(r[1]), "=r"(r[2]), "=r"(r[3]) : "r"(addr) : "memory");
}
__device__ __forceinline__ void st_rlx(void* p, uint32_t a, bool on) {
  asm volatile("{\n.reg .pred p;\nsetp.ne.b32 p, %2, 0;\n@p st.relaxed.gpu.global.u32 [%0], %1;\n}" :: "l"(p), "r"(a), "r"((int)on) : "memory");
}
__device__ __forceinline__ void st_rlx_v2(void* p, uint32_t a, uint32_t b, bool on) {
  asm volatile("{\n.reg .pred p;\nsetp.ne.b32 p, %3, 0;\n@p st.relaxed.gpu.global.v2.u32 [%0], {%1, %2};\n}" :: "l"(p), "r"(a), "r"(b), "r"((int)on) : "memory");
}
__device__ __forceinline__ uint2 ld_rlx_v2(const void* p) {
  uint2 v; asm volatile("ld.relaxed.gpu.global.v2.u32 {%0,%1}, [%2];" : "=r"(v.x), "=r"(v.y) : "l"(p) : "memory"); return v;
}
__device__ __forceinline__ void st_rlx_v4(void* p, uint32_t a, uint32_t b, uint32_t c, uint32_t d, bool on) {
  asm volatile("{\n.reg .pred p;\nsetp.ne.b32 p, %5, 0;\n@p st.relaxed.gpu.global.v4.u32 [%0], {%1, %2, %3, %4};\n}"
               :: "l"(p), "r"(a), "r"(b), "r"(c), "r"(d), "r"((int)on) : "memory");
}
__device__ __forceinline__ void st_nonzero_v4(void* p, uint32_t a, uint32_t b, uint32_t c, uint32_t d, bool on) {
  st_rlx_v4(p, max(a, 1u), max(b, 1u), max(c, 1u), max(d, 1u), on);
}
__device__ __forceinline__ uint32_t min4(const uint4& v) { return min(min(v.x, v.y), min(v.z, v.w)); }
__device__ __forceinline__ uint4 ld_rlx_v4(const void* p) {
  uint4 v; asm volatile("ld.relaxed.gpu.global.v4.u32 {%0,%1,%2,%3}, [%4];" : "=r"(v.x), "=r"(v.y), "=r"(v.z), "=r"(v.w) : "l"(p) : "memory"); return v;
}
__device__ __forceinline__ uint32_t movmatrix_t(uint32_t a) {
  uint32_t d; asm volatile("movmatrix.sync.aligned.m8n8.trans.b16 %0, %1;" : "=r"(d) : "r"(a)); return d;
}
__device__ __forceinline__ void mma16(float (&c)[4], uint32_t a0, uint32_t a1, uint32_t a2, uint32_t a3, uint32_t b0, uint32_t b1) {
  asm volatile("mma.sync.aligned.m16n8k16.row.col.f32.bf16.bf16.f32 {%0,%1,%2,%3}, {%4,%5,%6,%7}, {%8,%9}, {%0,%1,%2,%3};"
               : "+f"(c[0]), "+f"(c[1]), "+f"(c[2]), "+f"(c[3]) : "r"(a0), "r"(a1), "r"(a2), "r"(a3), "r"(b0), "r"(b1));
}
__device__ __forceinline__ void sts128(uint32_t addr, uint32_t a, uint32_t b, uint32_t c, uint32_t d) {
  asm volatile("st.shared.v4.b32 [%0], {%1,%2,%3,%4};" :: "r"(addr), "r"(a), "r"(b), "r"(c), "r"(d) : "memory");
}
__device__ __forceinline__ uint4 lds128(uint32_t addr) {
  uint4 v; asm volatile("ld.shared.v4.b32 {%0,%1,%2,%3}, [%4];" : "=r"(v.x), "=r"(v.y), "=r"(v.z), "=r"(v.w) : "r"(addr) : "memory"); return v;
}
__device__ __forceinline__ uint32_t lds32(uint32_t addr) {
  uint32_t v; asm volatile("ld.shared.b32 %0, [%1];" : "=r"(v) : "r"(addr) : "memory"); return v;
}
__device__ __forceinline__ float2 lds64f(uint32_t addr) {
  float2 v; asm volatile("ld.shared.v2.f32 {%0,%1}, [%2];" : "=f"(v.x), "=f"(v.y) : "r"(addr) : "memory"); return v;
}
__device__ __forceinline__ void sts64(uint32_t addr, uint32_t a, uint32_t b) {
  asm volatile("st.shared.v2.b32 [%0], {%1, %2};" :: "r"(addr), "r"(a), "r"(b) : "memory");
}
__device__ __forceinline__ float fast_ex2(float x) { float y; asm("ex2.approx.ftz.f32 %0, %1;" : "=f"(y) : "f"(x)); return y; }
__device__ __forceinline__ float fast_rcp(float x) { float y; asm("rcp.approx.ftz.f32 %0, %1;" : "=f"(y) : "f"(x)); return y; }
__device__ __forceinline__ float fast_rsqrt(float x) { float y; asm("rsqrt.approx.ftz.f32 %0, %1;" : "=f"(y) : "f"(x)); return y; }
__device__ __forceinline__ float silu_f(float g) { return g * fast_rcp(1.f + fast_ex2(g * -1.4426950408889634f)); }
__device__ __forceinline__ float swiglu(float h, float v) {
  float t; asm("tanh.approx.f32 %0, %1;" : "=f"(t) : "f"(h));
  const float p = h * v;
  return fmaf(p, t, p);
}

__device__ __forceinline__ void wgmma_m64n128k16_ss(float (&d)[64], uint64_t descA, uint64_t descB, int scaleD) {
  asm volatile("{\n.reg .pred p;\nsetp.ne.b32 p, %66, 0;\n"
    "wgmma.mma_async.sync.aligned.m64n128k16.f32.bf16.bf16 "
    "{%0, %1, %2, %3, %4, %5, %6, %7, %8, %9, %10, %11, %12, %13, %14, %15, "
    "%16, %17, %18, %19, %20, %21, %22, %23, %24, %25, %26, %27, %28, %29, %30, %31, "
    "%32, %33, %34, %35, %36, %37, %38, %39, %40, %41, %42, %43, %44, %45, %46, %47, "
    "%48, %49, %50, %51, %52, %53, %54, %55, %56, %57, %58, %59, %60, %61, %62, %63}, "
    "%64, %65, p, 1, 1, 0, 1;\n}\n"
    : "+f"(d[0]), "+f"(d[1]), "+f"(d[2]), "+f"(d[3]), "+f"(d[4]), "+f"(d[5]), "+f"(d[6]), "+f"(d[7]),
      "+f"(d[8]), "+f"(d[9]), "+f"(d[10]), "+f"(d[11]), "+f"(d[12]), "+f"(d[13]), "+f"(d[14]), "+f"(d[15]),
      "+f"(d[16]), "+f"(d[17]), "+f"(d[18]), "+f"(d[19]), "+f"(d[20]), "+f"(d[21]), "+f"(d[22]), "+f"(d[23]),
      "+f"(d[24]), "+f"(d[25]), "+f"(d[26]), "+f"(d[27]), "+f"(d[28]), "+f"(d[29]), "+f"(d[30]), "+f"(d[31]),
      "+f"(d[32]), "+f"(d[33]), "+f"(d[34]), "+f"(d[35]), "+f"(d[36]), "+f"(d[37]), "+f"(d[38]), "+f"(d[39]),
      "+f"(d[40]), "+f"(d[41]), "+f"(d[42]), "+f"(d[43]), "+f"(d[44]), "+f"(d[45]), "+f"(d[46]), "+f"(d[47]),
      "+f"(d[48]), "+f"(d[49]), "+f"(d[50]), "+f"(d[51]), "+f"(d[52]), "+f"(d[53]), "+f"(d[54]), "+f"(d[55]),
      "+f"(d[56]), "+f"(d[57]), "+f"(d[58]), "+f"(d[59]), "+f"(d[60]), "+f"(d[61]), "+f"(d[62]), "+f"(d[63])
    : "l"(descA), "l"(descB), "r"(scaleD));
}
__device__ __forceinline__ void wgmma_m64n256k16_rs(float (&d)[128], uint32_t a0, uint32_t a1, uint32_t a2, uint32_t a3, uint64_t descB, int scaleD) {
  asm volatile("{\n.reg .pred p;\nsetp.ne.b32 p, %133, 0;\n"
    "wgmma.mma_async.sync.aligned.m64n256k16.f32.bf16.bf16 "
    "{%0, %1, %2, %3, %4, %5, %6, %7, %8, %9, %10, %11, %12, %13, %14, %15, "
    "%16, %17, %18, %19, %20, %21, %22, %23, %24, %25, %26, %27, %28, %29, %30, %31, "
    "%32, %33, %34, %35, %36, %37, %38, %39, %40, %41, %42, %43, %44, %45, %46, %47, "
    "%48, %49, %50, %51, %52, %53, %54, %55, %56, %57, %58, %59, %60, %61, %62, %63, "
    "%64, %65, %66, %67, %68, %69, %70, %71, %72, %73, %74, %75, %76, %77, %78, %79, "
    "%80, %81, %82, %83, %84, %85, %86, %87, %88, %89, %90, %91, %92, %93, %94, %95, "
    "%96, %97, %98, %99, %100, %101, %102, %103, %104, %105, %106, %107, %108, %109, %110, %111, "
    "%112, %113, %114, %115, %116, %117, %118, %119, %120, %121, %122, %123, %124, %125, %126, %127}, "
    "{%128, %129, %130, %131}, %132, p, 1, 1, 1;\n}\n"
    : "+f"(d[0]), "+f"(d[1]), "+f"(d[2]), "+f"(d[3]), "+f"(d[4]), "+f"(d[5]), "+f"(d[6]), "+f"(d[7]),
      "+f"(d[8]), "+f"(d[9]), "+f"(d[10]), "+f"(d[11]), "+f"(d[12]), "+f"(d[13]), "+f"(d[14]), "+f"(d[15]),
      "+f"(d[16]), "+f"(d[17]), "+f"(d[18]), "+f"(d[19]), "+f"(d[20]), "+f"(d[21]), "+f"(d[22]), "+f"(d[23]),
      "+f"(d[24]), "+f"(d[25]), "+f"(d[26]), "+f"(d[27]), "+f"(d[28]), "+f"(d[29]), "+f"(d[30]), "+f"(d[31]),
      "+f"(d[32]), "+f"(d[33]), "+f"(d[34]), "+f"(d[35]), "+f"(d[36]), "+f"(d[37]), "+f"(d[38]), "+f"(d[39]),
      "+f"(d[40]), "+f"(d[41]), "+f"(d[42]), "+f"(d[43]), "+f"(d[44]), "+f"(d[45]), "+f"(d[46]), "+f"(d[47]),
      "+f"(d[48]), "+f"(d[49]), "+f"(d[50]), "+f"(d[51]), "+f"(d[52]), "+f"(d[53]), "+f"(d[54]), "+f"(d[55]),
      "+f"(d[56]), "+f"(d[57]), "+f"(d[58]), "+f"(d[59]), "+f"(d[60]), "+f"(d[61]), "+f"(d[62]), "+f"(d[63]),
      "+f"(d[64]), "+f"(d[65]), "+f"(d[66]), "+f"(d[67]), "+f"(d[68]), "+f"(d[69]), "+f"(d[70]), "+f"(d[71]),
      "+f"(d[72]), "+f"(d[73]), "+f"(d[74]), "+f"(d[75]), "+f"(d[76]), "+f"(d[77]), "+f"(d[78]), "+f"(d[79]),
      "+f"(d[80]), "+f"(d[81]), "+f"(d[82]), "+f"(d[83]), "+f"(d[84]), "+f"(d[85]), "+f"(d[86]), "+f"(d[87]),
      "+f"(d[88]), "+f"(d[89]), "+f"(d[90]), "+f"(d[91]), "+f"(d[92]), "+f"(d[93]), "+f"(d[94]), "+f"(d[95]),
      "+f"(d[96]), "+f"(d[97]), "+f"(d[98]), "+f"(d[99]), "+f"(d[100]), "+f"(d[101]), "+f"(d[102]), "+f"(d[103]),
      "+f"(d[104]), "+f"(d[105]), "+f"(d[106]), "+f"(d[107]), "+f"(d[108]), "+f"(d[109]), "+f"(d[110]), "+f"(d[111]),
      "+f"(d[112]), "+f"(d[113]), "+f"(d[114]), "+f"(d[115]), "+f"(d[116]), "+f"(d[117]), "+f"(d[118]), "+f"(d[119]),
      "+f"(d[120]), "+f"(d[121]), "+f"(d[122]), "+f"(d[123]), "+f"(d[124]), "+f"(d[125]), "+f"(d[126]), "+f"(d[127])
    : "r"(a0), "r"(a1), "r"(a2), "r"(a3), "l"(descB), "r"(scaleD));
}

constexpr uint32_t MSLOT = 32768, QSLOT = 49152;
constexpr int NM = 6;
constexpr uint32_t SM_X0 = 3 * QSLOT;
constexpr uint32_t SM_XR = SM_X0 + 16384;
constexpr uint32_t SM_STG = 196608;
constexpr uint32_t SM_XCH = SM_STG + 16384;
constexpr uint32_t SM_BAR = SM_STG + 32768;
constexpr uint32_t SM_VEC = SM_BAR + 512;
constexpr uint32_t SM_MODT = SM_VEC;
constexpr uint32_t SM_TOTAL = SM_VEC + 2048;
constexpr uint32_t B_X = SM_BAR  , B_EQ = B_X + 64, B_EM = B_EQ + 32, B_STREQ = B_EM + 48, B_STH = B_STREQ + 8, B_HREQ = B_STH + 8  , B_LN = B_HREQ + 16,
                   B_FQ = B_LN + 8, B_FM = B_FQ + 32, B_MOD = B_FM + 48  , B_GATE = B_MOD + 64, B_STFREE = B_GATE + 8, B_VEC = B_STFREE + 8  ,
                   B_FLG = B_VEC + 16  , B_H2A = B_FLG + 24, B_HFREE = B_FLG + 96  ,
                   B_END = B_HFREE + 16;
constexpr int NB_WG = 1  , NB_CONS = 3, NB_ORD = 4  ;
#define TUNE(name, value) constexpr int name = value
TUNE(PF_BYTES, 256);
TUNE(X_GAP, 250);
TUNE(AUX_HOLD, 3200);
TUNE(AUX_URG, 4);
TUNE(AUX_SLOW, 84);
TUNE(AUX_GAP, 500);
TUNE(MSEP, 6);
TUNE(ASPLIT, 2);
TUNE(WPRE, 2);
TUNE(DTAIL, 4);

struct Maps {
  CUtensorMap x, out;
  CUtensorMap o, h2, hh;
  CUtensorMap wqk, wvv, wq1, wo, w1, w3, w2;
  CUtensorMap wmod;
};

struct Ring { int st; uint32_t ph; int prev; uint32_t dl;
};
__device__ __forceinline__ void ring_next(Ring& r) { if (++r.st == NM) { r.st = 0; r.ph ^= 1; } }

__device__ __forceinline__ void retire_prev(uint32_t rel, bool on) {
  wgmma_commit();
  wgmma_wait<1>();
  if (on) mbar_arrive_e(rel);
}
struct Nop { __device__ __forceinline__ void operator()() const {} };
template <bool REL = true, class F = Nop>
__device__ __forceinline__ void mma_step(float (&acc)[64], uint32_t a, uint32_t b, bool first, uint32_t rel, F urgent = F()) {
  const uint32_t alo = (a >> 4) + (1u << 16), blo = (b >> 4) + (512u << 16);
  wgmma_fence();
  #pragma unroll
  for (int k = 0; k < 4; k++) {
    wgmma_m64n128k16_ss(acc, desc_from_lo(alo + k * 2), desc_from_lo(blo + k * 128), k > 0 || !first);
    if (k == 0) { retire_prev(rel, REL); urgent(); }
  }
  wgmma_commit();
}
__device__ __forceinline__ uint32_t m_wait(uint32_t sbase, const Ring& r) {
  mbar_wait(sbase + B_FM + 8 * r.st, r.ph, r.dl);
  return sbase + r.st * MSLOT;
}
__device__ __forceinline__ uint32_t m_prev(uint32_t sbase, const Ring& r) { return sbase + B_EM + 8 * r.prev; }
__device__ __forceinline__ void m_next(Ring& r) {
  r.prev = r.st; ring_next(r);
}
__device__ __forceinline__ void m_step(float (&acc)[64], uint32_t sbase, uint32_t wgoff, Ring& r, bool first = false) {
  const uint32_t slot = m_wait(sbase, r);
  mma_step(acc, slot + wgoff, slot + 16384, first, m_prev(sbase, r));
  m_next(r);
}

struct LnRow { uint32_t rs[2], nb[2]; };
__device__ __forceinline__ void ln_row(LnRow& l, int h, float mean, float rstd) {
  l.rs[h] = pack_bf16(rstd, rstd);
  const float nb = -mean * bf_lo(l.rs[h]);
  l.nb[h] = pack_bf16(nb, nb);
}
__device__ __forceinline__ uint32_t ln_mod(uint32_t x, const LnRow& l, int h, uint32_t c1, uint32_t s) {
  return fma_bf2(fma_bf2(x, l.rs[h], l.nb[h]), c1, s);
}

__device__ __forceinline__ uint32_t q_wait(int u, uint32_t sbase, uint32_t dl) {
  mbar_wait(sbase + B_FQ + 8 * (u & 3), (u >> 2) & 1, dl);
  return sbase + (u & 3) * QSLOT;
}
__device__ __forceinline__ uint32_t q_empty(int u, uint32_t sbase) { return sbase + B_EQ + 8 * (u & 3); }
struct Frag4 { uint32_t o[4]; };
__device__ __forceinline__ void q_load(uint32_t (&A)[16], uint4 (&p)[4], int kk, uint32_t tile, const Frag4& f, uint32_t t) {
  ldmatrix_x4(tile + f.o[kk], A[4 * kk], A[4 * kk + 1], A[4 * kk + 2], A[4 * kk + 3]);
  p[kk] = lds128(t + kk * 64);
}
__device__ __forceinline__ void q_norm(uint32_t (&A)[16], const uint4 (&p)[4], int kk, const LnRow& l) {
  A[4 * kk + 0] = ln_mod(A[4 * kk + 0], l, 0, p[kk].x, p[kk].z); A[4 * kk + 1] = ln_mod(A[4 * kk + 1], l, 1, p[kk].x, p[kk].z);
  A[4 * kk + 2] = ln_mod(A[4 * kk + 2], l, 0, p[kk].y, p[kk].w); A[4 * kk + 3] = ln_mod(A[4 * kk + 3], l, 1, p[kk].y, p[kk].w);
}
template <bool NEXT>
__device__ __forceinline__ void q_step_rs(float (&acc)[128], uint32_t (&A)[16], uint32_t (&N)[16], uint4 (&p)[4], int u, uint32_t sbase,
                                          const Frag4& f, uint32_t tab, const LnRow& l, uint32_t rot, bool keep, bool first, uint32_t dl, int wg, int zero) {
  const uint32_t slot = first ? sbase : q_wait(u, sbase, dl);
  const uint32_t blo = ((slot + 16384) >> 4) + (512u << 16) + rot * 128 + (zero << (u >> 2)), t = tab + ((u + 1) & 7) * 256;
  #pragma unroll
  for (int kk = 0; kk < 4; kk++) q_norm(A, p, kk, l);
  #pragma unroll
  for (int i = 0; i < 16; i++) asm volatile("" : "+r"(A[i]));
  if (!first) sched_fence(zero);
  if (first) {
    mbar_wait(sbase + B_GATE, 0, dl);
    PROF(6, threadIdx.x == 0);
  }
  if (!(first && wg == 0)) bar_sync(NB_ORD + wg, 256);
  wgmma_fence();
  #pragma unroll
  for (int kk = 0; kk < 4; kk++) {
    wgmma_m64n256k16_rs(acc, A[4 * kk], A[4 * kk + 1], A[4 * kk + 2], A[4 * kk + 3], desc_from_lo(blo ^ (kk * 128)), kk > 0 || !first);
    if (kk == 0) retire_prev(q_empty(u - 1, sbase), !first);
    if (NEXT && kk == 1) {
      if ((u & 1) && u < MSEP) mbar_wait(sbase + B_MOD + 4 * (u + 1), 0, dl);
      #pragma unroll
      for (int q = 0; q < 4; q++) q_load(N, p, q, slot, f, t);
    }
    if (kk == 3 && (NEXT || wg == 0)) bar_arrive(NB_ORD + (wg ^ 1), 256);
    if (kk == 1) stmatrix_x4_if(sbase + SM_STG + (u >> 3) * 16384 + (f.o[0] ^ (((u >> 1 & 3) ^ rot) << 5)), A[0], A[1], A[2], A[3], keep);
  }
  wgmma_commit();
}

typedef uint32_t Frag8[8];
template <int N> __device__ __forceinline__ void pack_half(Frag8& f, const float (&acc)[N], int off, int half) {
  #pragma unroll
  for (int e = 0; e < 8; e++) { f[e] = pack_bf16(acc[off + 4 * e + 2 * half], acc[off + 4 * e + 2 * half + 1]); asm volatile("" : "+r"(f[e])); }
}
__device__ __forceinline__ void transpose8(Frag8& f) {
  #pragma unroll
  for (int e = 0; e < 8; e++) f[e] = movmatrix_t(f[e]);
}
__device__ __forceinline__ void attn_send(const Frag8& f, int kv, uint32_t xch, int warp, uint4* halo_out, bool has_next) {
  if (warp == 3) {
    st_nonzero_v4(halo_out + kv * 64, f[0], f[1], f[2], f[3], has_next); st_nonzero_v4(halo_out + kv * 64 + 32, f[4], f[5], f[6], f[7], has_next);
  } else {
    sts128(xch + 2048 + kv * 1024, f[0], f[1], f[2], f[3]); sts128(xch + 2048 + kv * 1024 + 512, f[4], f[5], f[6], f[7]);
  }
}
template <int N>
__device__ __forceinline__ void attn_recv(uint4* p, int first, uint32_t xch, int wg, int warp, const uint4* halo_in, bool has_prev) {
  bar_sync(NB_WG + wg, 128);
  #pragma unroll
  for (int e = 0; e < N; e++)
    asm volatile("{\n.reg .pred p, q;\nsetp.ne.b32 p, %6, 0;\nsetp.ne.b32 q, %7, 0;\n"
                 "mov.b32 %0, 0;\nmov.b32 %1, 0;\nmov.b32 %2, 0;\nmov.b32 %3, 0;\n"
                 "@p ld.shared.v4.b32 {%0,%1,%2,%3}, [%4];\n@q ld.relaxed.gpu.global.v4.u32 {%0,%1,%2,%3}, [%5];\n}"
                 : "=&r"(p[e].x), "=&r"(p[e].y), "=&r"(p[e].z), "=&r"(p[e].w)
                 : "r"(xch + (first + e) * 512), "l"(halo_in + (first + e) * 32), "r"((int)(warp > 0)), "r"((int)(warp == 0 && has_prev)) : "memory");
}
template <int N>
__device__ __forceinline__ void attn_check(uint4* p, int first, bool remote, const uint4* halo_in, uint32_t dl) {
  if (remote) {
    while (true) {
      uint32_t m = ~0u;
      #pragma unroll
      for (int e = 0; e < N; e++) m = min(m, min4(p[e]));
      if (poll_done(m != 0, dl)) break;
      #pragma unroll
      for (int e = 0; e < N; e++) p[e] = ld_rlx_v4(halo_in + (first + e) * 32);
    }
  }
}
template <int SPLIT, class F>
__device__ __forceinline__ void attn_core(const Frag8& qA, const Frag8& qB, const Frag8& kA, const Frag8& kB, const Frag8& vA, const Frag8& vB,
                                          const uint4* kP, const uint4* vP, bool noprev, int lane, float (&o)[2][5][4], F late) {
  const int g = lane >> 2, qd = lane & 3;
  const bool s0 = 2 * qd > g, s1 = 2 * qd + 1 > g;
  const uint32_t msk = (s0 ? 0xFFFFu : 0u) | (s1 ? 0xFFFF0000u : 0u);
  float s[2][3][4];
  uint32_t pr[2][2];
  auto scores = [&](int h, int nb) {
    s[h][nb][0] = s[h][nb][1] = s[h][nb][2] = s[h][nb][3] = 0.f;
    #pragma unroll
    for (int kk = 0; kk < 2; kk++) {
      const int e = 4 * h + 2 * kk;
      mma16(s[h][nb], qA[e], qB[e], qA[e + 1], qB[e + 1], nb == 1 ? kA[e] : nb == 2 ? kB[e] : kk ? kP[h].z : kP[h].x,
            nb == 1 ? kA[e + 1] : nb == 2 ? kB[e + 1] : kk ? kP[h].w : kP[h].y);
    }
  };
  auto rows = [&](int h, int y) {
    constexpr float SC = 0.17677669529663687f * 1.4426950408889634f;
    const float l0 = s0 ? (y == 0 && noprev ? -INFINITY : s[h][y][2 * y]) : s[h][y + 1][2 * y];
    const float l1 = s1 ? (y == 0 && noprev ? -INFINITY : s[h][y][2 * y + 1]) : s[h][y + 1][2 * y + 1];
    float m = fmaxf(l0, l1);
    m = fmaxf(m, __shfl_xor_sync(0xffffffffu, m, 1));
    m = fmaxf(m, __shfl_xor_sync(0xffffffffu, m, 2));
    const uint32_t p = pr[h][y] = pack_bf16(fast_ex2((l0 - m) * SC), fast_ex2((l1 - m) * SC));
    #pragma unroll
    for (int m2 = 0; m2 < 2; m2++) {
      const int e = 4 * h + 2 * m2;
      float (&d)[4] = o[h][2 * m2 + y];
      d[0] = d[1] = d[2] = d[3] = 0.f;
      if (y == 0) mma16(d, m2 ? vP[h].z : vP[h].x, m2 ? vP[h].w : vP[h].y, vA[e], vA[e + 1], p & msk, p & ~msk);
      else mma16(d, vA[e], vA[e + 1], vB[e], vB[e + 1], p & msk, p & ~msk);
    }
  };
  #pragma unroll
  for (int h = 0; h < 2; h++) { scores(h, 1); scores(h, 2); if (SPLIT == 0) scores(h, 0); }
  if (SPLIT == 2) { rows(0, 1); rows(1, 1); }
  if (SPLIT) { late(); scores(0, 0); scores(1, 0); }
  #pragma unroll
  for (int h = 0; h < 2; h++) {
    if (SPLIT < 2) rows(h, 1);
    rows(h, 0);
    o[h][4][0] = o[h][4][1] = o[h][4][2] = o[h][4][3] = 0.f;
    mma16(o[h][4], 0x3F803F80u, 0u, 0u, 0x3F803F80u, pr[h][0], pr[h][1]);
  }
}
__device__ __forceinline__ void attn_store(const float (&o)[2][5][4], int h, uint32_t sbase, const Frag4& f) {
  float r[4];
  #pragma unroll
  for (int e = 0; e < 4; e++) r[e] = fast_rcp(o[h][4][e]);
  #pragma unroll
  for (int m = 0; m < 2; m++) {
    const float (&lo)[4] = o[h][2 * m], (&hi)[4] = o[h][2 * m + 1];
    stmatrix_x4_t(sbase + SM_STG + f.o[2 * h + m], pack_bf16(lo[0] * r[0], lo[1] * r[1]), pack_bf16(hi[0] * r[2], hi[1] * r[3]),
                  pack_bf16(lo[2] * r[0], lo[3] * r[1]), pack_bf16(hi[2] * r[2], hi[3] * r[3]));
  }
}

__device__ __forceinline__ void request_store(uint32_t bar) {
  fence_proxy_async_smem();
  mbar_arrive_e(bar);
}

__device__ __forceinline__ void g_quad(float (&a0)[64], float (&a1)[64], uint32_t rel2, uint32_t sbase, uint32_t wgoff, Ring& r) {
  const uint32_t x = m_wait(sbase, r);
  mma_step(a0, x + wgoff, x + 16384, false, m_prev(sbase, r), [&] { if (rel2) mbar_arrive_e(rel2); });
  m_next(r);
  const uint32_t xe = m_prev(sbase, r), y = m_wait(sbase, r);
  mma_step<false>(a1, x + wgoff, y, false, 0);
  m_next(r);
  const uint32_t z = m_wait(sbase, r);
  mma_step(a1, z + wgoff, y + 16384, false, xe);
  mma_step(a0, z + wgoff, z + 16384, false, m_prev(sbase, r));
  m_next(r);
}
template <int T>
__device__ __forceinline__ void g_piece(float (&prv)[64], int jj, int use, uint32_t sbase, const Frag4& f, uint32_t dl) {
  if (jj == 0) { mbar_wait(sbase + B_HFREE + 8 * T, use & 1, dl); fence_regs(prv); PROF(33 + 2 * use + T, threadIdx.x == 0); }
  uint32_t p[4];
  #pragma unroll
  for (int e = 0; e < 4; e++) {
    const int i = jj * 8 + e * 2;
    p[e] = pack_bf16(swiglu(prv[i], prv[i + 32]), swiglu(prv[i + 1], prv[i + 33]));
  }
  stmatrix_x4(sbase + SM_STG + T * 16384 + f.o[jj], p[0], p[1], p[2], p[3]);
  if (jj == 3) request_store(sbase + B_HREQ + 8 * T);
}
template <bool REL2, bool Q, class F>
__device__ __forceinline__ uint32_t g_ppqq(float (&p)[64], float (&q)[64], bool firstq, uint32_t rel2, uint32_t sbase, uint32_t wgoff, Ring& r, F after) {
  const uint32_t x = m_wait(sbase, r);
  mma_step(p, x + wgoff, x + 16384, false, m_prev(sbase, r), [&] { if (REL2) mbar_arrive_e(rel2); });
  m_next(r);
  after(0);
  const uint32_t xe = m_prev(sbase, r), z = m_wait(sbase, r);
  mma_step<!Q>(p, z + wgoff, z + 16384, false, xe);
  m_next(r);
  after(1);
  if (!Q) return 0;
  const uint32_t ze = m_prev(sbase, r), y = m_wait(sbase, r);
  mma_step<false>(q, x + wgoff, y, firstq, 0);
  after(2);
  mma_step(q, z + wgoff, y + 16384, false, xe);
  m_next(r);
  after(3);
  return ze;
}

__device__ __forceinline__ uint32_t bad2(uint32_t a, uint32_t b, unsigned par) {
  uint32_t d; asm("lop3.b32 %0, %1, %2, %3, 0x7E;" : "=r"(d) : "r"(a), "r"(b), "r"(par)); return d;
}
__device__ __forceinline__ uint32_t bad4(const uint4& v, unsigned par) { return bad2(v.x, v.y, par) | bad2(v.z, v.w, par); }
__device__ __forceinline__ uint32_t hi_halves(uint32_t lo, uint32_t hi) { return __byte_perm(lo, hi, 0x7632); }

__device__ __forceinline__ void gather_table(const float* src, uint32_t dst, uint32_t bar, unsigned par, uint32_t dl) {
  asm volatile("{\n.reg .pred p, e;\n.reg .b32 s<4>, c<4>, t<4>, w<4>;\n"
               "elect.sync _|e, 0xffffffff;\n"
               "LAB_POLL:\n"
               "ld.relaxed.gpu.global.v4.u32 {s0, s1, s2, s3}, [%0];\n"
               "ld.relaxed.gpu.global.v4.u32 {c0, c1, c2, c3}, [%0 + 4096];\n"
               "prmt.b32 w0, c0, c1, 0x7632;\nprmt.b32 w1, c2, c3, 0x7632;\nprmt.b32 w2, s0, s1, 0x7632;\nprmt.b32 w3, s2, s3, 0x7632;\n"
               "st.shared.v4.b32 [%1], {w0, w1, w2, w3};\n"
               "lop3.b32 t0, s0, s1, %3, 0x7E;\nlop3.b32 t1, s2, s3, %3, 0x7E;\nlop3.b32 t2, c0, c1, %3, 0x7E;\nlop3.b32 t3, c2, c3, %3, 0x7E;\n"
               "lop3.b32 t0, t0, t1, 1, 0xA8;\nlop3.b32 t2, t2, t3, 1, 0xA8;\n"
               "or.b32 t0, t0, t2;\n"
               "setp.eq.u32 p, t0, 0;\n"
               "vote.sync.all.pred p, p, 0xffffffff;\n"
               "@p bra.uni LAB_OK;\n"
               "mov.u32 t0, %%clock;\nsub.s32 t0, t0, %4;\nsetp.lt.s32 p, t0, 0;\n"
               "vote.sync.all.pred p, p, 0xffffffff;\n"
               "@p bra.uni LAB_POLL;\n"
               "LAB_OK:\n"
               "@e mbarrier.arrive.shared::cta.b64 _, [%2];\n}"
               :: "l"(src), "r"(dst), "r"(bar), "r"(par), "r"(dl) : "memory");
}

__device__ __forceinline__ int aux_col(int a, int u) { return u < 8 ? (a & 1) * 1024 + (2 * u + (a >> 1)) * 64 : 2048 + ((u - 8) * 4 + a) * 64; }
constexpr int NA = 7;
constexpr uint32_t A_FULL = SM_BAR, A_EMPTY = SM_BAR + 64, A_SUM = SM_BAR + 128, A_FREE = SM_BAR + 136, SM_RED = SM_VEC;
__device__ __forceinline__ void aux_role(const Maps& maps, const bf16* __restrict__ cvec, Mail* mail0, int zero, int a, uint32_t sbase, int wid) {
  const int tid = threadIdx.x, lane = tid & 31;
  const uint32_t dl = (clock32() + 800000000u) | 1;
  int st = 0; uint32_t ph = 0;
  if (wid == 8) {
    prefetch_tmap(&maps.wmod);
    #pragma unroll
    for (int i = 0; i < 18; i++) mbar_init_e(sbase + A_FULL + 8 * i, i < 8 ? 1 : i < 17 ? 8 : 2);
    fence_proxy_async_smem();
    bar_arrive(0, 352);
    PROF(39, lane == 0);
    #pragma unroll
    for (int i = 0; i < NA; i++) {
      mbar_expect_tx_e(sbase + A_FULL + 8 * i, 32768);
      tma_load_2d(sbase + i * MSLOT, &maps.wmod, sbase + A_FULL + 8 * i, aux_col(a, i >> 2), (i & 3) * 256);
    }
    PROF(40, lane == 0);
    #pragma unroll 1
    for (int i = NA; i < 96; i++) {
      if (i >= AUX_SLOW) wait_until(clock32() + AUX_GAP);
      if (i == 8) wait_until(dl - 800000000u + AUX_HOLD);
      mbar_wait(sbase + A_EMPTY + 8 * st, ph, dl);
      mbar_expect_tx_e(sbase + A_FULL + 8 * st, 32768);
      tma_load_2d<true>(sbase + st * MSLOT, &maps.wmod, sbase + A_FULL + 8 * st, aux_col(a, i >> 2), (i & 3) * 256);
      if (++st == NA) { st = 0; ph ^= 1; }
    }
  } else if (wid < 8) {
    const int g = lane >> 2, qd = lane & 3;
    uint32_t sc[16];
    const uint2 c = *reinterpret_cast<const uint2*>(cvec + tid * 4);
    sts64(sbase + SM_RED + tid * 8, pack_bf16(silu_f(bf_lo(c.x)), silu_f(bf_hi(c.x))), pack_bf16(silu_f(bf_lo(c.y)), silu_f(bf_hi(c.y))));
    bar_sync(0, 352);
    #pragma unroll
    for (int i = 0; i < 16; i++) sc[i] = lds32(sbase + SM_RED + ((i >> 2) * 256 + wid * 32 + (i & 3) * 8 + qd * 2) * 2);
    bar_sync(NB_CONS, 256);
    PROF(38, tid == 0);
    const uint32_t aoff = (wid * 32 + (lane & 7) + (lane >> 4) * 8) * 128 + ((((lane >> 3) & 1) ^ (lane & 7)) << 4);
    uint32_t w[2][8][4];
    auto fetch = [&](uint32_t (&f)[8][4]) {
      mbar_wait(sbase + A_FULL + 8 * st, ph, dl);
      #pragma unroll
      for (int e = 0; e < 8; e++) ldmatrix_x4_t((sbase + st * MSLOT + aoff + (e >> 2) * 2048) ^ ((e & 3) << 5), f[e]);
      if (++st == NA) { st = 0; ph ^= 1; }
    };
    #pragma unroll 1
    for (int u = 0; u < 24; u++) {
      float acc[4][4];
      #pragma unroll
      for (int m = 0; m < 4; m++) acc[m][0] = acc[m][1] = acc[m][2] = acc[m][3] = 0.f;
      fetch(w[0]);
      #pragma unroll
      for (int q = 0; q < 4; q++) {
        PROF(30 + (u & 1) * 4 + q, u < 2 && tid == 0);
        const uint32_t rel = sbase + A_EMPTY + 8 * (st == 0 ? NA - 1 : st - 1);
        if (q < 3) fetch(w[(q + 1) & 1]);
        uint32_t dep = 0;
        #pragma unroll
        for (int e = 0; e < 8; e++) dep |= w[q & 1][e][0];
        mbar_arrive_e(rel + (dep & zero));
        if (q == 1) mbar_wait(sbase + A_FREE, (u & 1) ^ 1, dl);
        #pragma unroll
        for (int e = 0; e < 8; e++) {
          const uint32_t (&f)[4] = w[q & 1][e];
          mma16(acc[e & 3], f[0], f[1], f[2], f[3], sc[4 * q + 2 * (e >> 2)], sc[4 * q + 2 * (e >> 2) + 1]);
        }
      }
      const float v0 = qd & 2 ? (qd & 1 ? acc[3][0] : acc[2][0]) : (qd & 1 ? acc[1][0] : acc[0][0]);
      const float v1 = qd & 2 ? (qd & 1 ? acc[3][2] : acc[2][2]) : (qd & 1 ? acc[1][2] : acc[0][2]);
      sts64(sbase + SM_RED + wid * 256 + (qd * 8 + g) * 8, __float_as_uint(v0), __float_as_uint(v1));
      mbar_arrive_e(sbase + A_SUM);
      if (u < AUX_URG) mbar_wait(sbase + A_FREE, u & 1, dl);
    }
  } else if (wid < 11) {
    float* const mail = &mail0->mod[(wid - 9) * 4 * 6 * D_ + 2 * lane];
    unsigned par = ld_relaxed(&mail0->flags[FL_EPOCH + (lane >> 5)]);
    bar_sync(0, 352);
    par = (par + 1) & 1;
    #pragma unroll 1
    for (int u = -2; u < 24; u++) {
      if (u >= 0) {
        const int col = aux_col(a, u);
        const float add = (col >> 10) == 1 || (col >> 10) == 4 ? 1.f : 0.f;
        const float mul = col < 3 * D_ ? 1.f : col < 5 * D_ ? 0.5f : 2.f;
        mbar_wait(sbase + A_SUM, u & 1, dl);
        float2 v[8];
        #pragma unroll
        for (int w = 0; w < 8; w++) v[w] = lds64f(sbase + SM_RED + w * 256 + lane * 8);
        const float t0 = ((v[0].x + v[1].x) + (v[2].x + v[3].x)) + ((v[4].x + v[5].x) + (v[6].x + v[7].x));
        const float t1 = ((v[0].y + v[1].y) + (v[2].y + v[3].y)) + ((v[4].y + v[5].y) + (v[6].y + v[7].y));
        mbar_arrive_e(sbase + A_FREE + (__float_as_uint(t0 + t1) & zero));
        const uint32_t w = pack_bf16((add + bf16_round(t0)) * mul, (add + bf16_round(t1)) * mul), o = __shfl_xor_sync(0xffffffffu, w, 1);
        const uint32_t m0 = (lane & 1) ? (o & 0xFFFF0000u) : (w << 16), m1 = (lane & 1) ? (w & 0xFFFF0000u) : (o << 16);
        #pragma unroll
        for (int c = 0; c < 4; c++) st_rlx_v2(mail + c * 6 * D_ + col, m0 | par, m1 | par, true);
        PROF(1 + u, tid == 288);
      }
      #pragma unroll 1
      for (int v = 2 * (u + 2); v < 2 * (u + 3) && v < 24; v++)
        #pragma unroll
        for (int c = 0; c < 4; c++) st_rlx_v2(mail + c * 6 * D_ + aux_col(a, v), par ^ 1, par ^ 1, true);
    }
    const int t = a * 64 + tid - 288;
    #pragma unroll 1
    for (int i = t; i < 16 * 16 * 256; i += 256) mail0->halo[par ^ 1][i] = make_uint4(0, 0, 0, 0);
    #pragma unroll 1
    for (int i = t; i < 16 * 8 * 64; i += 256) mail0->st2[par ^ 1][i] = make_uint4(0, 0, 0, 0);
  }
}

template <int MODE>
__global__ void __launch_bounds__(384, 1)
fused_block_kernel(const bf16* __restrict__ x, const bf16* __restrict__ cvec, const bf16* __restrict__ wmod, Mail* mail0, int zero,
                   const __grid_constant__ Maps maps) {
  extern __shared__ __align__(1024) uint8_t smem_raw[];
  const uint32_t sbase = smem_u32(smem_raw);
  const int tid = threadIdx.x, lane = tid & 31;
  PROFN(0, tid == 0);
  const int wid = __shfl_sync(0xffffffffu, tid >> 5, 0);
  const int b = cta_role<MODE>();
  if (b >= NCTA) { aux_role(maps, cvec, mail0, zero, b - NCTA, sbase, wid); return; }
  const int jg = b >> 6, mb = jg ? 31 - (b >> 2) : (b >> 2), j = 4 * jg + (b & 3);
  const uint32_t dl = (clock32() + 800000000u) | 1;
  unsigned* const flags = &mail0->flags[mb * 32];
  const int row0 = mb * 128;

  if (wid >= 8) {
    if (wid == 8) {
      #pragma unroll
      for (int i = 0; i < 8; i++) mbar_init_e(sbase + B_X + 8 * i, 1);
      fence_proxy_async_smem();
      mbar_expect_tx_e(sbase + B_X, 4096);
      bulk_load(sbase + SM_XR, x + (size_t)(row0 + j * 16) * D_, 4096, sbase + B_X);
    } else if (wid == 11) {
      #pragma unroll
      for (int i = 0; i < 12; i++) prefetch_tmap(&maps.x + i);
    } else if (wid == 9) {
      #pragma unroll
      for (uint32_t bar = B_EQ; bar < B_FM; bar += 8) mbar_init_e(sbase + bar, bar < B_FQ ? 8 : bar == B_FQ + 8 || bar == B_FQ + 24 ? 2 : 1);
      fence_proxy_async_smem();
    } else {
      #pragma unroll
      for (uint32_t bar = B_FM; bar < B_END; bar += 8) mbar_init_e(sbase + bar, 1);
      fence_proxy_async_smem();
    }
    bar_sync(0, 384);
    reg_dealloc<40>();
    PROF(92, tid == 256);
    if (wid == 8) {
      uint32_t tnext = clock32();
      #pragma unroll 1
      for (int q = 1; q < 8; q++) {
        wait_until(tnext);
        mbar_expect_tx_e(sbase + B_X + 8 * q, 4096);
        bulk_load(sbase + SM_XR + q * 4096, x + (size_t)(row0 + j * 16 + 2 * q) * D_, 4096, sbase + B_X + 8 * q);
        tnext += X_GAP;
      }
      #pragma unroll 1
      for (int u = 0; u < 16; u++) {
        const int st = u & 3;
        if (u == 1) mbar_wait(sbase + B_X + 56, 0, dl);
        if (u == 2) { mbar_wait(sbase + B_GATE, 0, dl); PROFN(60, lane == 0); }
        if (u == 3) mbar_wait(sbase + B_EQ, 0, dl);
        mbar_wait(sbase + B_EQ + 8 * st, ((u >> 2) & 1) ^ 1, dl);
        const uint32_t slot = sbase + st * QSLOT, fb = sbase + B_FQ + 8 * st;
        mbar_expect_tx_e(fb, u == 0 ? 65536 : u == 15 ? 32768 : 49152);
        if ((u & 1) && (u < MSEP || u == 15)) mbar_arrive_e(fb);
        if (u == 0) tma_load_3d(sbase + SM_X0, &maps.x, fb, 0, mb * 64, 0);
        tma_load_4d<true>(slot + 16384, &maps.wqk, fb, 0, u * 64, j, 0);
        tma_load_4d<true>(slot + 32768, &maps.wvv, fb, 0, u * 64, j, 0);
        if (u < 15) tma_load_3d(slot, &maps.x, fb, u * 64 + 64, mb * 64, 0);
      }
      const unsigned e1 = 1 + ld_relaxed(flags + FO_EPOCH);
      Ring r{0, 1, 0, dl};
      uint32_t slot, fb;
      auto acquire = [&](uint32_t bytes) {
        mbar_wait(sbase + B_EM + 8 * r.st, r.ph, dl);
        slot = sbase + r.st * MSLOT; fb = sbase + B_FM + 8 * r.st;
        mbar_expect_tx_e(fb, bytes);
        ring_next(r);
      };
      #pragma unroll 1
      for (int kt = 0; kt < 16; kt++) {
        if (kt < 5) mbar_wait(sbase + B_EQ + 8 * (kt - (kt >= 2)), 1, dl);
        if ((kt & 7) == 0) { PROF(46, lane == 0 && kt == 8); mbar_wait(sbase + B_FLG + kt, 0, dl); PROF(47, lane == 0 && kt == 8); }
        acquire(32768);
        tma_load_4d<true>(slot + 16384, &maps.wq1, fb, (j + 8) * 64, (kt & 1) * 64 + (kt & 6) * 8, (kt >> 3) * 4, 0);
        tma_load_3d(slot, &maps.hh, fb, (kt & 7) * 64, row0, kt >> 3);
      }
      PROF(82, lane == 0);
      mbar_wait(sbase + B_FLG + 16, 0, dl);
      PROF(83, lane == 0);
      #pragma unroll 1
      for (int kt = 0; kt < 8; kt++) {
        if (kt == 4) {
          acquire(32768);
          tma_load_3d(slot, &maps.x, fb, j * 128, mb * 64, 0);
          tma_load_3d(slot + 16384, &maps.x, fb, j * 128 + 64, mb * 64, 0);
        }
        acquire(32768);
        tma_load_3d<true>(slot + 16384, &maps.wo, fb, 0, kt * 64, 2 * j);
        tma_load_2d(slot, &maps.o, fb, kt * 64, row0);
      }
      acquire(16384);
      tma_load_3d<true>(slot + 16384, &maps.wo, fb, 0, (8 + j) * 64, 2 * j);
      const uint32_t oth = (0x2107654u + (0x1110000u << (4 * (j & 3)) & 0x1110000u)) ^ ((j & 4) ? 0x4444444u : 0u);
      auto deferred = [&](const CUtensorMap* map, const unsigned* flag, Ring ra, int n, int col0, int step) {
        uint32_t dst = sbase + ra.st * MSLOT, bar = sbase + B_FM + 8 * ra.st, col = col0 + (~j & 4) * step;
        asm volatile("" : "+r"(dst), "+r"(bar), "+r"(col));
        wait_flag(flag, e1 * NCTA, dl);
        tma_load_2d(dst, map, bar, col, row0);
        #pragma unroll 1
        for (int i = 1; i < n; i++) { ring_next(ra); tma_load_2d(sbase + ra.st * MSLOT, map, sbase + B_FM + 8 * ra.st, col + i * step, row0); }
      };
      {
        const Ring ra = r;
        #pragma unroll 1
        for (int i = 0; i < 7; i++) {
          const int kt = 8 + (oth >> (4 * i) & 7);
          acquire(32768);
          tma_load_3d<true>(slot + 16384, &maps.wo, fb, 0, kt * 64, 2 * j);
          if (i == WPRE - 1) { deferred(&maps.o, &mail0->flags[FL_O], ra, WPRE, 512, 64); PROFN(61, lane == 0); }
          if (i >= WPRE) tma_load_2d(slot, &maps.o, fb, kt * 64, row0);
        }
      }
      uint64_t ord = (uint64_t)(2 * oth) | (uint64_t)(2 * oth + 0x1111111u) << 28;
      auto load_b = [&](uint32_t dst, int col, int kt) {
        tma_load_2d<true>(dst, &maps.w1, fb, col, kt * 64);
        tma_load_2d<true>(dst + 8192, &maps.w3, fb, col, kt * 64);
      };
      Ring ra = r;
      #pragma unroll 1
      for (int i = -2; i < 5; i++) {
        const int kt = i < 0 ? 2 * j + i + 2 : 2 * ((~j & 4) + min(i, 3));
        if (i == 0) ra = r;
        acquire(32768);
        load_b(slot + 16384, i < 0 || i == 3 ? (8 + j) * 64 : j * 64, kt);
        if (i < 0 || i == 3) load_b(slot, i < 0 ? j * 64 : (8 + j) * 64, i < 0 ? kt : kt - 2);
      }
      deferred(&maps.h2, &mail0->flags[FL_H2], ra, 3, 0, 128);
      tma_load_2d(slot, &maps.h2, fb, ((~j & 4) + 3) * 128, row0);
      PROFN(62, lane == 0);
      mbar_arrive_e(sbase + B_H2A);
      #pragma unroll 1
      for (int q = 2; q < 31; q++) {
        const int pr = q >> 3, w = q & 7, col = (16 * pr + j) * 64 + (w == 7 ? 512 : 0), y = pr == 3 ? 0 : w == 0 || w >= 6 ? 2 : 1;
        if (q == 7) ord = (j & 4) ? 0xFEDCBA9875316420ull : 0x76543210FDB9ECA8ull;
        const uint32_t kk = (uint32_t)(ord >> (w == 7 ? 0 : 8 * w + (pr == 0 ? 0 : 8)));
        const int k0 = kk & 15, k1 = kk >> 4 & 15;
        #pragma unroll
        for (int t = 1; t <= 2; t++) {
          if (t == 2 && q == 3) mbar_wait(sbase + B_FLG + 32, 0, dl);
          acquire(32768);
          load_b(slot + 16384, col, t == 1 ? k0 : k1);
          tma_load_2d(slot, &maps.h2, fb, (t == 1 ? k0 : k1) * 64, row0);
          if (t == y) {
            acquire(32768);
            load_b(slot, col + 512, k0);
            load_b(slot + 16384, col + 512, k1);
          }
        }
      }
      #pragma unroll 1
      for (int kt = 0; kt < 56; kt++) {
        if ((kt & 7) == 0) mbar_wait(sbase + B_FLG + 40 + kt, 0, dl);
        acquire(32768);
        tma_load_3d(slot + 16384, &maps.w2, fb, 0, kt * 64, 2 * j);
        tma_load_3d(slot, &maps.hh, fb, (kt & 7) * 64, row0, kt >> 3);
      }
    } else {
      const unsigned e1 = 1 + ld_relaxed(wid == 9 ? flags + FO_EPOCH : &mail0->flags[FL_EPOCH]), par = e1 & 1;
      if (wid == 9) {
        #pragma unroll 1
        for (int n = 0; n < 12; n++) {
          if (n == 4) {
            mbar_wait(sbase + B_STH, 0, dl);
            tma_store_2d(&maps.h2, sbase + SM_STG, j * 128, row0);
            bulk_commit();
            bulk_wait0();
            red_add_e(&mail0->flags[FL_H2], 1);
            PROF(84, lane == 0);
            mbar_wait(sbase + B_H2A, 0, dl);
          }
          const int ht = (n - 5) & 1;
          if (n >= 1 && n <= 4) mbar_wait(sbase + B_STREQ, n & 1, dl);
          else mbar_sleep(n == 0 ? sbase + B_STREQ : sbase + B_HREQ + 8 * ht, n == 0 ? 0 : ((n - 5) >> 1) & 1, dl);
          if (n == 0) fence_proxy_async_smem();
          if (n == 2 || n == 3) tma_store_2d(&maps.o, sbase + SM_STG, (j + 8 * (n - 2)) * 64, row0);
          else if (n == 4) tma_store_2d(&maps.h2, sbase + SM_STG + 16384, j * 128 + 64, row0);
          else tma_store_3d(&maps.hh, sbase + SM_STG + (n < 2 ? n : ht) * 16384, j * 64, row0, n < 2 ? n : n - 5);
          bulk_commit();
          bulk_wait0();
          red_add_e(n == 3 ? &mail0->flags[FL_O] : flags + FO_CNT + n, 1);
          mbar_arrive_e(n < 4 ? sbase + B_STFREE : sbase + B_HFREE + 8 * ht);
          if (n == 4) mbar_arrive_e(sbase + B_HFREE);
          PROFN(70 + n, lane == 0 && n > 0); PROF(85, lane == 0 && n == 0);
          if (n != 3) { wait_flag(flags + FO_CNT + n, e1 * 8, dl); mbar_arrive_e(sbase + B_FLG + 8 * n); }
        }
      } else {
        mbar_wait(sbase + B_X + 24, 0, dl);
        const float* const mail = &mail0->mod[(b & 7) * 6 * D_ + lane * 4];
        if (wid == 10) {
          #pragma unroll 1
          for (int p = 0; p < 8; p++) {
            if (p >= 2) mbar_wait(p == 2 ? q_empty(0, sbase) : q_empty(2 * p - 5, sbase), p == 2 ? 0 : ((2 * p - 5) >> 2) & 1, dl);
            gather_table(mail + p * 128, sbase + SM_MODT + (p & 3) * 512 + ((lane * 16) ^ ((j >> 1) << 6)), 2 * p - 1 < MSEP ? sbase + B_MOD + 8 * p : sbase + B_FQ + 8 * ((2 * p - 1) & 3), par, dl);
            PROF(63 + p, lane == 0 && p < 7);
          }
          const uint32_t vdst = sbase + SM_VEC + (lane >> 3) * 64 + (lane & 3) * 16 + ((lane >> 2) & 1) * 8;
          #pragma unroll 1
          for (int v = 0; v < 2; v++) {
            mbar_sleep(sbase + B_FLG + 16 + 24 * v, 0, dl);
            uint4 m[3];
            while (true) {
              #pragma unroll
              for (int e = 0; e < 3; e++) m[e] = ld_rlx_v4(mail + (2 + v + e) * 1024 + j * 128);
              if (poll_done(((bad4(m[0], par) | bad4(m[1], par) | bad4(m[2], par)) & 1) == 0, dl)) break;
              __nanosleep(200);
            }
            #pragma unroll
            for (int e = 0; e < 3; e++) sts64(vdst + (v + e) * 256, hi_halves(m[e].x, m[e].y), hi_halves(m[e].z, m[e].w));
            mbar_arrive_e(sbase + B_VEC + 8 * v);
            PROF(70, lane == 0 && v == 0);
          }
        } else {
          mbar_wait(sbase + B_LN, 0, dl);
          red_add_e(&mail0->flags[FL_LN1], 1);
          wait_flag(&mail0->flags[FL_LN1], e1 * NCTA, dl);
          mbar_arrive_e(sbase + B_GATE);
          PROF(41, lane == 0);
        }
      }
    }
  } else {
    const int wg = wid >> 2, warp = wid & 3;
    const int g = lane >> 2, qd = lane & 3;
    bulk_prefetch(wmod + (size_t)(b * 8 + wid) * (6 * D_), PF_BYTES);
    bulk_prefetch(wmod + (size_t)(b * 8 + wid) * (6 * D_) + D_, PF_BYTES);
    bar_sync(0, 384);
    bulk_prefetch(wmod + (size_t)(b * 8 + wid) * (6 * D_) + PF_BYTES / 2, PF_BYTES);
    bulk_prefetch(wmod + (size_t)(b * 8 + wid) * (6 * D_) + PF_BYTES / 2 + D_, PF_BYTES);
    const unsigned e1 = 1 + ld_relaxed(flags + FO_EPOCH), par = e1 & 1;
    reg_alloc<232>();
    PROF(1, tid == 0);
    const uint32_t wgoff = wg * 8192;
    const uint32_t frag0 = wid * 2048 + (lane & 15) * 128 + (((lane >> 4) ^ (lane & 7)) << 4);
    const uint32_t slab = sbase + SM_STG + wid * 2048;

    LnRow ln;
    {
      uint2* const lmail = &mail0->ln1[(mb * 8 + (wid & 1) * 4 + (j >> 1)) * 16 + (j & 1) * 8 + (wid >> 1) + (lane & 1) * 4];
      st_rlx_v2(lmail, par ^ 1, par ^ 1, lane < 2);
      float sm = 0.f, qm = 0.f, so = 0.f, qo = 0.f;
      #pragma unroll
      for (int h = 0; h < 2; h++) {
        sm = so; qm = qo;
        float s[2] = {0.f, 0.f}, q2[2] = {0.f, 0.f};
        mbar_wait(sbase + B_X + 8 * (4 * h + (wid >> 1)), 0, dl);
        PROF(3, tid == 224); PROF(93, tid == 0);
        #pragma unroll
        for (int c = 0; c < 4; c++) {
          const uint4 v = lds128(sbase + SM_XR + h * 16384 + wid * 2048 + c * 512 + lane * 16);
          const uint32_t vv[4] = {v.x, v.y, v.z, v.w};
          #pragma unroll
          for (int e = 0; e < 4; e++) {
            const float lo = bf_lo(vv[e]), hi = bf_hi(vv[e]);
            s[0] += lo; s[1] += hi; q2[0] = fmaf(lo, lo, q2[0]); q2[1] = fmaf(hi, hi, q2[1]);
          }
        }
        so = s[0] + s[1]; qo = q2[0] + q2[1];
      }
      const bool odd = lane & 1;
      { const float a = odd ? so : sm, c = odd ? qo : qm;
        sm = a + __shfl_xor_sync(0xffffffffu, odd ? sm : so, 1); qm = c + __shfl_xor_sync(0xffffffffu, odd ? qm : qo, 1); }
      #pragma unroll
      for (int o = 2; o < 32; o <<= 1) { sm += __shfl_xor_sync(0xffffffffu, sm, o); qm += __shfl_xor_sync(0xffffffffu, qm, o); }
      sm *= (1.f / D_);
      ln_row(ln, 0, sm, fast_rsqrt(fmaxf(qm * (1.f / D_) - sm * sm, 0.f) + 1e-5f));
      st_rlx_v2(lmail, (ln.rs[0] << 16) | par, (ln.nb[0] << 16) | par, lane < 2);
      mbar_arrive_e(sbase + B_LN);
      PROF(4, tid == 224);
    }

    uint4* const halo_out = mail0->halo[par] + ((mb * 16 + j) * 2 + wg) * 128 + lane;
    const uint4* const halo_in = halo_out - 16 * 256;
    const uint32_t xch = sbase + SM_XCH + (tid >> 5) * 2048 + lane * 16;
    const bool noprev = mb == 0 && warp == 0, remote = mb > 0 && warp == 0;
    float a0[64], a1[64];
    uint32_t x2[32];
    Ring r{zero, 0, 0, dl};
    Frag8 qA, qB, kA, kB, vA, vB, wA, wB;
    {
      float acc[128];
      uint32_t A0[16], A1[16];
      undef_regs(acc);
      const uint32_t tab = sbase + SM_MODT + qd * 16;
      uint4 p[4];
      const uint32_t rot = j >> 1;
      Frag4 fq;
      #pragma unroll
      for (int q = 0; q < 4; q++) fq.o[q] = frag0 ^ ((q ^ rot) << 5);
      mbar_wait(sbase + B_LN, 0, dl);
      const uint2* const lin = &mail0->ln1[(mb * 8 + wid) * 16 + g];
      uint2 v0, v1;
      q_wait(0, sbase, dl);
      #pragma unroll
      for (int kk = 0; kk < 4; kk++) ldmatrix_x4(sbase + SM_X0 + fq.o[kk], A0[4 * kk], A0[4 * kk + 1], A0[4 * kk + 2], A0[4 * kk + 3]);
      do { v0 = ld_rlx_v2(lin); v1 = ld_rlx_v2(lin + 8); } while (!poll_done(((bad2(v0.x, v0.y, par) | bad2(v1.x, v1.y, par)) & 1) == 0, dl));
      ln.rs[0] = hi_halves(v0.x, v0.x); ln.nb[0] = hi_halves(v0.y, v0.y); ln.rs[1] = hi_halves(v1.x, v1.x); ln.nb[1] = hi_halves(v1.y, v1.y);
      mbar_wait(sbase + B_MOD, 0, dl);
      #pragma unroll
      for (int kk = 0; kk < 4; kk++) p[kk] = lds128(tab + kk * 64);
      PROF(5, tid == 0);
      q_step_rs<true>(acc, A0, A1, p, 0, sbase, fq, tab, ln, rot, !(j & 1), true, dl, wg, zero);
      #pragma unroll
      for (int u = 1; u < 15; u += 2) {
        q_step_rs<true>(acc, A1, A0, p, u, sbase, fq, tab, ln, rot, j & 1, false, dl, wg, zero);
        q_step_rs<true>(acc, A0, A1, p, u + 1, sbase, fq, tab, ln, rot, !(j & 1), false, dl, wg, zero);
        if (u == 7) mbar_arrive_e(sbase + B_STREQ);
      }
      q_step_rs<false>(acc, A1, A0, p, 15, sbase, fq, tab, ln, rot, j & 1, false, dl, wg, zero);
      PROF(7, tid == 0);
      mbar_wait(sbase + B_STFREE, 0, dl);
      request_store(sbase + B_STREQ);
      wgmma_wait<0>();
      undef_regs(a0);
      { const uint32_t slot = m_wait(sbase, r); mma_step(a0, slot + wgoff, slot + 16384, true, q_empty(15, sbase)); m_next(r); }
      fence_regs(acc);
      PROF(8, tid == 0);
      sched_fence(zero);
      pack_half(vB, acc, 64, 1); transpose8(vB);
      m_step(a0, sbase, wgoff, r);
      sched_fence(zero);
      pack_half(kB, acc, 32, 1);
      attn_send(vB, 1, xch - 16384, warp, halo_out, mb < 15); attn_send(kB, 0, xch - 16384, warp, halo_out, mb < 15);
      m_step(a0, sbase, wgoff, r);
      sched_fence(zero);
      pack_half(qA, acc, 0, 0); pack_half(qB, acc, 0, 1); pack_half(kA, acc, 32, 0); pack_half(wB, acc, 96, 1); pack_half(wA, acc, 96, 0);
      m_step(a0, sbase, wgoff, r);
      sched_fence(zero);
      pack_half(vA, acc, 64, 0); transpose8(vA);
    }
    uint4 wP[2];
    Frag4 frag;
    #pragma unroll
    for (int q = 0; q < 4; q++) frag.o[q] = frag0 ^ (q << 5);
    {
      m_step(a0, sbase, wgoff, r);
      uint4 pv[4];
      attn_recv<4>(pv, 0, xch - 16384, wg, warp, halo_in, mb > 0);
      m_step(a0, sbase, wgoff, r);
      mbar_wait(sbase + B_STFREE, 1, dl);
      transpose8(wB);
      m_step(a0, sbase, wgoff, r);
      attn_check<4>(pv, 0, remote, halo_in, dl);
      wgmma_wait<0>();
      PROF(9, tid == 0);
      float o[2][5][4];
      sched_fence(zero);
      attn_core<0>(qA, qB, kA, kB, vA, vB, pv, pv + 2, noprev, lane, o, Nop());
      attn_store(o, 0, sbase, frag);
      attn_store(o, 1, sbase, frag);
      request_store(sbase + B_STREQ);
      bar_sync(NB_CONS, 256);
      PROF(10, tid == 0);
      m_step(a0, sbase, wgoff, r);
      sched_fence(zero);
      attn_send(wB, 1, xch, warp, halo_out + 8 * 256, mb < 15);
      m_step(a0, sbase, wgoff, r);
      sched_fence(zero);
      transpose8(wA);
      #pragma unroll 1
      for (int i = 9; i < 15; i++) m_step(a0, sbase, wgoff, r);
      attn_recv<2>(wP, 2, xch, wg, warp, halo_in + 8 * 256, mb > 0);
      m_step(a0, sbase, wgoff, r);
    }
    {
      undef_regs(a1);
      {
        const uint32_t slot = m_wait(sbase, r);
        mma_step(a1, slot + wgoff, slot + 16384, true, m_prev(sbase, r), [&] {
          fence_regs(a0);
          pack_half(kB, a0, 32, 1);
          attn_send(kB, 0, xch, warp, halo_out + 8 * 256, mb < 15);
        });
        m_next(r);
      }
      PROF(14, tid == 0);
      sched_fence(zero);
      pack_half(kA, a0, 32, 0); pack_half(qA, a0, 0, 0); pack_half(qB, a0, 0, 1);
      m_step(a1, sbase, wgoff, r);
      attn_check<2>(wP, 2, remote, halo_in + 8 * 256, dl);
      uint4 kP[2];
      attn_recv<2>(kP, 0, xch, wg, warp, halo_in + 8 * 256, mb > 0);
      m_step(a1, sbase, wgoff, r);
      if (ASPLIT == 0) attn_check<2>(kP, 0, remote, halo_in + 8 * 256, dl);
      wgmma_wait<0>();
      PROF(15, tid == 0);
      float o[2][5][4];
      mbar_wait(sbase + B_STFREE, 0, dl);
      attn_core<ASPLIT>(qA, qB, kA, kB, wA, wB, kP, wP, noprev, lane, o, [&] { attn_check<2>(kP, 0, remote, halo_in + 8 * 256, dl); });
      attn_store(o, 0, sbase, frag);
      attn_store(o, 1, sbase, frag);
      request_store(sbase + B_STREQ);
      bar_sync(NB_CONS, 256);
      PROF(16, tid == 0);
      auto residual = [&] {
        const uint32_t xs = m_wait(sbase, r), xe = sbase + B_EM + 8 * r.st;
        ring_next(r);
        #pragma unroll
        for (int t = 0; t < 2; t++) {
          #pragma unroll
          for (int jj = 4 * t; jj < 4 * t + 4; jj++) ldmatrix_x4(xs + t * 16384 + frag.o[jj & 3], x2[4 * jj], x2[4 * jj + 1], x2[4 * jj + 2], x2[4 * jj + 3]);
          if (t == 1) {
            uint32_t dep = 0;
            #pragma unroll
            for (int jj = 0; jj < 8; jj++) dep |= x2[4 * jj];
            mbar_arrive_e(xe + (dep & zero));
          }
          m_step(a1, sbase, wgoff, r);
        }
      };
      m_step(a1, sbase, wgoff, r);
      residual();
      #pragma unroll 1
      for (int i = 6; i < 8; i++) m_step(a1, sbase, wgoff, r);
      mma_step(a1, sbase + SM_STG + wgoff, m_wait(sbase, r) + 16384, false, m_prev(sbase, r));
      m_next(r);
      PROF(17, tid == 0);
      uint4* const sm = mail0->st2[par] + (mb * 8 + wid) * 64 + g;
      st_rlx_v4(sm + j * 8, 0, 0, 0, 0, qd == (g >> 1));
      #pragma unroll 1
      for (int i = 0; i < 7; i++) { m_step(a1, sbase, wgoff, r); PROF(42, tid == 0 && i == 0); }
      PROF(45, tid == 0);
      mbar_wait(sbase + B_VEC, 0, dl);
      mbar_wait(sbase + B_STFREE, 1, dl);
      const uint32_t vec = sbase + SM_VEC + qd * 16;
      uint4 ga[4];
      #pragma unroll
      for (int q = 0; q < 4; q++) ga[q] = lds128(vec + q * 64);
      wgmma_wait<0>();
      mbar_arrive_e(m_prev(sbase, r));
      fence_regs(a1);
      PROF(18, tid == 0);
      float gl[4] = {0.f, 0.f, 0.f, 0.f}, gh[4] = {0.f, 0.f, 0.f, 0.f};
      #pragma unroll
      for (int jj = 0; jj < 8; jj++) {
        uint32_t* v = &x2[4 * jj];
        const uint32_t wl = (jj & 1) ? ga[jj >> 1].z : ga[jj >> 1].x, wh = (jj & 1) ? ga[jj >> 1].w : ga[jj >> 1].y;
        #pragma unroll
        for (int e = 0; e < 4; e++) v[e] = fma_bf2(e & 2 ? wh : wl, pack_bf16(a1[8 * jj + 2 * e], a1[8 * jj + 2 * e + 1]), v[e]);
        mma16(gl, v[0], 0x3F803F80u, v[2], 0x3F803F80u, v[0], v[2]);
        mma16(gh, v[1], 0x3F803F80u, v[3], 0x3F803F80u, v[1], v[3]);
      }
      st_nonzero_v4(sm + j * 8, __float_as_uint(g & 1 ? gl[3] : gl[2]), __float_as_uint(g & 1 ? gl[1] : gl[0]),
                __float_as_uint(g & 1 ? gh[3] : gh[2]), __float_as_uint(g & 1 ? gh[1] : gh[0]), qd == (g >> 1));
      float s[2], q2[2];
      PROF(19, tid == 0);
      uint4 sb[4], cb[4];
      #pragma unroll
      for (int q = 0; q < 4; q++) { sb[q] = lds128(vec + 256 + q * 64); cb[q] = lds128(vec + 512 + q * 64); }
      uint4 p0, p1;
      while (true) {
        p0 = ld_rlx_v4(sm + qd * 16); p1 = ld_rlx_v4(sm + qd * 16 + 8);
        if (poll_done(min(min4(p0), min4(p1)) != 0, dl)) break;
      }
      PROF(20, tid == 0);
      s[0] = __uint_as_float(p0.x) + __uint_as_float(p1.x); q2[0] = __uint_as_float(p0.y) + __uint_as_float(p1.y);
      s[1] = __uint_as_float(p0.z) + __uint_as_float(p1.z); q2[1] = __uint_as_float(p0.w) + __uint_as_float(p1.w);
      #pragma unroll
      for (int o2 = 1; o2 <= 2; o2 <<= 1)
        #pragma unroll
        for (int h = 0; h < 2; h++) { s[h] += __shfl_xor_sync(0xffffffffu, s[h], o2); q2[h] += __shfl_xor_sync(0xffffffffu, q2[h], o2); }
      #pragma unroll
      for (int h = 0; h < 2; h++) {
        const float m = s[h] * (1.f / D_);
        ln_row(ln, h, m, fast_rsqrt(fmaxf(q2[h] * (1.f / D_) - m * m, 0.f) + 1e-5f));
      }
      #pragma unroll
      for (int jj = 0; jj < 8; jj++) {
        const uint32_t cl = (jj & 1) ? cb[jj >> 1].z : cb[jj >> 1].x, ch = (jj & 1) ? cb[jj >> 1].w : cb[jj >> 1].y;
        const uint32_t sl = (jj & 1) ? sb[jj >> 1].z : sb[jj >> 1].x, sh = (jj & 1) ? sb[jj >> 1].w : sb[jj >> 1].y;
        stmatrix_x4(sbase + SM_STG + (jj >> 2) * 16384 + frag.o[jj & 3], ln_mod(x2[4 * jj], ln, 0, cl, sl), ln_mod(x2[4 * jj + 1], ln, 1, cl, sl),
                    ln_mod(x2[4 * jj + 2], ln, 0, ch, sh), ln_mod(x2[4 * jj + 3], ln, 1, ch, sh));
        if (jj == 3) { request_store(sbase + B_STH); sched_fence(zero); }
      }
      request_store(sbase + B_STREQ);
      bar_sync(NB_WG + wg, 128);
      PROF(21, tid == 0);
    }

    undef_regs(a0);
    #pragma unroll
    for (int t = 0; t < 2; t++) {
      const uint32_t slot = m_wait(sbase, r);
      if (t == 0) mma_step<false>(a0, sbase + SM_STG + wgoff, slot, true, 0);
      else mma_step(a0, sbase + SM_STG + 16384 + wgoff, slot, false, m_prev(sbase, r));
      mma_step<false>(a1, sbase + SM_STG + t * 16384 + wgoff, slot + 16384, t == 0, 0);
      m_next(r);
    }
    PROF(22, tid == 0);
    #pragma unroll 1
    for (int i = 0; i < 2; i++) m_step(a0, sbase, wgoff, r);
    uint32_t held = 0;
    #pragma unroll 1
    for (int pr = 0; pr < 3; pr++) {
      #pragma unroll 1
      for (int i = 0; i < 5; i++) { g_quad(a0, a1, held, sbase, wgoff, r); held = 0; }
      held = g_ppqq<false, true>(a0, a1, false, 0, sbase, wgoff, r, [&](int i) { if (i >= 2) g_piece<0>(a0, i - 2, pr, sbase, frag, dl); });
      held = g_ppqq<true, true>(a1, a0, true, held, sbase, wgoff, r,
                                [&](int i) { if (i < 2) g_piece<0>(a0, i + 2, pr, sbase, frag, dl); else g_piece<1>(a1, i - 2, pr, sbase, frag, dl); });
      if (pr == 2) break;
      held = g_ppqq<true, true>(a0, a1, true, held, sbase, wgoff, r, [&](int i) { if (i < 2) g_piece<1>(a1, i + 2, pr, sbase, frag, dl); });
    }
    g_ppqq<true, false>(a0, a1, false, held, sbase, wgoff, r, [&](int i) { g_piece<1>(a1, i + 2, 2, sbase, frag, dl); });
    #pragma unroll 1
    for (int i = 4; i < 15; i++) m_step(a0, sbase, wgoff, r);
    m_step(a0, sbase, wgoff, r);
    #pragma unroll
    for (int jj = 0; jj < 4; jj++) { m_step(a1, sbase, wgoff, r, jj == 0); g_piece<0>(a0, jj, 3, sbase, frag, dl); }
    #pragma unroll 1
    for (int i = 4; i < 56 - DTAIL; i++) m_step(a1, sbase, wgoff, r);
    if (DTAIL) {
      if (wg == 1) { wgmma_wait<0>(); mbar_arrive_e(m_prev(sbase, r)); bar_sync(NB_ORD, 256); }
      #pragma unroll 1
      for (int i = 0; i < DTAIL; i++) {
        const uint32_t slot = m_wait(sbase, r);
        const uint32_t alo = ((slot + wgoff) >> 4) + (1u << 16), blo = ((slot + 16384) >> 4) + (512u << 16);
        wgmma_fence();
        #pragma unroll
        for (int k = 0; k < 4; k++) wgmma_m64n128k16_ss(a1, desc_from_lo(alo + k * 2), desc_from_lo(blo + k * 128), true);
        wgmma_commit();
        ring_next(r);
      }
      if (wg == 0) bar_arrive(NB_ORD, 256);
    }
    {
      mbar_wait(sbase + B_HFREE, 0, dl);
      mbar_wait(sbase + B_HFREE + 8, 1, dl);
      mbar_wait(sbase + B_VEC + 8, 0, dl);
      uint4 gb[4];
      #pragma unroll
      for (int q = 0; q < 4; q++) gb[q] = lds128(sbase + SM_VEC + 768 + qd * 16 + q * 64);
      wgmma_wait<0>();
      fence_regs(a1);
      PROF(50, tid == 128);
      #pragma unroll
      for (int t = 0; t < 2; t++) {
        #pragma unroll
        for (int jj = 4 * t; jj < 4 * t + 4; jj++) {
          const uint32_t gl = (jj & 1) ? gb[jj >> 1].z : gb[jj >> 1].x, gh = (jj & 1) ? gb[jj >> 1].w : gb[jj >> 1].y;
          const int i = 8 * jj;
          stmatrix_x4(sbase + SM_STG + t * 16384 + frag.o[jj & 3],
                      fma_bf2(gl, pack_bf16(a1[i], a1[i + 1]), x2[4 * jj]), fma_bf2(gl, pack_bf16(a1[i + 2], a1[i + 3]), x2[4 * jj + 1]),
                      fma_bf2(gh, pack_bf16(a1[i + 4], a1[i + 5]), x2[4 * jj + 2]), fma_bf2(gh, pack_bf16(a1[i + 6], a1[i + 7]), x2[4 * jj + 3]));
        }
        fence_proxy_async_smem();
        tma_store_3d(&maps.out, slab + t * 16384, j * 128 + t * 64, mb * 64 + warp * 16, wg);
      }
      bulk_commit();
      st_rlx(tid == 0 ? flags + FO_EPOCH : &mail0->flags[FL_EPOCH], e1, j == 0 && (tid == 0 || (tid == 1 && mb == 0)));
      bulk_wait_read0();
      PROFN(51, tid == 128);
    }
  }
}

typedef CUresult (*PFN_encodeTiled)(CUtensorMap*, CUtensorMapDataType, cuuint32_t, void*, const cuuint64_t*, const cuuint64_t*,
                                    const cuuint32_t*, const cuuint32_t*, CUtensorMapInterleave, CUtensorMapSwizzle,
                                    CUtensorMapL2promotion, CUtensorMapFloatOOBfill);

void encode(PFN_encodeTiled fn, CUtensorMap* m, const void* ptr, int rank, const cuuint64_t* dims, const cuuint64_t* strides,
            const cuuint32_t* box) {
  const cuuint32_t es[5] = {1, 1, 1, 1, 1};
  fn(m, CU_TENSOR_MAP_DATA_TYPE_BFLOAT16, rank, const_cast<void*>(ptr), dims, strides, box, es, CU_TENSOR_MAP_INTERLEAVE_NONE,
     CU_TENSOR_MAP_SWIZZLE_128B, CU_TENSOR_MAP_L2_PROMOTION_L2_256B, CU_TENSOR_MAP_FLOAT_OOB_FILL_NONE);
}
void map2d(PFN_encodeTiled fn, CUtensorMap* m, const void* ptr, int cols, int rows, int boxrows) {
  const cuuint64_t dims[2] = {(cuuint64_t)cols, (cuuint64_t)rows}, strides[1] = {(cuuint64_t)cols * 2};
  const cuuint32_t box[2] = {64, (cuuint32_t)boxrows};
  encode(fn, m, ptr, 2, dims, strides, box);
}
void map_w2chunk(PFN_encodeTiled fn, CUtensorMap* m, const void* ptr, int cols, int rows) {
  const cuuint64_t dims[3] = {64, (cuuint64_t)rows, (cuuint64_t)cols / 64}, strides[2] = {(cuuint64_t)cols * 2, 128};
  const cuuint32_t box[3] = {64, 64, 2};
  encode(fn, m, ptr, 3, dims, strides, box);
}
void map_parity(PFN_encodeTiled fn, CUtensorMap* m, const void* ptr, int boxpairs, int boxpar) {
  const cuuint64_t dims[3] = {D_, S_ / 2, 2}, strides[2] = {D_ * 4, D_ * 2};
  const cuuint32_t box[3] = {64, (cuuint32_t)boxpairs, (cuuint32_t)boxpar};
  encode(fn, m, ptr, 3, dims, strides, box);
}

}

extern "C" void kernel_launch(void* const* d_in, const int* in_sizes, int n_in, void* d_out, int out_size) {
  (void)in_sizes; (void)n_in; (void)out_size;
  const bf16* x = (const bf16*)d_in[0];
  const bf16* wqkv = (const bf16*)d_in[1];
  const bf16* wo = (const bf16*)d_in[2];
  const bf16* w1 = (const bf16*)d_in[4];
  const bf16* w3 = (const bf16*)d_in[5];
  const bf16* w2 = (const bf16*)d_in[6];
  const bf16* cvec = (const bf16*)d_in[7];
  const bf16* w_mod = (const bf16*)d_in[8];

  static PFN_encodeTiled fn = nullptr;
  static Maps maps;
  static const void* cached[8] = {};
  static int sms = 0;
  static void* mail = nullptr;
  if (!fn) {
    void* p = nullptr; cudaDriverEntryPointQueryResult st;
    cudaGetDriverEntryPoint("cuTensorMapEncodeTiled", &p, cudaEnableDefault, &st);
    fn = (PFN_encodeTiled)p;
    cudaFuncSetAttribute(fused_block_kernel<0>, cudaFuncAttributeMaxDynamicSharedMemorySize, SM_TOTAL + SM_PROF);
    cudaFuncSetAttribute(fused_block_kernel<1>, cudaFuncAttributeMaxDynamicSharedMemorySize, SM_TOTAL + SM_PROF);
    cudaFuncSetAttribute(fused_block_kernel<2>, cudaFuncAttributeMaxDynamicSharedMemorySize, SM_TOTAL + SM_PROF);
    cudaGetSymbolAddress(&mail, g_mail);
    int dev = 0;
    cudaGetDevice(&dev);
    cudaDeviceGetAttribute(&sms, cudaDevAttrMultiProcessorCount, dev);
  }
  const void* cur[8] = {x, wqkv, wo, w1, w3, w2, d_out, w_mod};
  bool same = true;
  for (int i = 0; i < 8; i++) same = same && cached[i] == cur[i];
  if (!same) {
    void *o, *h2, *hh;
    cudaGetSymbolAddress(&hh, g_hh); cudaGetSymbolAddress(&o, g_o);
    h2 = o;
    map_parity(fn, &maps.x, x, 64, 2); map_parity(fn, &maps.out, d_out, 16, 1);
    map2d(fn, &maps.o, o, D_, S_, 128); map2d(fn, &maps.h2, h2, D_, S_, 128);
    {
      const cuuint64_t dims[3] = {512, (cuuint64_t)S_, 7}, strides[2] = {1024, (cuuint64_t)S_ * 1024};
      const cuuint32_t box[3] = {64, 128, 1};
      encode(fn, &maps.hh, hh, 3, dims, strides, box);
    }
    {
      const cuuint64_t dims[4] = {64, 1024, 16, 2}, strides[3] = {3072 * 2, 128, 2048};
      const cuuint64_t dimv[4] = {64, 1024, 8, 2}, stridev[3] = {3072 * 2, 128, 1024};
      const cuuint32_t box[4] = {64, 64, 1, 2};
      encode(fn, &maps.wqk, wqkv, 4, dims, strides, box);
      encode(fn, &maps.wvv, wqkv + 2048, 4, dimv, stridev, box);
      const cuuint64_t dim1[4] = {1024, 128, 8, 2}, stride1[3] = {3072 * 2, 128 * 3072 * 2, 2048};
      const cuuint32_t box1[4] = {64, 16, 4, 2};
      encode(fn, &maps.wq1, wqkv, 4, dim1, stride1, box1);
    }
    map_w2chunk(fn, &maps.wo, wo, D_, D_); map_w2chunk(fn, &maps.w2, w2, D_, F_);
    map2d(fn, &maps.w1, w1, F_, D_, 64); map2d(fn, &maps.w3, w3, F_, D_, 64);
    map2d(fn, &maps.wmod, w_mod, 6 * D_, D_, 256);
    for (int i = 0; i < 8; i++) cached[i] = cur[i];
  }
  if (sms == NCTA + NAUX) {
    fused_block_kernel<0><<<NCTA + NAUX, 384, SM_TOTAL + SM_PROF>>>(x, cvec, w_mod, (Mail*)mail, 0, maps);
  } else {
    fused_block_kernel<1><<<NAUX, 384, SM_TOTAL + SM_PROF>>>(x, cvec, w_mod, (Mail*)mail, 0, maps);
    fused_block_kernel<2><<<NCTA, 384, SM_TOTAL + SM_PROF>>>(x, cvec, w_mod, (Mail*)mail, 0, maps);
  }
}
```

```cpp
#include <cuda.h>
#include <cuda_runtime.h>
#include <cuda_bf16.h>
#include <stdint.h>

namespace {

typedef __nv_bfloat16 bf16;

constexpr int S_ = 2048, D_ = 1024, F_ = 3584;
constexpr int NCTA = 128, NAUX = 4;

__device__ __align__(1024) bf16 g_o[S_ * D_];
__device__ __align__(1024) bf16 g_hh[S_ * F_];
constexpr int FO_EPOCH = 0, FO_CNT = 1;
constexpr int FL_EPOCH = 16 * 32, FL_LN1 = FL_EPOCH + 2, FL_H2 = FL_EPOCH + 3, FL_O = FL_EPOCH + 4;
struct Mail {
  unsigned flags[32 * 32];
  float mod[8 * 6 * D_];
  uint2 ln1[16 * 8 * 16];
  uint4 st2[16 * 8 * 8 * 8];
  uint4 halo[2][16 * 16 * 2 * 4 * 32];
};
__device__ __align__(1024) Mail g_mail;

template <int mode>
__device__ __forceinline__ int cta_role() {
  if (mode) return mode == 1 ? NCTA + (blockIdx.x & 3) : blockIdx.x & 127;
  uint32_t sm;
  asm("mov.u32 %0, %%smid;" : "=r"(sm));
  sm = (sm & ~3u) == 12 ? sm + 108 : (sm & ~3u) == 120 ? sm - 108 : sm;
  const int t = sm >> 1;
  int r;
  if (t < 32) r = (t & 7) * 16 + (t >> 3) * 2 + (sm & 1);
  else if (t < 60) r = (1 + (t - 32) % 7) * 16 + 8 + ((t - 32) / 7) * 2 + (sm & 1);
  else if (t < 62) r = NCTA + sm - 120;
  else r = sm - 116;
  return r;
}
#define PROF(slot, on) do {} while (0)
#define PROFN(slot, on) do {} while (0)
#define PROF_OUT(role, t) do {} while (0)
constexpr uint32_t SM_PROF = 0;

__device__ __forceinline__ uint32_t smem_u32(const void* p) { return (uint32_t)__cvta_generic_to_shared(p); }
#define ELECT "{\n.reg .pred p;\nelect.sync _|p, 0xffffffff;\n@p "
__device__ __forceinline__ void mbar_init_e(uint32_t bar, uint32_t count) {
  asm volatile(ELECT "mbarrier.init.shared::cta.b64 [%0], %1;\n}" :: "r"(bar), "r"(count) : "memory");
}
__device__ __forceinline__ void mbar_expect_tx_e(uint32_t bar, uint32_t bytes) {
  asm volatile(ELECT "mbarrier.arrive.expect_tx.shared::cta.b64 _, [%0], %1;\n}" :: "r"(bar), "r"(bytes) : "memory");
}
__device__ __forceinline__ void mbar_arrive_e(uint32_t bar) {
  asm volatile(ELECT "mbarrier.arrive.shared::cta.b64 _, [%0];\n}" :: "r"(bar) : "memory");
}
__device__ __forceinline__ uint32_t clock32() { uint32_t t; asm volatile("mov.u32 %0, %%clock;" : "=r"(t)); return t; }
#define WAIT_TAIL "setp.ne.and.u32 p, %2, 0, !p;\n@p bra LAB_WAIT;\n}"
__device__ __forceinline__ void mbar_wait(uint32_t bar, uint32_t parity, uint32_t dl) {
  asm volatile("{\n.reg .pred p;\n.reg .b32 t;\nLAB_WAIT:\nmbarrier.try_wait.parity.shared::cta.b64 p, [%0], %1;\n" WAIT_TAIL
               :: "r"(bar), "r"(parity), "r"(dl) : "memory");
}
__device__ __forceinline__ void mbar_sleep(uint32_t bar, uint32_t parity, uint32_t dl) {
  asm volatile("{\n.reg .pred p;\n.reg .b32 t;\nLAB_WAIT:\nmbarrier.try_wait.parity.shared::cta.b64 p, [%0], %1, 20000;\n" WAIT_TAIL
               :: "r"(bar), "r"(parity), "r"(dl) : "memory");
}
__device__ __forceinline__ bool poll_done(bool ok, uint32_t dl) {
  return __all_sync(0xffffffffu, ok || (int)(clock32() - dl) >= 0);
}
__device__ __forceinline__ unsigned ld_relaxed(const unsigned* p) {
  unsigned v; asm volatile("ld.relaxed.gpu.global.u32 %0, [%1];" : "=r"(v) : "l"(p) : "memory"); return v;
}
__device__ __forceinline__ void red_add_e(unsigned* p, unsigned v) {
  asm volatile(ELECT "red.relaxed.gpu.global.add.u32 [%0], %1;\n}" :: "l"(p), "r"(v) : "memory");
}
__device__ __forceinline__ void wait_flag(const unsigned* p, unsigned target, uint32_t dl) {
  asm volatile("{\n.reg .pred p;\n.reg .b32 t;\n"
               "LAB_WAIT:\n"
               "ld.relaxed.gpu.global.u32 t, [%0];\n"
               "sub.s32 t, t, %1;\n"
               "setp.ge.s32 p, t, 0;\n"
               "@p bra LAB_DONE;\n"
               "mov.u32 t, %%clock;\n"
               "sub.s32 t, t, %2;\n"
               "setp.lt.s32 p, t, 0;\n"
               "@p bra LAB_WAIT;\n"
               "LAB_DONE:\n}" :: "l"(p), "r"(target), "r"(dl) : "memory");
}
__device__ __forceinline__ void wait_until(uint32_t t) { while ((int)(clock32() - t) < 0) {} }
__device__ __forceinline__ void fence_proxy_async_smem() { asm volatile("fence.proxy.async.shared::cta;" ::: "memory"); }

constexpr uint64_t EVICT_FIRST = 0x12F0000000000000ull;
template <bool STREAM = false>
__device__ __forceinline__ void tma_load_2d(uint32_t dst, const CUtensorMap* m, uint32_t bar, int c0, int c1) {
  if (STREAM)
    asm volatile(ELECT "cp.async.bulk.tensor.2d.shared::cluster.global.mbarrier::complete_tx::bytes.L2::cache_hint [%0], [%1, {%3, %4}], [%2], %5;\n}"
                 :: "r"(dst), "l"(m), "r"(bar), "r"(c0), "r"(c1), "l"(EVICT_FIRST) : "memory");
  else
    asm volatile(ELECT "cp.async.bulk.tensor.2d.shared::cluster.global.mbarrier::complete_tx::bytes [%0], [%1, {%3, %4}], [%2];\n}"
                 :: "r"(dst), "l"(m), "r"(bar), "r"(c0), "r"(c1) : "memory");
}
template <bool STREAM = false>
__device__ __forceinline__ void tma_load_3d(uint32_t dst, const CUtensorMap* m, uint32_t bar, int c0, int c1, int c2) {
  if (STREAM)
    asm volatile(ELECT "cp.async.bulk.tensor.3d.shared::cluster.global.mbarrier::complete_tx::bytes.L2::cache_hint [%0], [%1, {%3, %4, %5}], [%2], %6;\n}"
                 :: "r"(dst), "l"(m), "r"(bar), "r"(c0), "r"(c1), "r"(c2), "l"(EVICT_FIRST) : "memory");
  else
    asm volatile(ELECT "cp.async.bulk.tensor.3d.shared::cluster.global.mbarrier::complete_tx::bytes [%0], [%1, {%3, %4, %5}], [%2];\n}"
                 :: "r"(dst), "l"(m), "r"(bar), "r"(c0), "r"(c1), "r"(c2) : "memory");
}
template <bool STREAM = false>
__device__ __forceinline__ void tma_load_4d(uint32_t dst, const CUtensorMap* m, uint32_t bar, int c0, int c1, int c2, int c3) {
  if (STREAM)
    asm volatile(ELECT "cp.async.bulk.tensor.4d.shared::cluster.global.mbarrier::complete_tx::bytes.L2::cache_hint [%0], [%1, {%3, %4, %5, %6}], [%2], %7;\n}"
                 :: "r"(dst), "l"(m), "r"(bar), "r"(c0), "r"(c1), "r"(c2), "r"(c3), "l"(EVICT_FIRST) : "memory");
  else
    asm volatile(ELECT "cp.async.bulk.tensor.4d.shared::cluster.global.mbarrier::complete_tx::bytes [%0], [%1, {%3, %4, %5, %6}], [%2];\n}"
                 :: "r"(dst), "l"(m), "r"(bar), "r"(c0), "r"(c1), "r"(c2), "r"(c3) : "memory");
}
__device__ __forceinline__ void tma_store_2d(const CUtensorMap* m, uint32_t src, int c0, int c1) {
  asm volatile(ELECT "cp.async.bulk.tensor.2d.global.shared::cta.bulk_group [%0, {%2, %3}], [%1];\n}"
               :: "l"(m), "r"(src), "r"(c0), "r"(c1) : "memory");
}
__device__ __forceinline__ void tma_store_3d(const CUtensorMap* m, uint32_t src, int c0, int c1, int c2) {
  asm volatile(ELECT "cp.async.bulk.tensor.3d.global.shared::cta.bulk_group [%0, {%2, %3, %4}], [%1];\n}"
               :: "l"(m), "r"(src), "r"(c0), "r"(c1), "r"(c2) : "memory");
}
__device__ __forceinline__ void bulk_load(uint32_t dst, const void* src, uint32_t bytes, uint32_t bar) {
  asm volatile(ELECT "cp.async.bulk.shared::cluster.global.mbarrier::complete_tx::bytes [%0], [%1], %2, [%3];\n}"
               :: "r"(dst), "l"(src), "r"(bytes), "r"(bar) : "memory");
}
__device__ __forceinline__ void bulk_prefetch(const void* src, uint32_t bytes) {
  asm volatile(ELECT "cp.async.bulk.prefetch.L2.global [%0], %1;\n}" :: "l"(src), "r"(bytes) : "memory");
}
__device__ __forceinline__ void bulk_commit() { asm volatile("cp.async.bulk.commit_group;" ::: "memory"); }
__device__ __forceinline__ void bulk_wait0() { asm volatile("cp.async.bulk.wait_group 0;" ::: "memory"); }
__device__ __forceinline__ void bulk_wait_read0() { asm volatile("cp.async.bulk.wait_group.read 0;" ::: "memory"); }
__device__ __forceinline__ void prefetch_tmap(const CUtensorMap* m) { asm volatile(ELECT "prefetch.tensormap [%0];\n}" :: "l"(m) : "memory"); }
__device__ __forceinline__ void wgmma_fence() { asm volatile("wgmma.fence.sync.aligned;" ::: "memory"); }
__device__ __forceinline__ void wgmma_commit() { asm volatile("wgmma.commit_group.sync.aligned;" ::: "memory"); }
template <int N> __device__ __forceinline__ void wgmma_wait() { asm volatile("wgmma.wait_group.sync.aligned %0;" :: "n"(N) : "memory"); }
template <int R> __device__ __forceinline__ void reg_alloc() { asm volatile("setmaxnreg.inc.sync.aligned.u32 %0;" :: "n"(R)); }
template <int R> __device__ __forceinline__ void reg_dealloc() { asm volatile("setmaxnreg.dec.sync.aligned.u32 %0;" :: "n"(R)); }
__device__ __forceinline__ void bar_sync(int id, int n) { asm volatile("bar.sync %0, %1;" :: "r"(id), "r"(n) : "memory"); }
__device__ __forceinline__ void bar_arrive(int id, int n) { asm volatile("bar.arrive %0, %1;" :: "r"(id), "r"(n) : "memory"); }
__device__ __forceinline__ void sched_fence(int zero) {
  asm volatile("{\n.reg .pred p;\n.reg .b32 t;\nsetp.eq.s32 p, %0, 0;\n@p bra.uni LAB_S;\n"
               "LAB_F:\nmov.u32 t, %%clock;\nsetp.eq.u32 p, t, 0;\n@p bra LAB_F;\nLAB_S:\n}" :: "r"(zero) : "memory");
}
template <int N> __device__ __forceinline__ void fence_regs(float (&a)[N]) {
  #pragma unroll
  for (int i = 0; i < N; i++) asm volatile("" : "+f"(a[i]) :: "memory");
}
template <int N> __device__ __forceinline__ void undef_regs(float (&a)[N]) {
  #pragma unroll
  for (int i = 0; i < N; i++) asm volatile("" : "=f"(a[i]));
}

__device__ __forceinline__ uint64_t desc_from_lo(uint32_t lo) { return (uint64_t)lo | ((uint64_t)0x40000040u << 32); }
__device__ __forceinline__ uint32_t pack_bf16(float lo, float hi) {
  uint32_t r; asm("cvt.rn.bf16x2.f32 %0, %1, %2;" : "=r"(r) : "f"(hi), "f"(lo)); return r;
}
__device__ __forceinline__ uint32_t fma_bf2(uint32_t a, uint32_t b, uint32_t c) {
  uint32_t d; asm("fma.rn.bf16x2 %0, %1, %2, %3;" : "=r"(d) : "r"(a), "r"(b), "r"(c)); return d;
}
__device__ __forceinline__ float bf_lo(uint32_t v) { return __uint_as_float(v << 16); }
__device__ __forceinline__ float bf_hi(uint32_t v) { return __uint_as_float(v & 0xFFFF0000u); }
__device__ __forceinline__ float bf16_round(float x) { return bf_lo(pack_bf16(x, 0.f)); }
__device__ __forceinline__ void stmatrix_x4(uint32_t addr, uint32_t r0, uint32_t r1, uint32_t r2, uint32_t r3) {
  asm volatile("stmatrix.sync.aligned.m8n8.x4.shared.b16 [%0], {%1, %2, %3, %4};" :: "r"(addr), "r"(r0), "r"(r1), "r"(r2), "r"(r3) : "memory");
}
__device__ __forceinline__ void stmatrix_x4_t(uint32_t addr, uint32_t r0, uint32_t r1, uint32_t r2, uint32_t r3) {
  asm volatile("stmatrix.sync.aligned.m8n8.x4.trans.shared.b16 [%0], {%1, %2, %3, %4};" :: "r"(addr), "r"(r0), "r"(r1), "r"(r2), "r"(r3) : "memory");
}
__device__ __forceinline__ void stmatrix_x4_if(uint32_t addr, uint32_t r0, uint32_t r1, uint32_t r2, uint32_t r3, bool on) {
  asm volatile("{\n.reg .pred p;\nsetp.ne.b32 p, %5, 0;\n@p stmatrix.sync.aligned.m8n8.x4.shared.b16 [%0], {%1, %2, %3, %4};\n}"
               :: "r"(addr), "r"(r0), "r"(r1), "r"(r2), "r"(r3), "r"((int)on) : "memory");
}
__device__ __forceinline__ void ldmatrix_x4(uint32_t addr, uint32_t& r0, uint32_t& r1, uint32_t& r2, uint32_t& r3) {
  asm volatile("ldmatrix.sync.aligned.m8n8.x4.shared.b16 {%0, %1, %2, %3}, [%4];" : "=r"(r0), "=r"(r1), "=r"(r2), "=r"(r3) : "r"(addr) : "memory");
}
__device__ __forceinline__ void ldmatrix_x4_t(uint32_t addr, uint32_t (&r)[4]) {
  asm volatile("ldmatrix.sync.aligned.m8n8.x4.trans.shared.b16 {%0, %1, %2, %3}, [%4];" : "=r"(r[0]), "=r"(r[1]), "=r"(r[2]), "=r"(r[3]) : "r"(addr) : "memory");
}
__device__ __forceinline__ void st_rlx(void* p, uint32_t a, bool on) {
  asm volatile("{\n.reg .pred p;\nsetp.ne.b32 p, %2, 0;\n@p st.relaxed.gpu.global.u32 [%0], %1;\n}" :: "l"(p), "r"(a), "r"((int)on) : "memory");
}
__device__ __forceinline__ void st_rlx_v2(void* p, uint32_t a, uint32_t b, bool on) {
  asm volatile("{\n.reg .pred p;\nsetp.ne.b32 p, %3, 0;\n@p st.relaxed.gpu.global.v2.u32 [%0], {%1, %2};\n}" :: "l"(p), "r"(a), "r"(b), "r"((int)on) : "memory");
}
__device__ __forceinline__ uint2 ld_rlx_v2(const void* p) {
  uint2 v; asm volatile("ld.relaxed.gpu.global.v2.u32 {%0,%1}, [%2];" : "=r"(v.x), "=r"(v.y) : "l"(p) : "memory"); return v;
}
__device__ __forceinline__ void st_rlx_v4(void* p, uint32_t a, uint32_t b, uint32_t c, uint32_t d, bool on) {
  asm volatile("{\n.reg .pred p;\nsetp.ne.b32 p, %5, 0;\n@p st.relaxed.gpu.global.v4.u32 [%0], {%1, %2, %3, %4};\n}"
               :: "l"(p), "r"(a), "r"(b), "r"(c), "r"(d), "r"((int)on) : "memory");
}
__device__ __forceinline__ void st_nonzero_v4(void* p, uint32_t a, uint32_t b, uint32_t c, uint32_t d, bool on) {
  st_rlx_v4(p, max(a, 1u), max(b, 1u), max(c, 1u), max(d, 1u), on);
}
__device__ __forceinline__ uint32_t min4(const uint4& v) { return min(min(v.x, v.y), min(v.z, v.w)); }
__device__ __forceinline__ uint4 ld_rlx_v4(const void* p) {
  uint4 v; asm volatile("ld.relaxed.gpu.global.v4.u32 {%0,%1,%2,%3}, [%4];" : "=r"(v.x), "=r"(v.y), "=r"(v.z), "=r"(v.w) : "l"(p) : "memory"); return v;
}
__device__ __forceinline__ uint32_t movmatrix_t(uint32_t a) {
  uint32_t d; asm volatile("movmatrix.sync.aligned.m8n8.trans.b16 %0, %1;" : "=r"(d) : "r"(a)); return d;
}
__device__ __forceinline__ void mma16(float (&c)[4], uint32_t a0, uint32_t a1, uint32_t a2, uint32_t a3, uint32_t b0, uint32_t b1) {
  asm volatile("mma.sync.aligned.m16n8k16.row.col.f32.bf16.bf16.f32 {%0,%1,%2,%3}, {%4,%5,%6,%7}, {%8,%9}, {%0,%1,%2,%3};"
               : "+f"(c[0]), "+f"(c[1]), "+f"(c[2]), "+f"(c[3]) : "r"(a0), "r"(a1), "r"(a2), "r"(a3), "r"(b0), "r"(b1));
}
__device__ __forceinline__ void sts128(uint32_t addr, uint32_t a, uint32_t b, uint32_t c, uint32_t d) {
  asm volatile("st.shared.v4.b32 [%0], {%1,%2,%3,%4};" :: "r"(addr), "r"(a), "r"(b), "r"(c), "r"(d) : "memory");
}
__device__ __forceinline__ uint4 lds128(uint32_t addr) {
  uint4 v; asm volatile("ld.shared.v4.b32 {%0,%1,%2,%3}, [%4];" : "=r"(v.x), "=r"(v.y), "=r"(v.z), "=r"(v.w) : "r"(addr) : "memory"); return v;
}
__device__ __forceinline__ uint32_t lds32(uint32_t addr) {
  uint32_t v; asm volatile("ld.shared.b32 %0, [%1];" : "=r"(v) : "r"(addr) : "memory"); return v;
}
__device__ __forceinline__ float2 lds64f(uint32_t addr) {
  float2 v; asm volatile("ld.shared.v2.f32 {%0,%1}, [%2];" : "=f"(v.x), "=f"(v.y) : "r"(addr) : "memory"); return v;
}
__device__ __forceinline__ void sts64(uint32_t addr, uint32_t a, uint32_t b) {
  asm volatile("st.shared.v2.b32 [%0], {%1, %2};" :: "r"(addr), "r"(a), "r"(b) : "memory");
}
__device__ __forceinline__ float fast_ex2(float x) { float y; asm("ex2.approx.ftz.f32 %0, %1;" : "=f"(y) : "f"(x)); return y; }
__device__ __forceinline__ float fast_rcp(float x) { float y; asm("rcp.approx.ftz.f32 %0, %1;" : "=f"(y) : "f"(x)); return y; }
__device__ __forceinline__ float fast_rsqrt(float x) { float y; asm("rsqrt.approx.ftz.f32 %0, %1;" : "=f"(y) : "f"(x)); return y; }
__device__ __forceinline__ float silu_f(float g) { return g * fast_rcp(1.f + fast_ex2(g * -1.4426950408889634f)); }
__device__ __forceinline__ float swiglu(float h, float v) {
  float t; asm("tanh.approx.f32 %0, %1;" : "=f"(t) : "f"(h));
  const float p = h * v;
  return fmaf(p, t, p);
}

__device__ __forceinline__ void wgmma_m64n128k16_ss(float (&d)[64], uint64_t descA, uint64_t descB, int scaleD) {
  asm volatile("{\n.reg .pred p;\nsetp.ne.b32 p, %66, 0;\n"
    "wgmma.mma_async.sync.aligned.m64n128k16.f32.bf16.bf16 "
    "{%0, %1, %2, %3, %4, %5, %6, %7, %8, %9, %10, %11, %12, %13, %14, %15, "
    "%16, %17, %18, %19, %20, %21, %22, %23, %24, %25, %26, %27, %28, %29, %30, %31, "
    "%32, %33, %34, %35, %36, %37, %38, %39, %40, %41, %42, %43, %44, %45, %46, %47, "
    "%48, %49, %50, %51, %52, %53, %54, %55, %56, %57, %58, %59, %60, %61, %62, %63}, "
    "%64, %65, p, 1, 1, 0, 1;\n}\n"
    : "+f"(d[0]), "+f"(d[1]), "+f"(d[2]), "+f"(d[3]), "+f"(d[4]), "+f"(d[5]), "+f"(d[6]), "+f"(d[7]),
      "+f"(d[8]), "+f"(d[9]), "+f"(d[10]), "+f"(d[11]), "+f"(d[12]), "+f"(d[13]), "+f"(d[14]), "+f"(d[15]),
      "+f"(d[16]), "+f"(d[17]), "+f"(d[18]), "+f"(d[19]), "+f"(d[20]), "+f"(d[21]), "+f"(d[22]), "+f"(d[23]),
      "+f"(d[24]), "+f"(d[25]), "+f"(d[26]), "+f"(d[27]), "+f"(d[28]), "+f"(d[29]), "+f"(d[30]), "+f"(d[31]),
      "+f"(d[32]), "+f"(d[33]), "+f"(d[34]), "+f"(d[35]), "+f"(d[36]), "+f"(d[37]), "+f"(d[38]), "+f"(d[39]),
      "+f"(d[40]), "+f"(d[41]), "+f"(d[42]), "+f"(d[43]), "+f"(d[44]), "+f"(d[45]), "+f"(d[46]), "+f"(d[47]),
      "+f"(d[48]), "+f"(d[49]), "+f"(d[50]), "+f"(d[51]), "+f"(d[52]), "+f"(d[53]), "+f"(d[54]), "+f"(d[55]),
      "+f"(d[56]), "+f"(d[57]), "+f"(d[58]), "+f"(d[59]), "+f"(d[60]), "+f"(d[61]), "+f"(d[62]), "+f"(d[63])
    : "l"(descA), "l"(descB), "r"(scaleD));
}
__device__ __forceinline__ void wgmma_m64n256k16_rs(float (&d)[128], uint32_t a0, uint32_t a1, uint32_t a2, uint32_t a3, uint64_t descB, int scaleD) {
  asm volatile("{\n.reg .pred p;\nsetp.ne.b32 p, %133, 0;\n"
    "wgmma.mma_async.sync.aligned.m64n256k16.f32.bf16.bf16 "
    "{%0, %1, %2, %3, %4, %5, %6, %7, %8, %9, %10, %11, %12, %13, %14, %15, "
    "%16, %17, %18, %19, %20, %21, %22, %23, %24, %25, %26, %27, %28, %29, %30, %31, "
    "%32, %33, %34, %35, %36, %37, %38, %39, %40, %41, %42, %43, %44, %45, %46, %47, "
    "%48, %49, %50, %51, %52, %53, %54, %55, %56, %57, %58, %59, %60, %61, %62, %63, "
    "%64, %65, %66, %67, %68, %69, %70, %71, %72, %73, %74, %75, %76, %77, %78, %79, "
    "%80, %81, %82, %83, %84, %85, %86, %87, %88, %89, %90, %91, %92, %93, %94, %95, "
    "%96, %97, %98, %99, %100, %101, %102, %103, %104, %105, %106, %107, %108, %109, %110, %111, "
    "%112, %113, %114, %115, %116, %117, %118, %119, %120, %121, %122, %123, %124, %125, %126, %127}, "
    "{%128, %129, %130, %131}, %132, p, 1, 1, 1;\n}\n"
    : "+f"(d[0]), "+f"(d[1]), "+f"(d[2]), "+f"(d[3]), "+f"(d[4]), "+f"(d[5]), "+f"(d[6]), "+f"(d[7]),
      "+f"(d[8]), "+f"(d[9]), "+f"(d[10]), "+f"(d[11]), "+f"(d[12]), "+f"(d[13]), "+f"(d[14]), "+f"(d[15]),
      "+f"(d[16]), "+f"(d[17]), "+f"(d[18]), "+f"(d[19]), "+f"(d[20]), "+f"(d[21]), "+f"(d[22]), "+f"(d[23]),
      "+f"(d[24]), "+f"(d[25]), "+f"(d[26]), "+f"(d[27]), "+f"(d[28]), "+f"(d[29]), "+f"(d[30]), "+f"(d[31]),
      "+f"(d[32]), "+f"(d[33]), "+f"(d[34]), "+f"(d[35]), "+f"(d[36]), "+f"(d[37]), "+f"(d[38]), "+f"(d[39]),
      "+f"(d[40]), "+f"(d[41]), "+f"(d[42]), "+f"(d[43]), "+f"(d[44]), "+f"(d[45]), "+f"(d[46]), "+f"(d[47]),
      "+f"(d[48]), "+f"(d[49]), "+f"(d[50]), "+f"(d[51]), "+f"(d[52]), "+f"(d[53]), "+f"(d[54]), "+f"(d[55]),
      "+f"(d[56]), "+f"(d[57]), "+f"(d[58]), "+f"(d[59]), "+f"(d[60]), "+f"(d[61]), "+f"(d[62]), "+f"(d[63]),
      "+f"(d[64]), "+f"(d[65]), "+f"(d[66]), "+f"(d[67]), "+f"(d[68]), "+f"(d[69]), "+f"(d[70]), "+f"(d[71]),
      "+f"(d[72]), "+f"(d[73]), "+f"(d[74]), "+f"(d[75]), "+f"(d[76]), "+f"(d[77]), "+f"(d[78]), "+f"(d[79]),
      "+f"(d[80]), "+f"(d[81]), "+f"(d[82]), "+f"(d[83]), "+f"(d[84]), "+f"(d[85]), "+f"(d[86]), "+f"(d[87]),
      "+f"(d[88]), "+f"(d[89]), "+f"(d[90]), "+f"(d[91]), "+f"(d[92]), "+f"(d[93]), "+f"(d[94]), "+f"(d[95]),
      "+f"(d[96]), "+f"(d[97]), "+f"(d[98]), "+f"(d[99]), "+f"(d[100]), "+f"(d[101]), "+f"(d[102]), "+f"(d[103]),
      "+f"(d[104]), "+f"(d[105]), "+f"(d[106]), "+f"(d[107]), "+f"(d[108]), "+f"(d[109]), "+f"(d[110]), "+f"(d[111]),
      "+f"(d[112]), "+f"(d[113]), "+f"(d[114]), "+f"(d[115]), "+f"(d[116]), "+f"(d[117]), "+f"(d[118]), "+f"(d[119]),
      "+f"(d[120]), "+f"(d[121]), "+f"(d[122]), "+f"(d[123]), "+f"(d[124]), "+f"(d[125]), "+f"(d[126]), "+f"(d[127])
    : "r"(a0), "r"(a1), "r"(a2), "r"(a3), "l"(descB), "r"(scaleD));
}

constexpr uint32_t MSLOT = 32768, QSLOT = 49152;
constexpr int NM = 6;
constexpr uint32_t SM_X0 = 3 * QSLOT;
constexpr uint32_t SM_XR = SM_X0 + 16384;
constexpr uint32_t SM_STG = 196608;
constexpr uint32_t SM_XCH = SM_STG + 16384;
constexpr uint32_t SM_BAR = SM_STG + 32768;
constexpr uint32_t SM_VEC = SM_BAR + 512;
constexpr uint32_t SM_MODT = SM_VEC;
constexpr uint32_t SM_TOTAL = SM_VEC + 2048;
constexpr uint32_t B_X = SM_BAR  , B_EQ = B_X + 64, B_EM = B_EQ + 32, B_STREQ = B_EM + 48, B_STH = B_STREQ + 8, B_HREQ = B_STH + 8  , B_LN = B_HREQ + 16,
                   B_FQ = B_LN + 8, B_FM = B_FQ + 32, B_MOD = B_FM + 48  , B_GATE = B_MOD + 64, B_STFREE = B_GATE + 8, B_VEC = B_STFREE + 8  ,
                   B_FLG = B_VEC + 16  , B_H2A = B_FLG + 24, B_HFREE = B_FLG + 96  ,
                   B_RST = B_HFREE + 16, B_END = B_RST + 8;
constexpr int NB_WG = 1  , NB_CONS = 3, NB_ORD = 4  ;
#define TUNE(name, value) constexpr int name = value
TUNE(PF_BYTES, 256);
TUNE(X_GAP, 250);
TUNE(AUX_HOLD, 3200);
TUNE(AUX_URG, 4);
TUNE(AUX_SLOW, 84);
TUNE(AUX_GAP, 500);
TUNE(MSEP, 6);
TUNE(ASPLIT, 2);
TUNE(WPRE, 2);
TUNE(DTAIL, 4);

struct Maps {
  CUtensorMap x, out;
  CUtensorMap o, h2, hh;
  CUtensorMap wqk, wvv, wq1, wo, w1, w3, w2;
  CUtensorMap wmod;
};

struct Ring { int st; uint32_t ph; int prev; uint32_t dl;
};
__device__ __forceinline__ void ring_next(Ring& r) { if (++r.st == NM) { r.st = 0; r.ph ^= 1; } }

__device__ __forceinline__ void retire_prev(uint32_t rel, bool on) {
  wgmma_commit();
  wgmma_wait<1>();
  if (on) mbar_arrive_e(rel);
}
struct Nop { __device__ __forceinline__ void operator()() const {} };
template <bool REL = true, class F = Nop>
__device__ __forceinline__ void mma_step(float (&acc)[64], uint32_t a, uint32_t b, bool first, uint32_t rel, F urgent = F()) {
  const uint32_t alo = (a >> 4) + (1u << 16), blo = (b >> 4) + (512u << 16);
  wgmma_fence();
  #pragma unroll
  for (int k = 0; k < 4; k++) {
    wgmma_m64n128k16_ss(acc, desc_from_lo(alo + k * 2), desc_from_lo(blo + k * 128), k > 0 || !first);
    if (k == 0) { retire_prev(rel, REL); urgent(); }
  }
  wgmma_commit();
}
__device__ __forceinline__ uint32_t m_wait(uint32_t sbase, const Ring& r) {
  mbar_wait(sbase + B_FM + 8 * r.st, r.ph, r.dl);
  return sbase + r.st * MSLOT;
}
__device__ __forceinline__ uint32_t m_prev(uint32_t sbase, const Ring& r) { return sbase + B_EM + 8 * r.prev; }
__device__ __forceinline__ void m_next(Ring& r) {
  r.prev = r.st; ring_next(r);
}
__device__ __forceinline__ void m_step(float (&acc)[64], uint32_t sbase, uint32_t wgoff, Ring& r, bool first = false) {
  const uint32_t slot = m_wait(sbase, r);
  mma_step(acc, slot + wgoff, slot + 16384, first, m_prev(sbase, r));
  m_next(r);
}

struct LnRow { uint32_t rs[2], nb[2]; };
__device__ __forceinline__ void ln_row(LnRow& l, int h, float mean, float rstd) {
  l.rs[h] = pack_bf16(rstd, rstd);
  const float nb = -mean * bf_lo(l.rs[h]);
  l.nb[h] = pack_bf16(nb, nb);
}
__device__ __forceinline__ uint32_t ln_mod(uint32_t x, const LnRow& l, int h, uint32_t c1, uint32_t s) {
  return fma_bf2(fma_bf2(x, l.rs[h], l.nb[h]), c1, s);
}

__device__ __forceinline__ uint32_t q_wait(int u, uint32_t sbase, uint32_t dl) {
  mbar_wait(sbase + B_FQ + 8 * (u & 3), (u >> 2) & 1, dl);
  return sbase + (u & 3) * QSLOT;
}
__device__ __forceinline__ uint32_t q_empty(int u, uint32_t sbase) { return sbase + B_EQ + 8 * (u & 3); }
struct Frag4 { uint32_t o[4]; };
__device__ __forceinline__ void q_load(uint32_t (&A)[16], uint4 (&p)[4], int kk, uint32_t tile, const Frag4& f, uint32_t t) {
  ldmatrix_x4(tile + f.o[kk], A[4 * kk], A[4 * kk + 1], A[4 * kk + 2], A[4 * kk + 3]);
  p[kk] = lds128(t + kk * 64);
}
__device__ __forceinline__ void q_norm(uint32_t (&A)[16], const uint4 (&p)[4], int kk, const LnRow& l) {
  A[4 * kk + 0] = ln_mod(A[4 * kk + 0], l, 0, p[kk].x, p[kk].z); A[4 * kk + 1] = ln_mod(A[4 * kk + 1], l, 1, p[kk].x, p[kk].z);
  A[4 * kk + 2] = ln_mod(A[4 * kk + 2], l, 0, p[kk].y, p[kk].w); A[4 * kk + 3] = ln_mod(A[4 * kk + 3], l, 1, p[kk].y, p[kk].w);
}
template <bool NEXT>
__device__ __forceinline__ void q_step_rs(float (&acc)[128], uint32_t (&A)[16], uint32_t (&N)[16], uint4 (&p)[4], int u, uint32_t sbase,
                                          const Frag4& f, uint32_t tab, const LnRow& l, uint32_t rot, bool keep, bool first, uint32_t dl, int wg, int zero) {
  const uint32_t slot = first ? sbase : q_wait(u, sbase, dl);
  const uint32_t blo = ((slot + 16384) >> 4) + (512u << 16) + rot * 128 + (zero << (u >> 2)), t = tab + ((u + 1) & 7) * 256;
  #pragma unroll
  for (int kk = 0; kk < 4; kk++) q_norm(A, p, kk, l);
  #pragma unroll
  for (int i = 0; i < 16; i++) asm volatile("" : "+r"(A[i]));
  if (!first) sched_fence(zero);
  if (first) {
    mbar_wait(sbase + B_GATE, 0, dl);
    PROF(6, threadIdx.x == 0);
  }
  if (!(first && wg == 0)) bar_sync(NB_ORD + wg, 256);
  wgmma_fence();
  #pragma unroll
  for (int kk = 0; kk < 4; kk++) {
    wgmma_m64n256k16_rs(acc, A[4 * kk], A[4 * kk + 1], A[4 * kk + 2], A[4 * kk + 3], desc_from_lo(blo ^ (kk * 128)), kk > 0 || !first);
    if (kk == 0) retire_prev(q_empty(u - 1, sbase), !first);
    if (NEXT && kk == 1) {
      if ((u & 1) && u < MSEP) mbar_wait(sbase + B_MOD + 4 * (u + 1), 0, dl);
      #pragma unroll
      for (int q = 0; q < 4; q++) q_load(N, p, q, slot, f, t);
    }
    if (kk == 3 && (NEXT || wg == 0)) bar_arrive(NB_ORD + (wg ^ 1), 256);
    if (kk == 1) stmatrix_x4_if(sbase + SM_STG + (u >> 3) * 16384 + (f.o[0] ^ (((u >> 1 & 3) ^ rot) << 5)), A[0], A[1], A[2], A[3], keep);
  }
  wgmma_commit();
}

typedef uint32_t Frag8[8];
template <int N> __device__ __forceinline__ void pack_half(Frag8& f, const float (&acc)[N], int off, int half) {
  #pragma unroll
  for (int e = 0; e < 8; e++) { f[e] = pack_bf16(acc[off + 4 * e + 2 * half], acc[off + 4 * e + 2 * half + 1]); asm volatile("" : "+r"(f[e])); }
}
__device__ __forceinline__ void transpose8(Frag8& f) {
  #pragma unroll
  for (int e = 0; e < 8; e++) f[e] = movmatrix_t(f[e]);
}
__device__ __forceinline__ void attn_send(const Frag8& f, int kv, uint32_t xch, int warp, uint4* halo_out, bool has_next) {
  if (warp == 3) {
    st_nonzero_v4(halo_out + kv * 64, f[0], f[1], f[2], f[3], has_next); st_nonzero_v4(halo_out + kv * 64 + 32, f[4], f[5], f[6], f[7], has_next);
  } else {
    sts128(xch + 2048 + kv * 1024, f[0], f[1], f[2], f[3]); sts128(xch + 2048 + kv * 1024 + 512, f[4], f[5], f[6], f[7]);
  }
}
template <int N>
__device__ __forceinline__ void attn_recv(uint4* p, int first, uint32_t xch, int wg, int warp, const uint4* halo_in, bool has_prev) {
  bar_sync(NB_WG + wg, 128);
  #pragma unroll
  for (int e = 0; e < N; e++)
    asm volatile("{\n.reg .pred p, q;\nsetp.ne.b32 p, %6, 0;\nsetp.ne.b32 q, %7, 0;\n"
                 "mov.b32 %0, 0;\nmov.b32 %1, 0;\nmov.b32 %2, 0;\nmov.b32 %3, 0;\n"
                 "@p ld.shared.v4.b32 {%0,%1,%2,%3}, [%4];\n@q ld.relaxed.gpu.global.v4.u32 {%0,%1,%2,%3}, [%5];\n}"
                 : "=&r"(p[e].x), "=&r"(p[e].y), "=&r"(p[e].z), "=&r"(p[e].w)
                 : "r"(xch + (first + e) * 512), "l"(halo_in + (first + e) * 32), "r"((int)(warp > 0)), "r"((int)(warp == 0 && has_prev)) : "memory");
}
template <int N>
__device__ __forceinline__ void attn_check(uint4* p, int first, bool remote, const uint4* halo_in, uint32_t dl) {
  if (remote) {
    while (true) {
      uint32_t m = ~0u;
      #pragma unroll
      for (int e = 0; e < N; e++) m = min(m, min4(p[e]));
      if (poll_done(m != 0, dl)) break;
      #pragma unroll
      for (int e = 0; e < N; e++) p[e] = ld_rlx_v4(halo_in + (first + e) * 32);
    }
  }
}
template <int SPLIT, class F>
__device__ __forceinline__ void attn_core(const Frag8& qA, const Frag8& qB, const Frag8& kA, const Frag8& kB, const Frag8& vA, const Frag8& vB,
                                          const uint4* kP, const uint4* vP, bool noprev, int lane, float (&o)[2][5][4], F late) {
  const int g = lane >> 2, qd = lane & 3;
  const bool s0 = 2 * qd > g, s1 = 2 * qd + 1 > g;
  const uint32_t msk = (s0 ? 0xFFFFu : 0u) | (s1 ? 0xFFFF0000u : 0u);
  float s[2][3][4];
  uint32_t pr[2][2];
  auto scores = [&](int h, int nb) {
    s[h][nb][0] = s[h][nb][1] = s[h][nb][2] = s[h][nb][3] = 0.f;
    #pragma unroll
    for (int kk = 0; kk < 2; kk++) {
      const int e = 4 * h + 2 * kk;
      mma16(s[h][nb], qA[e], qB[e], qA[e + 1], qB[e + 1], nb == 1 ? kA[e] : nb == 2 ? kB[e] : kk ? kP[h].z : kP[h].x,
            nb == 1 ? kA[e + 1] : nb == 2 ? kB[e + 1] : kk ? kP[h].w : kP[h].y);
    }
  };
  auto rows = [&](int h, int y) {
    constexpr float SC = 0.17677669529663687f * 1.4426950408889634f;
    const float l0 = s0 ? (y == 0 && noprev ? -INFINITY : s[h][y][2 * y]) : s[h][y + 1][2 * y];
    const float l1 = s1 ? (y == 0 && noprev ? -INFINITY : s[h][y][2 * y + 1]) : s[h][y + 1][2 * y + 1];
    float m = fmaxf(l0, l1);
    m = fmaxf(m, __shfl_xor_sync(0xffffffffu, m, 1));
    m = fmaxf(m, __shfl_xor_sync(0xffffffffu, m, 2));
    const uint32_t p = pr[h][y] = pack_bf16(fast_ex2((l0 - m) * SC), fast_ex2((l1 - m) * SC));
    #pragma unroll
    for (int m2 = 0; m2 < 2; m2++) {
      const int e = 4 * h + 2 * m2;
      float (&d)[4] = o[h][2 * m2 + y];
      d[0] = d[1] = d[2] = d[3] = 0.f;
      if (y == 0) mma16(d, m2 ? vP[h].z : vP[h].x, m2 ? vP[h].w : vP[h].y, vA[e], vA[e + 1], p & msk, p & ~msk);
      else mma16(d, vA[e], vA[e + 1], vB[e], vB[e + 1], p & msk, p & ~msk);
    }
  };
  #pragma unroll
  for (int h = 0; h < 2; h++) { scores(h, 1); scores(h, 2); if (SPLIT == 0) scores(h, 0); }
  if (SPLIT == 2) { rows(0, 1); rows(1, 1); }
  if (SPLIT) { late(); scores(0, 0); scores(1, 0); }
  #pragma unroll
  for (int h = 0; h < 2; h++) {
    if (SPLIT < 2) rows(h, 1);
    rows(h, 0);
    o[h][4][0] = o[h][4][1] = o[h][4][2] = o[h][4][3] = 0.f;
    mma16(o[h][4], 0x3F803F80u, 0u, 0u, 0x3F803F80u, pr[h][0], pr[h][1]);
  }
}
__device__ __forceinline__ void attn_store(const float (&o)[2][5][4], int h, uint32_t sbase, const Frag4& f) {
  float r[4];
  #pragma unroll
  for (int e = 0; e < 4; e++) r[e] = fast_rcp(o[h][4][e]);
  #pragma unroll
  for (int m = 0; m < 2; m++) {
    const float (&lo)[4] = o[h][2 * m], (&hi)[4] = o[h][2 * m + 1];
    stmatrix_x4_t(sbase + SM_STG + f.o[2 * h + m], pack_bf16(lo[0] * r[0], lo[1] * r[1]), pack_bf16(hi[0] * r[2], hi[1] * r[3]),
                  pack_bf16(lo[2] * r[0], lo[3] * r[1]), pack_bf16(hi[2] * r[2], hi[3] * r[3]));
  }
}

__device__ __forceinline__ void request_store(uint32_t bar) {
  fence_proxy_async_smem();
  mbar_arrive_e(bar);
}

__device__ __forceinline__ void g_quad(float (&a0)[64], float (&a1)[64], uint32_t rel2, uint32_t sbase, uint32_t wgoff, Ring& r) {
  const uint32_t x = m_wait(sbase, r);
  mma_step(a0, x + wgoff, x + 16384, false, m_prev(sbase, r), [&] { if (rel2) mbar_arrive_e(rel2); });
  m_next(r);
  const uint32_t xe = m_prev(sbase, r), y = m_wait(sbase, r);
  mma_step<false>(a1, x + wgoff, y, false, 0);
  m_next(r);
  const uint32_t z = m_wait(sbase, r);
  mma_step(a1, z + wgoff, y + 16384, false, xe);
  mma_step(a0, z + wgoff, z + 16384, false, m_prev(sbase, r));
  m_next(r);
}
template <int T>
__device__ __forceinline__ void g_piece(float (&prv)[64], int jj, int use, uint32_t sbase, const Frag4& f, uint32_t dl) {
  if (jj == 0) { mbar_wait(sbase + B_HFREE + 8 * T, use & 1, dl); fence_regs(prv); PROF(33 + 2 * use + T, threadIdx.x == 0); }
  uint32_t p[4];
  #pragma unroll
  for (int e = 0; e < 4; e++) {
    const int i = jj * 8 + e * 2;
    p[e] = pack_bf16(swiglu(prv[i], prv[i + 32]), swiglu(prv[i + 1], prv[i + 33]));
  }
  stmatrix_x4(sbase + SM_STG + T * 16384 + f.o[jj], p[0], p[1], p[2], p[3]);
  if (jj == 3) request_store(sbase + B_HREQ + 8 * T);
}
template <bool REL2, bool Q, class F>
__device__ __forceinline__ uint32_t g_ppqq(float (&p)[64], float (&q)[64], bool firstq, uint32_t rel2, uint32_t sbase, uint32_t wgoff, Ring& r, F after) {
  const uint32_t x = m_wait(sbase, r);
  mma_step(p, x + wgoff, x + 16384, false, m_prev(sbase, r), [&] { if (REL2) mbar_arrive_e(rel2); });
  m_next(r);
  after(0);
  const uint32_t xe = m_prev(sbase, r), z = m_wait(sbase, r);
  mma_step<!Q>(p, z + wgoff, z + 16384, false, xe);
  m_next(r);
  after(1);
  if (!Q) return 0;
  const uint32_t ze = m_prev(sbase, r), y = m_wait(sbase, r);
  mma_step<false>(q, x + wgoff, y, firstq, 0);
  after(2);
  mma_step(q, z + wgoff, y + 16384, false, xe);
  m_next(r);
  after(3);
  return ze;
}

__device__ __forceinline__ uint32_t bad2(uint32_t a, uint32_t b, unsigned par) {
  uint32_t d; asm("lop3.b32 %0, %1, %2, %3, 0x7E;" : "=r"(d) : "r"(a), "r"(b), "r"(par)); return d;
}
__device__ __forceinline__ uint32_t bad4(const uint4& v, unsigned par) { return bad2(v.x, v.y, par) | bad2(v.z, v.w, par); }
__device__ __forceinline__ uint32_t hi_halves(uint32_t lo, uint32_t hi) { return __byte_perm(lo, hi, 0x7632); }

__device__ __forceinline__ void gather_table(const float* src, uint32_t dst, uint32_t bar, unsigned par, uint32_t dl) {
  asm volatile("{\n.reg .pred p, e;\n.reg .b32 s<4>, c<4>, t<4>, w<4>;\n"
               "elect.sync _|e, 0xffffffff;\n"
               "LAB_POLL:\n"
               "ld.relaxed.gpu.global.v4.u32 {s0, s1, s2, s3}, [%0];\n"
               "ld.relaxed.gpu.global.v4.u32 {c0, c1, c2, c3}, [%0 + 4096];\n"
               "prmt.b32 w0, c0, c1, 0x7632;\nprmt.b32 w1, c2, c3, 0x7632;\nprmt.b32 w2, s0, s1, 0x7632;\nprmt.b32 w3, s2, s3, 0x7632;\n"
               "st.shared.v4.b32 [%1], {w0, w1, w2, w3};\n"
               "lop3.b32 t0, s0, s1, %3, 0x7E;\nlop3.b32 t1, s2, s3, %3, 0x7E;\nlop3.b32 t2, c0, c1, %3, 0x7E;\nlop3.b32 t3, c2, c3, %3, 0x7E;\n"
               "lop3.b32 t0, t0, t1, 1, 0xA8;\nlop3.b32 t2, t2, t3, 1, 0xA8;\n"
               "or.b32 t0, t0, t2;\n"
               "setp.eq.u32 p, t0, 0;\n"
               "vote.sync.all.pred p, p, 0xffffffff;\n"
               "@p bra.uni LAB_OK;\n"
               "mov.u32 t0, %%clock;\nsub.s32 t0, t0, %4;\nsetp.lt.s32 p, t0, 0;\n"
               "vote.sync.all.pred p, p, 0xffffffff;\n"
               "@p bra.uni LAB_POLL;\n"
               "LAB_OK:\n"
               "@e mbarrier.arrive.shared::cta.b64 _, [%2];\n}"
               :: "l"(src), "r"(dst), "r"(bar), "r"(par), "r"(dl) : "memory");
}

__device__ __forceinline__ int aux_col(int a, int u) { return u < 8 ? (a & 1) * 1024 + (2 * u + (a >> 1)) * 64 : 2048 + ((u - 8) * 4 + a) * 64; }
constexpr int NA = 7;
constexpr uint32_t A_FULL = SM_BAR, A_EMPTY = SM_BAR + 64, A_SUM = SM_BAR + 128, A_FREE = SM_BAR + 136, SM_RED = SM_VEC;
__device__ __forceinline__ void aux_role(const Maps& maps, const bf16* __restrict__ cvec, Mail* mail0, int zero, int a, uint32_t sbase, int wid) {
  const int tid = threadIdx.x, lane = tid & 31;
  const uint32_t dl = (clock32() + 800000000u) | 1;
  int st = 0; uint32_t ph = 0;
  if (wid == 8) {
    prefetch_tmap(&maps.wmod);
    #pragma unroll
    for (int i = 0; i < 18; i++) mbar_init_e(sbase + A_FULL + 8 * i, i < 8 ? 1 : i < 17 ? 8 : 2);
    fence_proxy_async_smem();
    bar_arrive(0, 352);
    PROF(39, lane == 0);
    #pragma unroll
    for (int i = 0; i < NA; i++) {
      mbar_expect_tx_e(sbase + A_FULL + 8 * i, 32768);
      tma_load_2d(sbase + i * MSLOT, &maps.wmod, sbase + A_FULL + 8 * i, aux_col(a, i >> 2), (i & 3) * 256);
    }
    PROF(40, lane == 0);
    #pragma unroll 1
    for (int i = NA; i < 96; i++) {
      if (i >= AUX_SLOW) wait_until(clock32() + AUX_GAP);
      if (i == 8) wait_until(dl - 800000000u + AUX_HOLD);
      mbar_wait(sbase + A_EMPTY + 8 * st, ph, dl);
      mbar_expect_tx_e(sbase + A_FULL + 8 * st, 32768);
      tma_load_2d<true>(sbase + st * MSLOT, &maps.wmod, sbase + A_FULL + 8 * st, aux_col(a, i >> 2), (i & 3) * 256);
      if (++st == NA) { st = 0; ph ^= 1; }
    }
  } else if (wid < 8) {
    const int g = lane >> 2, qd = lane & 3;
    uint32_t sc[16];
    const uint2 c = *reinterpret_cast<const uint2*>(cvec + tid * 4);
    sts64(sbase + SM_RED + tid * 8, pack_bf16(silu_f(bf_lo(c.x)), silu_f(bf_hi(c.x))), pack_bf16(silu_f(bf_lo(c.y)), silu_f(bf_hi(c.y))));
    bar_sync(0, 352);
    #pragma unroll
    for (int i = 0; i < 16; i++) sc[i] = lds32(sbase + SM_RED + ((i >> 2) * 256 + wid * 32 + (i & 3) * 8 + qd * 2) * 2);
    bar_sync(NB_CONS, 256);
    PROF(38, tid == 0);
    const uint32_t aoff = (wid * 32 + (lane & 7) + (lane >> 4) * 8) * 128 + ((((lane >> 3) & 1) ^ (lane & 7)) << 4);
    uint32_t w[2][8][4];
    auto fetch = [&](uint32_t (&f)[8][4]) {
      mbar_wait(sbase + A_FULL + 8 * st, ph, dl);
      #pragma unroll
      for (int e = 0; e < 8; e++) ldmatrix_x4_t((sbase + st * MSLOT + aoff + (e >> 2) * 2048) ^ ((e & 3) << 5), f[e]);
      if (++st == NA) { st = 0; ph ^= 1; }
    };
    #pragma unroll 1
    for (int u = 0; u < 24; u++) {
      float acc[4][4];
      #pragma unroll
      for (int m = 0; m < 4; m++) acc[m][0] = acc[m][1] = acc[m][2] = acc[m][3] = 0.f;
      fetch(w[0]);
      #pragma unroll
      for (int q = 0; q < 4; q++) {
        PROF(30 + (u & 1) * 4 + q, u < 2 && tid == 0);
        const uint32_t rel = sbase + A_EMPTY + 8 * (st == 0 ? NA - 1 : st - 1);
        if (q < 3) fetch(w[(q + 1) & 1]);
        uint32_t dep = 0;
        #pragma unroll
        for (int e = 0; e < 8; e++) dep |= w[q & 1][e][0];
        mbar_arrive_e(rel + (dep & zero));
        if (q == 1) mbar_wait(sbase + A_FREE, (u & 1) ^ 1, dl);
        #pragma unroll
        for (int e = 0; e < 8; e++) {
          const uint32_t (&f)[4] = w[q & 1][e];
          mma16(acc[e & 3], f[0], f[1], f[2], f[3], sc[4 * q + 2 * (e >> 2)], sc[4 * q + 2 * (e >> 2) + 1]);
        }
      }
      const float v0 = qd & 2 ? (qd & 1 ? acc[3][0] : acc[2][0]) : (qd & 1 ? acc[1][0] : acc[0][0]);
      const float v1 = qd & 2 ? (qd & 1 ? acc[3][2] : acc[2][2]) : (qd & 1 ? acc[1][2] : acc[0][2]);
      sts64(sbase + SM_RED + wid * 256 + (qd * 8 + g) * 8, __float_as_uint(v0), __float_as_uint(v1));
      mbar_arrive_e(sbase + A_SUM);
      if (u < AUX_URG) mbar_wait(sbase + A_FREE, u & 1, dl);
    }
  } else if (wid < 11) {
    float* const mail = &mail0->mod[(wid - 9) * 4 * 6 * D_ + 2 * lane];
    unsigned par = ld_relaxed(&mail0->flags[FL_EPOCH + (lane >> 5)]);
    bar_sync(0, 352);
    par = (par + 1) & 1;
    #pragma unroll 1
    for (int u = 0; u < 24; u++) {
      const int col = aux_col(a, u);
      const float add = (col >> 10) == 1 || (col >> 10) == 4 ? 1.f : 0.f;
      const float mul = col < 3 * D_ ? 1.f : col < 5 * D_ ? 0.5f : 2.f;
      mbar_wait(sbase + A_SUM, u & 1, dl);
      float2 v[8];
      #pragma unroll
      for (int w = 0; w < 8; w++) v[w] = lds64f(sbase + SM_RED + w * 256 + lane * 8);
      const float t0 = ((v[0].x + v[1].x) + (v[2].x + v[3].x)) + ((v[4].x + v[5].x) + (v[6].x + v[7].x));
      const float t1 = ((v[0].y + v[1].y) + (v[2].y + v[3].y)) + ((v[4].y + v[5].y) + (v[6].y + v[7].y));
      mbar_arrive_e(sbase + A_FREE + (__float_as_uint(t0 + t1) & zero));
      const uint32_t w = pack_bf16((add + bf16_round(t0)) * mul, (add + bf16_round(t1)) * mul), o = __shfl_xor_sync(0xffffffffu, w, 1);
      const uint32_t m0 = (lane & 1) ? (o & 0xFFFF0000u) : (w << 16), m1 = (lane & 1) ? (w & 0xFFFF0000u) : (o << 16);
      #pragma unroll
      for (int c = 0; c < 4; c++) st_rlx_v2(mail + c * 6 * D_ + col, m0 | par, m1 | par, true);
      PROF(1 + u, tid == 288);
    }
    const int t = a * 64 + tid - 288;
    #pragma unroll 1
    for (int i = t; i < 16 * 16 * 256; i += 256) mail0->halo[par ^ 1][i] = make_uint4(0, 0, 0, 0);
  }
}

template <int MODE>
__global__ void __launch_bounds__(384, 1)
fused_block_kernel(const bf16* __restrict__ x, const bf16* __restrict__ cvec, const bf16* __restrict__ wmod, Mail* mail0, int zero,
                   const __grid_constant__ Maps maps) {
  extern __shared__ __align__(1024) uint8_t smem_raw[];
  const uint32_t sbase = smem_u32(smem_raw);
  const int tid = threadIdx.x, lane = tid & 31;
  PROFN(0, tid == 0);
  const int wid = __shfl_sync(0xffffffffu, tid >> 5, 0);
  const int b = cta_role<MODE>();
  if (b >= NCTA) { aux_role(maps, cvec, mail0, zero, b - NCTA, sbase, wid); return; }
  const int jg = b >> 6, mb = jg ? 31 - (b >> 2) : (b >> 2), j = 4 * jg + (b & 3);
  const uint32_t dl = (clock32() + 800000000u) | 1;
  unsigned* const flags = &mail0->flags[mb * 32];
  const int row0 = mb * 128;

  if (wid >= 8) {
    if (wid == 8) {
      #pragma unroll
      for (int i = 0; i < 8; i++) mbar_init_e(sbase + B_X + 8 * i, 1);
      fence_proxy_async_smem();
      mbar_expect_tx_e(sbase + B_X, 4096);
      bulk_load(sbase + SM_XR, x + (size_t)(row0 + j * 16) * D_, 4096, sbase + B_X);
    } else if (wid == 11) {
      #pragma unroll
      for (int i = 0; i < 12; i++) prefetch_tmap(&maps.x + i);
    } else if (wid == 9) {
      #pragma unroll
      for (uint32_t bar = B_EQ; bar < B_FM; bar += 8) mbar_init_e(sbase + bar, bar < B_FQ ? 8 : bar == B_FQ + 8 || bar == B_FQ + 24 ? 2 : 1);
      fence_proxy_async_smem();
    } else {
      #pragma unroll
      for (uint32_t bar = B_FM; bar < B_END; bar += 8) mbar_init_e(sbase + bar, 1);
      fence_proxy_async_smem();
    }
    bar_sync(0, 384);
    reg_dealloc<40>();
    PROF(92, tid == 256);
    if (wid == 8) {
      uint32_t tnext = clock32();
      #pragma unroll 1
      for (int q = 1; q < 8; q++) {
        wait_until(tnext);
        mbar_expect_tx_e(sbase + B_X + 8 * q, 4096);
        bulk_load(sbase + SM_XR + q * 4096, x + (size_t)(row0 + j * 16 + 2 * q) * D_, 4096, sbase + B_X + 8 * q);
        tnext += X_GAP;
      }
      #pragma unroll 1
      for (int u = 0; u < 16; u++) {
        const int st = u & 3;
        if (u == 1) mbar_wait(sbase + B_X + 56, 0, dl);
        if (u == 2) { mbar_wait(sbase + B_GATE, 0, dl); PROFN(60, lane == 0); }
        if (u == 3) mbar_wait(sbase + B_EQ, 0, dl);
        mbar_wait(sbase + B_EQ + 8 * st, ((u >> 2) & 1) ^ 1, dl);
        const uint32_t slot = sbase + st * QSLOT, fb = sbase + B_FQ + 8 * st;
        mbar_expect_tx_e(fb, u == 0 ? 65536 : u == 15 ? 32768 : 49152);
        if ((u & 1) && (u < MSEP || u == 15)) mbar_arrive_e(fb);
        if (u == 0) tma_load_3d(sbase + SM_X0, &maps.x, fb, 0, mb * 64, 0);
        tma_load_4d<true>(slot + 16384, &maps.wqk, fb, 0, u * 64, j, 0);
        tma_load_4d<true>(slot + 32768, &maps.wvv, fb, 0, u * 64, j, 0);
        if (u < 15) tma_load_3d(slot, &maps.x, fb, u * 64 + 64, mb * 64, 0);
      }
      const unsigned e1 = 1 + ld_relaxed(flags + FO_EPOCH);
      Ring r{0, 1, 0, dl};
      uint32_t slot, fb;
      auto acquire = [&](uint32_t bytes) {
        mbar_wait(sbase + B_EM + 8 * r.st, r.ph, dl);
        slot = sbase + r.st * MSLOT; fb = sbase + B_FM + 8 * r.st;
        mbar_expect_tx_e(fb, bytes);
        ring_next(r);
      };
      #pragma unroll 1
      for (int kt = 0; kt < 16; kt++) {
        if (kt < 5) mbar_wait(sbase + B_EQ + 8 * (kt - (kt >= 2)), 1, dl);
        if ((kt & 7) == 0) { PROF(46, lane == 0 && kt == 8); mbar_wait(sbase + B_FLG + kt, 0, dl); PROF(47, lane == 0 && kt == 8); }
        acquire(32768);
        tma_load_4d<true>(slot + 16384, &maps.wq1, fb, (j + 8) * 64, (kt & 1) * 64 + (kt & 6) * 8, (kt >> 3) * 4, 0);
        tma_load_3d(slot, &maps.hh, fb, (kt & 7) * 64, row0, kt >> 3);
      }
      PROF(82, lane == 0);
      mbar_wait(sbase + B_FLG + 16, 0, dl);
      PROF(83, lane == 0);
      #pragma unroll 1
      for (int kt = 0; kt < 8; kt++) {
        if (kt == 4) {
          acquire(32768);
          tma_load_3d(slot, &maps.x, fb, j * 128, mb * 64, 0);
          tma_load_3d(slot + 16384, &maps.x, fb, j * 128 + 64, mb * 64, 0);
        }
        acquire(32768);
        tma_load_3d<true>(slot + 16384, &maps.wo, fb, 0, kt * 64, 2 * j);
        tma_load_2d(slot, &maps.o, fb, kt * 64, row0);
      }
      acquire(16384);
      tma_load_3d<true>(slot + 16384, &maps.wo, fb, 0, (8 + j) * 64, 2 * j);
      const uint32_t oth = (0x2107654u + (0x1110000u << (4 * (j & 3)) & 0x1110000u)) ^ ((j & 4) ? 0x4444444u : 0u);
      auto deferred = [&](const CUtensorMap* map, const unsigned* flag, Ring ra, int n, int col0, int step) {
        uint32_t dst = sbase + ra.st * MSLOT, bar = sbase + B_FM + 8 * ra.st, col = col0 + (~j & 4) * step;
        asm volatile("" : "+r"(dst), "+r"(bar), "+r"(col));
        wait_flag(flag, e1 * NCTA, dl);
        tma_load_2d(dst, map, bar, col, row0);
        #pragma unroll 1
        for (int i = 1; i < n; i++) { ring_next(ra); tma_load_2d(sbase + ra.st * MSLOT, map, sbase + B_FM + 8 * ra.st, col + i * step, row0); }
      };
      {
        const Ring ra = r;
        #pragma unroll 1
        for (int i = 0; i < 7; i++) {
          const int kt = 8 + (oth >> (4 * i) & 7);
          acquire(32768);
          tma_load_3d<true>(slot + 16384, &maps.wo, fb, 0, kt * 64, 2 * j);
          if (i == WPRE - 1) { deferred(&maps.o, &mail0->flags[FL_O], ra, WPRE, 512, 64); PROFN(61, lane == 0); }
          if (i >= WPRE) tma_load_2d(slot, &maps.o, fb, kt * 64, row0);
        }
      }
      uint64_t ord = (uint64_t)(2 * oth) | (uint64_t)(2 * oth + 0x1111111u) << 28;
      auto load_b = [&](uint32_t dst, int col, int kt) {
        tma_load_2d<true>(dst, &maps.w1, fb, col, kt * 64);
        tma_load_2d<true>(dst + 8192, &maps.w3, fb, col, kt * 64);
      };
      Ring ra = r;
      #pragma unroll 1
      for (int i = -2; i < 5; i++) {
        const int kt = i < 0 ? 2 * j + i + 2 : 2 * ((~j & 4) + min(i, 3));
        if (i == 0) ra = r;
        acquire(32768);
        load_b(slot + 16384, i < 0 || i == 3 ? (8 + j) * 64 : j * 64, kt);
        if (i < 0 || i == 3) load_b(slot, i < 0 ? j * 64 : (8 + j) * 64, i < 0 ? kt : kt - 2);
      }
      deferred(&maps.h2, &mail0->flags[FL_H2], ra, 3, 0, 128);
      tma_load_2d(slot, &maps.h2, fb, ((~j & 4) + 3) * 128, row0);
      PROFN(62, lane == 0);
      mbar_arrive_e(sbase + B_H2A);
      #pragma unroll 1
      for (int q = 2; q < 31; q++) {
        const int pr = q >> 3, w = q & 7, col = (16 * pr + j) * 64 + (w == 7 ? 512 : 0), y = pr == 3 ? 0 : w == 0 || w >= 6 ? 2 : 1;
        if (q == 7) ord = (j & 4) ? 0xFEDCBA9875316420ull : 0x76543210FDB9ECA8ull;
        const uint32_t kk = (uint32_t)(ord >> (w == 7 ? 0 : 8 * w + (pr == 0 ? 0 : 8)));
        const int k0 = kk & 15, k1 = kk >> 4 & 15;
        #pragma unroll
        for (int t = 1; t <= 2; t++) {
          if (t == 2 && q == 3) mbar_wait(sbase + B_FLG + 32, 0, dl);
          acquire(32768);
          load_b(slot + 16384, col, t == 1 ? k0 : k1);
          tma_load_2d(slot, &maps.h2, fb, (t == 1 ? k0 : k1) * 64, row0);
          if (t == y) {
            acquire(32768);
            load_b(slot, col + 512, k0);
            load_b(slot + 16384, col + 512, k1);
          }
        }
      }
      #pragma unroll 1
      for (int kt = 0; kt < 56; kt++) {
        if ((kt & 7) == 0) mbar_wait(sbase + B_FLG + 40 + kt, 0, dl);
        acquire(32768);
        tma_load_3d(slot + 16384, &maps.w2, fb, 0, kt * 64, 2 * j);
        tma_load_3d(slot, &maps.hh, fb, (kt & 7) * 64, row0, kt >> 3);
      }
    } else {
      const unsigned e1 = 1 + ld_relaxed(wid == 9 ? flags + FO_EPOCH : &mail0->flags[FL_EPOCH]), par = e1 & 1;
      if (wid == 9) {
        #pragma unroll 1
        for (int n = 0; n < 12; n++) {
          if (n == 4) {
            mbar_wait(sbase + B_STH, 0, dl);
            tma_store_2d(&maps.h2, sbase + SM_STG, j * 128, row0);
            bulk_commit();
            bulk_wait0();
            red_add_e(&mail0->flags[FL_H2], 1);
            PROF(84, lane == 0);
            mbar_wait(sbase + B_H2A, 0, dl);
          }
          if (n == 3) mbar_wait(sbase + B_RST, 0, dl);
          const int ht = (n - 5) & 1;
          if (n >= 1 && n <= 4) mbar_wait(sbase + B_STREQ, n & 1, dl);
          else mbar_sleep(n == 0 ? sbase + B_STREQ : sbase + B_HREQ + 8 * ht, n == 0 ? 0 : ((n - 5) >> 1) & 1, dl);
          if (n == 0) fence_proxy_async_smem();
          if (n == 2 || n == 3) tma_store_2d(&maps.o, sbase + SM_STG, (j + 8 * (n - 2)) * 64, row0);
          else if (n == 4) tma_store_2d(&maps.h2, sbase + SM_STG + 16384, j * 128 + 64, row0);
          else tma_store_3d(&maps.hh, sbase + SM_STG + (n < 2 ? n : ht) * 16384, j * 64, row0, n < 2 ? n : n - 5);
          bulk_commit();
          bulk_wait0();
          red_add_e(n == 3 ? &mail0->flags[FL_O] : flags + FO_CNT + n, 1);
          mbar_arrive_e(n < 4 ? sbase + B_STFREE : sbase + B_HFREE + 8 * ht);
          if (n == 4) mbar_arrive_e(sbase + B_HFREE);
          PROFN(70 + n, lane == 0 && n > 0); PROF(85, lane == 0 && n == 0);
          if (n != 3) { wait_flag(flags + FO_CNT + n, e1 * 8, dl); mbar_arrive_e(sbase + B_FLG + 8 * n); }
        }
      } else {
        const float* const mail = &mail0->mod[(b & 7) * 6 * D_ + lane * 4];
        if (wid == 10) {
          #pragma unroll 1
          for (int p = 0; p < 8; p++) {
            if (p >= 2) mbar_wait(p == 2 ? q_empty(0, sbase) : q_empty(2 * p - 5, sbase), p == 2 ? 0 : ((2 * p - 5) >> 2) & 1, dl);
            gather_table(mail + p * 128, sbase + SM_MODT + (p & 3) * 512 + ((lane * 16) ^ ((j >> 1) << 6)), 2 * p - 1 < MSEP ? sbase + B_MOD + 8 * p : sbase + B_FQ + 8 * ((2 * p - 1) & 3), par, dl);
            PROF(63 + p, lane == 0 && p < 7);
          }
          const uint32_t vdst = sbase + SM_VEC + (lane >> 3) * 64 + (lane & 3) * 16 + ((lane >> 2) & 1) * 8;
          #pragma unroll 1
          for (int v = 0; v < 2; v++) {
            mbar_sleep(sbase + B_FLG + 16 + 24 * v, 0, dl);
            uint4 m[3];
            while (true) {
              #pragma unroll
              for (int e = 0; e < 3; e++) m[e] = ld_rlx_v4(mail + (2 + v + e) * 1024 + j * 128);
              if (poll_done(((bad4(m[0], par) | bad4(m[1], par) | bad4(m[2], par)) & 1) == 0, dl)) break;
              __nanosleep(200);
            }
            #pragma unroll
            for (int e = 0; e < 3; e++) sts64(vdst + (v + e) * 256, hi_halves(m[e].x, m[e].y), hi_halves(m[e].z, m[e].w));
            mbar_arrive_e(sbase + B_VEC + 8 * v);
            PROF(70, lane == 0 && v == 0);
          }
        } else {
          mbar_wait(sbase + B_LN, 0, dl);
          red_add_e(&mail0->flags[FL_LN1], 1);
          wait_flag(&mail0->flags[FL_LN1], e1 * NCTA, dl);
          mbar_arrive_e(sbase + B_GATE);
          PROF(41, lane == 0);
          mbar_sleep(sbase + B_FLG, 0, dl);
          #pragma unroll
          for (int e = 0; e < 2; e++) st_rlx_v4(mail0->st2 + ((mb * 8 + e * 4 + (lane >> 3)) * 8 + j) * 8 + (lane & 7), 0, 0, 0, 0, true);
          __threadfence();
          mbar_arrive_e(sbase + B_RST);
          PROF(86, lane == 0);
        }
      }
    }
  } else {
    const int wg = wid >> 2, warp = wid & 3;
    const int g = lane >> 2, qd = lane & 3;
    bulk_prefetch(wmod + (size_t)(b * 8 + wid) * (6 * D_), PF_BYTES);
    bulk_prefetch(wmod + (size_t)(b * 8 + wid) * (6 * D_) + D_, PF_BYTES);
    bar_sync(0, 384);
    bulk_prefetch(wmod + (size_t)(b * 8 + wid) * (6 * D_) + PF_BYTES / 2, PF_BYTES);
    bulk_prefetch(wmod + (size_t)(b * 8 + wid) * (6 * D_) + PF_BYTES / 2 + D_, PF_BYTES);
    const unsigned e1 = 1 + ld_relaxed(flags + FO_EPOCH), par = e1 & 1;
    reg_alloc<232>();
    PROF(1, tid == 0);
    const uint32_t wgoff = wg * 8192;
    const uint32_t frag0 = wid * 2048 + (lane & 15) * 128 + (((lane >> 4) ^ (lane & 7)) << 4);
    const uint32_t slab = sbase + SM_STG + wid * 2048;

    LnRow ln;
    {
      uint2* const lmail = &mail0->ln1[(mb * 8 + (wid & 1) * 4 + (j >> 1)) * 16 + (j & 1) * 8 + (wid >> 1) + (lane & 1) * 4];
      float sm = 0.f, qm = 0.f, so = 0.f, qo = 0.f;
      #pragma unroll
      for (int h = 0; h < 2; h++) {
        sm = so; qm = qo;
        float s[2] = {0.f, 0.f}, q2[2] = {0.f, 0.f};
        mbar_wait(sbase + B_X + 8 * (4 * h + (wid >> 1)), 0, dl);
        PROF(3, tid == 224); PROF(93, tid == 0);
        #pragma unroll
        for (int c = 0; c < 4; c++) {
          const uint4 v = lds128(sbase + SM_XR + h * 16384 + wid * 2048 + c * 512 + lane * 16);
          const uint32_t vv[4] = {v.x, v.y, v.z, v.w};
          #pragma unroll
          for (int e = 0; e < 4; e++) {
            const float lo = bf_lo(vv[e]), hi = bf_hi(vv[e]);
            s[0] += lo; s[1] += hi; q2[0] = fmaf(lo, lo, q2[0]); q2[1] = fmaf(hi, hi, q2[1]);
          }
        }
        so = s[0] + s[1]; qo = q2[0] + q2[1];
      }
      const bool odd = lane & 1;
      { const float a = odd ? so : sm, c = odd ? qo : qm;
        sm = a + __shfl_xor_sync(0xffffffffu, odd ? sm : so, 1); qm = c + __shfl_xor_sync(0xffffffffu, odd ? qm : qo, 1); }
      #pragma unroll
      for (int o = 2; o < 32; o <<= 1) { sm += __shfl_xor_sync(0xffffffffu, sm, o); qm += __shfl_xor_sync(0xffffffffu, qm, o); }
      sm *= (1.f / D_);
      ln_row(ln, 0, sm, fast_rsqrt(fmaxf(qm * (1.f / D_) - sm * sm, 0.f) + 1e-5f));
      st_rlx_v2(lmail, (ln.rs[0] << 16) | par, (ln.nb[0] << 16) | par, lane < 2);
      mbar_arrive_e(sbase + B_LN);
      PROF(4, tid == 224);
    }

    uint4* const halo_out = mail0->halo[par] + ((mb * 16 + j) * 2 + wg) * 128 + lane;
    const uint4* const halo_in = halo_out - 16 * 256;
    const uint32_t xch = sbase + SM_XCH + (tid >> 5) * 2048 + lane * 16;
    const bool noprev = mb == 0 && warp == 0, remote = mb > 0 && warp == 0;
    float a0[64], a1[64];
    uint32_t x2[32];
    Ring r{zero, 0, 0, dl};
    Frag8 qA, qB, kA, kB, vA, vB, wA, wB;
    {
      float acc[128];
      uint32_t A0[16], A1[16];
      undef_regs(acc);
      const uint32_t tab = sbase + SM_MODT + qd * 16;
      uint4 p[4];
      const uint32_t rot = j >> 1;
      Frag4 fq;
      #pragma unroll
      for (int q = 0; q < 4; q++) fq.o[q] = frag0 ^ ((q ^ rot) << 5);
      mbar_wait(sbase + B_LN, 0, dl);
      const uint2* const lin = &mail0->ln1[(mb * 8 + wid) * 16 + g];
      uint2 v0, v1;
      q_wait(0, sbase, dl);
      #pragma unroll
      for (int kk = 0; kk < 4; kk++) ldmatrix_x4(sbase + SM_X0 + fq.o[kk], A0[4 * kk], A0[4 * kk + 1], A0[4 * kk + 2], A0[4 * kk + 3]);
      do { v0 = ld_rlx_v2(lin); v1 = ld_rlx_v2(lin + 8); } while (!poll_done(((bad2(v0.x, v0.y, par) | bad2(v1.x, v1.y, par)) & 1) == 0, dl));
      ln.rs[0] = hi_halves(v0.x, v0.x); ln.nb[0] = hi_halves(v0.y, v0.y); ln.rs[1] = hi_halves(v1.x, v1.x); ln.nb[1] = hi_halves(v1.y, v1.y);
      mbar_wait(sbase + B_MOD, 0, dl);
      #pragma unroll
      for (int kk = 0; kk < 4; kk++) p[kk] = lds128(tab + kk * 64);
      PROF(5, tid == 0);
      q_step_rs<true>(acc, A0, A1, p, 0, sbase, fq, tab, ln, rot, !(j & 1), true, dl, wg, zero);
      #pragma unroll
      for (int u = 1; u < 15; u += 2) {
        q_step_rs<true>(acc, A1, A0, p, u, sbase, fq, tab, ln, rot, j & 1, false, dl, wg, zero);
        q_step_rs<true>(acc, A0, A1, p, u + 1, sbase, fq, tab, ln, rot, !(j & 1), false, dl, wg, zero);
        if (u == 7) mbar_arrive_e(sbase + B_STREQ);
      }
      q_step_rs<false>(acc, A1, A0, p, 15, sbase, fq, tab, ln, rot, j & 1, false, dl, wg, zero);
      PROF(7, tid == 0);
      mbar_wait(sbase + B_STFREE, 0, dl);
      request_store(sbase + B_STREQ);
      wgmma_wait<0>();
      undef_regs(a0);
      { const uint32_t slot = m_wait(sbase, r); mma_step(a0, slot + wgoff, slot + 16384, true, q_empty(15, sbase)); m_next(r); }
      fence_regs(acc);
      PROF(8, tid == 0);
      sched_fence(zero);
      pack_half(vB, acc, 64, 1); transpose8(vB);
      m_step(a0, sbase, wgoff, r);
      sched_fence(zero);
      pack_half(kB, acc, 32, 1);
      attn_send(vB, 1, xch - 16384, warp, halo_out, mb < 15); attn_send(kB, 0, xch - 16384, warp, halo_out, mb < 15);
      m_step(a0, sbase, wgoff, r);
      sched_fence(zero);
      pack_half(qA, acc, 0, 0); pack_half(qB, acc, 0, 1); pack_half(kA, acc, 32, 0); pack_half(wB, acc, 96, 1); pack_half(wA, acc, 96, 0);
      m_step(a0, sbase, wgoff, r);
      sched_fence(zero);
      pack_half(vA, acc, 64, 0); transpose8(vA);
    }
    uint4 wP[2];
    Frag4 frag;
    #pragma unroll
    for (int q = 0; q < 4; q++) frag.o[q] = frag0 ^ (q << 5);
    {
      m_step(a0, sbase, wgoff, r);
      uint4 pv[4];
      attn_recv<4>(pv, 0, xch - 16384, wg, warp, halo_in, mb > 0);
      m_step(a0, sbase, wgoff, r);
      mbar_wait(sbase + B_STFREE, 1, dl);
      transpose8(wB);
      m_step(a0, sbase, wgoff, r);
      attn_check<4>(pv, 0, remote, halo_in, dl);
      wgmma_wait<0>();
      PROF(9, tid == 0);
      float o[2][5][4];
      sched_fence(zero);
      attn_core<0>(qA, qB, kA, kB, vA, vB, pv, pv + 2, noprev, lane, o, Nop());
      attn_store(o, 0, sbase, frag);
      attn_store(o, 1, sbase, frag);
      request_store(sbase + B_STREQ);
      bar_sync(NB_CONS, 256);
      PROF(10, tid == 0);
      m_step(a0, sbase, wgoff, r);
      sched_fence(zero);
      attn_send(wB, 1, xch, warp, halo_out + 8 * 256, mb < 15);
      m_step(a0, sbase, wgoff, r);
      sched_fence(zero);
      transpose8(wA);
      #pragma unroll 1
      for (int i = 9; i < 15; i++) m_step(a0, sbase, wgoff, r);
      attn_recv<2>(wP, 2, xch, wg, warp, halo_in + 8 * 256, mb > 0);
      m_step(a0, sbase, wgoff, r);
    }
    {
      undef_regs(a1);
      {
        const uint32_t slot = m_wait(sbase, r);
        mma_step(a1, slot + wgoff, slot + 16384, true, m_prev(sbase, r), [&] {
          fence_regs(a0);
          pack_half(kB, a0, 32, 1);
          attn_send(kB, 0, xch, warp, halo_out + 8 * 256, mb < 15);
        });
        m_next(r);
      }
      PROF(14, tid == 0);
      sched_fence(zero);
      pack_half(kA, a0, 32, 0); pack_half(qA, a0, 0, 0); pack_half(qB, a0, 0, 1);
      m_step(a1, sbase, wgoff, r);
      attn_check<2>(wP, 2, remote, halo_in + 8 * 256, dl);
      uint4 kP[2];
      attn_recv<2>(kP, 0, xch, wg, warp, halo_in + 8 * 256, mb > 0);
      m_step(a1, sbase, wgoff, r);
      if (ASPLIT == 0) attn_check<2>(kP, 0, remote, halo_in + 8 * 256, dl);
      wgmma_wait<0>();
      PROF(15, tid == 0);
      float o[2][5][4];
      mbar_wait(sbase + B_STFREE, 0, dl);
      attn_core<ASPLIT>(qA, qB, kA, kB, wA, wB, kP, wP, noprev, lane, o, [&] { attn_check<2>(kP, 0, remote, halo_in + 8 * 256, dl); });
      attn_store(o, 0, sbase, frag);
      attn_store(o, 1, sbase, frag);
      request_store(sbase + B_STREQ);
      bar_sync(NB_CONS, 256);
      PROF(16, tid == 0);
      auto residual = [&] {
        const uint32_t xs = m_wait(sbase, r), xe = sbase + B_EM + 8 * r.st;
        ring_next(r);
        #pragma unroll
        for (int t = 0; t < 2; t++) {
          #pragma unroll
          for (int jj = 4 * t; jj < 4 * t + 4; jj++) ldmatrix_x4(xs + t * 16384 + frag.o[jj & 3], x2[4 * jj], x2[4 * jj + 1], x2[4 * jj + 2], x2[4 * jj + 3]);
          if (t == 1) {
            uint32_t dep = 0;
            #pragma unroll
            for (int jj = 0; jj < 8; jj++) dep |= x2[4 * jj];
            mbar_arrive_e(xe + (dep & zero));
          }
          m_step(a1, sbase, wgoff, r);
        }
      };
      m_step(a1, sbase, wgoff, r);
      residual();
      #pragma unroll 1
      for (int i = 6; i < 8; i++) m_step(a1, sbase, wgoff, r);
      mma_step(a1, sbase + SM_STG + wgoff, m_wait(sbase, r) + 16384, false, m_prev(sbase, r));
      m_next(r);
      PROF(17, tid == 0);
      #pragma unroll 1
      for (int i = 0; i < 7; i++) { m_step(a1, sbase, wgoff, r); PROF(42, tid == 0 && i == 0); }
      PROF(45, tid == 0);
      uint4* sm = mail0->st2 + (mb * 8 + wid) * 64 + g;
      asm volatile("" : "+l"(sm));
      mbar_wait(sbase + B_VEC, 0, dl);
      mbar_wait(sbase + B_STFREE, 1, dl);
      const uint32_t vec = sbase + SM_VEC + qd * 16;
      uint4 ga[4];
      #pragma unroll
      for (int q = 0; q < 4; q++) ga[q] = lds128(vec + q * 64);
      wgmma_wait<0>();
      mbar_arrive_e(m_prev(sbase, r));
      fence_regs(a1);
      PROF(18, tid == 0);
      float gl[4] = {0.f, 0.f, 0.f, 0.f}, gh[4] = {0.f, 0.f, 0.f, 0.f};
      #pragma unroll
      for (int jj = 0; jj < 8; jj++) {
        uint32_t* v = &x2[4 * jj];
        const uint32_t wl = (jj & 1) ? ga[jj >> 1].z : ga[jj >> 1].x, wh = (jj & 1) ? ga[jj >> 1].w : ga[jj >> 1].y;
        #pragma unroll
        for (int e = 0; e < 4; e++) v[e] = fma_bf2(e & 2 ? wh : wl, pack_bf16(a1[8 * jj + 2 * e], a1[8 * jj + 2 * e + 1]), v[e]);
        mma16(gl, v[0], 0x3F803F80u, v[2], 0x3F803F80u, v[0], v[2]);
        mma16(gh, v[1], 0x3F803F80u, v[3], 0x3F803F80u, v[1], v[3]);
      }
      st_nonzero_v4(sm + j * 8, __float_as_uint(g & 1 ? gl[3] : gl[2]), __float_as_uint(g & 1 ? gl[1] : gl[0]),
                __float_as_uint(g & 1 ? gh[3] : gh[2]), __float_as_uint(g & 1 ? gh[1] : gh[0]), qd == (g >> 1));
      float s[2], q2[2];
      PROF(19, tid == 0);
      uint4 sb[4], cb[4];
      #pragma unroll
      for (int q = 0; q < 4; q++) { sb[q] = lds128(vec + 256 + q * 64); cb[q] = lds128(vec + 512 + q * 64); }
      uint4 p0, p1;
      while (true) {
        p0 = ld_rlx_v4(sm + qd * 16); p1 = ld_rlx_v4(sm + qd * 16 + 8);
        if (poll_done(min(min4(p0), min4(p1)) != 0, dl)) break;
      }
      PROF(20, tid == 0);
      s[0] = __uint_as_float(p0.x) + __uint_as_float(p1.x); q2[0] = __uint_as_float(p0.y) + __uint_as_float(p1.y);
      s[1] = __uint_as_float(p0.z) + __uint_as_float(p1.z); q2[1] = __uint_as_float(p0.w) + __uint_as_float(p1.w);
      #pragma unroll
      for (int o2 = 1; o2 <= 2; o2 <<= 1)
        #pragma unroll
        for (int h = 0; h < 2; h++) { s[h] += __shfl_xor_sync(0xffffffffu, s[h], o2); q2[h] += __shfl_xor_sync(0xffffffffu, q2[h], o2); }
      #pragma unroll
      for (int h = 0; h < 2; h++) {
        const float m = s[h] * (1.f / D_);
        ln_row(ln, h, m, fast_rsqrt(fmaxf(q2[h] * (1.f / D_) - m * m, 0.f) + 1e-5f));
      }
      #pragma unroll
      for (int jj = 0; jj < 8; jj++) {
        const uint32_t cl = (jj & 1) ? cb[jj >> 1].z : cb[jj >> 1].x, ch = (jj & 1) ? cb[jj >> 1].w : cb[jj >> 1].y;
        const uint32_t sl = (jj & 1) ? sb[jj >> 1].z : sb[jj >> 1].x, sh = (jj & 1) ? sb[jj >> 1].w : sb[jj >> 1].y;
        stmatrix_x4(sbase + SM_STG + (jj >> 2) * 16384 + frag.o[jj & 3], ln_mod(x2[4 * jj], ln, 0, cl, sl), ln_mod(x2[4 * jj + 1], ln, 1, cl, sl),
                    ln_mod(x2[4 * jj + 2], ln, 0, ch, sh), ln_mod(x2[4 * jj + 3], ln, 1, ch, sh));
        if (jj == 3) { request_store(sbase + B_STH); sched_fence(zero); }
      }
      request_store(sbase + B_STREQ);
      bar_sync(NB_WG + wg, 128);
      PROF(21, tid == 0);
    }

    undef_regs(a0);
    #pragma unroll
    for (int t = 0; t < 2; t++) {
      const uint32_t slot = m_wait(sbase, r);
      if (t == 0) mma_step<false>(a0, sbase + SM_STG + wgoff, slot, true, 0);
      else mma_step(a0, sbase + SM_STG + 16384 + wgoff, slot, false, m_prev(sbase, r));
      mma_step<false>(a1, sbase + SM_STG + t * 16384 + wgoff, slot + 16384, t == 0, 0);
      m_next(r);
    }
    PROF(22, tid == 0);
    #pragma unroll 1
    for (int i = 0; i < 2; i++) m_step(a0, sbase, wgoff, r);
    uint32_t held = 0;
    #pragma unroll 1
    for (int pr = 0; pr < 3; pr++) {
      #pragma unroll 1
      for (int i = 0; i < 5; i++) { g_quad(a0, a1, held, sbase, wgoff, r); held = 0; }
      held = g_ppqq<false, true>(a0, a1, false, 0, sbase, wgoff, r, [&](int i) { if (i >= 2) g_piece<0>(a0, i - 2, pr, sbase, frag, dl); });
      held = g_ppqq<true, true>(a1, a0, true, held, sbase, wgoff, r,
                                [&](int i) { if (i < 2) g_piece<0>(a0, i + 2, pr, sbase, frag, dl); else g_piece<1>(a1, i - 2, pr, sbase, frag, dl); });
      if (pr == 2) break;
      held = g_ppqq<true, true>(a0, a1, true, held, sbase, wgoff, r, [&](int i) { if (i < 2) g_piece<1>(a1, i + 2, pr, sbase, frag, dl); });
    }
    g_ppqq<true, false>(a0, a1, false, held, sbase, wgoff, r, [&](int i) { g_piece<1>(a1, i + 2, 2, sbase, frag, dl); });
    #pragma unroll 1
    for (int i = 4; i < 15; i++) m_step(a0, sbase, wgoff, r);
    m_step(a0, sbase, wgoff, r);
    #pragma unroll
    for (int jj = 0; jj < 4; jj++) { m_step(a1, sbase, wgoff, r, jj == 0); g_piece<0>(a0, jj, 3, sbase, frag, dl); }
    #pragma unroll 1
    for (int i = 4; i < 56 - DTAIL; i++) m_step(a1, sbase, wgoff, r);
    if (DTAIL) {
      if (wg == 1) { wgmma_wait<0>(); mbar_arrive_e(m_prev(sbase, r)); bar_sync(NB_ORD, 256); }
      #pragma unroll 1
      for (int i = 0; i < DTAIL; i++) {
        const uint32_t slot = m_wait(sbase, r);
        const uint32_t alo = ((slot + wgoff) >> 4) + (1u << 16), blo = ((slot + 16384) >> 4) + (512u << 16);
        wgmma_fence();
        #pragma unroll
        for (int k = 0; k < 4; k++) wgmma_m64n128k16_ss(a1, desc_from_lo(alo + k * 2), desc_from_lo(blo + k * 128), true);
        wgmma_commit();
        ring_next(r);
      }
      if (wg == 0) bar_arrive(NB_ORD, 256);
    }
    {
      mbar_wait(sbase + B_HFREE, 0, dl);
      mbar_wait(sbase + B_HFREE + 8, 1, dl);
      mbar_wait(sbase + B_VEC + 8, 0, dl);
      uint4 gb[4];
      #pragma unroll
      for (int q = 0; q < 4; q++) gb[q] = lds128(sbase + SM_VEC + 768 + qd * 16 + q * 64);
      wgmma_wait<0>();
      fence_regs(a1);
      PROF(50, tid == 128);
      #pragma unroll
      for (int t = 0; t < 2; t++) {
        #pragma unroll
        for (int jj = 4 * t; jj < 4 * t + 4; jj++) {
          const uint32_t gl = (jj & 1) ? gb[jj >> 1].z : gb[jj >> 1].x, gh = (jj & 1) ? gb[jj >> 1].w : gb[jj >> 1].y;
          const int i = 8 * jj;
          stmatrix_x4(sbase + SM_STG + t * 16384 + frag.o[jj & 3],
                      fma_bf2(gl, pack_bf16(a1[i], a1[i + 1]), x2[4 * jj]), fma_bf2(gl, pack_bf16(a1[i + 2], a1[i + 3]), x2[4 * jj + 1]),
                      fma_bf2(gh, pack_bf16(a1[i + 4], a1[i + 5]), x2[4 * jj + 2]), fma_bf2(gh, pack_bf16(a1[i + 6], a1[i + 7]), x2[4 * jj + 3]));
        }
        fence_proxy_async_smem();
        tma_store_3d(&maps.out, slab + t * 16384, j * 128 + t * 64, mb * 64 + warp * 16, wg);
      }
      bulk_commit();
      st_rlx(tid == 0 ? flags + FO_EPOCH : &mail0->flags[FL_EPOCH], e1, j == 0 && (tid == 0 || (tid == 1 && mb == 0)));
      bulk_wait_read0();
      PROFN(51, tid == 128);
    }
  }
}

typedef CUresult (*PFN_encodeTiled)(CUtensorMap*, CUtensorMapDataType, cuuint32_t, void*, const cuuint64_t*, const cuuint64_t*,
                                    const cuuint32_t*, const cuuint32_t*, CUtensorMapInterleave, CUtensorMapSwizzle,
                                    CUtensorMapL2promotion, CUtensorMapFloatOOBfill);

void encode(PFN_encodeTiled fn, CUtensorMap* m, const void* ptr, int rank, const cuuint64_t* dims, const cuuint64_t* strides,
            const cuuint32_t* box) {
  const cuuint32_t es[5] = {1, 1, 1, 1, 1};
  fn(m, CU_TENSOR_MAP_DATA_TYPE_BFLOAT16, rank, const_cast<void*>(ptr), dims, strides, box, es, CU_TENSOR_MAP_INTERLEAVE_NONE,
     CU_TENSOR_MAP_SWIZZLE_128B, CU_TENSOR_MAP_L2_PROMOTION_L2_256B, CU_TENSOR_MAP_FLOAT_OOB_FILL_NONE);
}
void map2d(PFN_encodeTiled fn, CUtensorMap* m, const void* ptr, int cols, int rows, int boxrows) {
  const cuuint64_t dims[2] = {(cuuint64_t)cols, (cuuint64_t)rows}, strides[1] = {(cuuint64_t)cols * 2};
  const cuuint32_t box[2] = {64, (cuuint32_t)boxrows};
  encode(fn, m, ptr, 2, dims, strides, box);
}
void map_w2chunk(PFN_encodeTiled fn, CUtensorMap* m, const void* ptr, int cols, int rows) {
  const cuuint64_t dims[3] = {64, (cuuint64_t)rows, (cuuint64_t)cols / 64}, strides[2] = {(cuuint64_t)cols * 2, 128};
  const cuuint32_t box[3] = {64, 64, 2};
  encode(fn, m, ptr, 3, dims, strides, box);
}
void map_parity(PFN_encodeTiled fn, CUtensorMap* m, const void* ptr, int boxpairs, int boxpar) {
  const cuuint64_t dims[3] = {D_, S_ / 2, 2}, strides[2] = {D_ * 4, D_ * 2};
  const cuuint32_t box[3] = {64, (cuuint32_t)boxpairs, (cuuint32_t)boxpar};
  encode(fn, m, ptr, 3, dims, strides, box);
}

}

extern "C" void kernel_launch(void* const* d_in, const int* in_sizes, int n_in, void* d_out, int out_size) {
  (void)in_sizes; (void)n_in; (void)out_size;
  const bf16* x = (const bf16*)d_in[0];
  const bf16* wqkv = (const bf16*)d_in[1];
  const bf16* wo = (const bf16*)d_in[2];
  const bf16* w1 = (const bf16*)d_in[4];
  const bf16* w3 = (const bf16*)d_in[5];
  const bf16* w2 = (const bf16*)d_in[6];
  const bf16* cvec = (const bf16*)d_in[7];
  const bf16* w_mod = (const bf16*)d_in[8];

  static PFN_encodeTiled fn = nullptr;
  static Maps maps;
  static const void* cached[8] = {};
  static int sms = 0;
  static void* mail = nullptr;
  if (!fn) {
    void* p = nullptr; cudaDriverEntryPointQueryResult st;
    cudaGetDriverEntryPoint("cuTensorMapEncodeTiled", &p, cudaEnableDefault, &st);
    fn = (PFN_encodeTiled)p;
    cudaFuncSetAttribute(fused_block_kernel<0>, cudaFuncAttributeMaxDynamicSharedMemorySize, SM_TOTAL + SM_PROF);
    cudaFuncSetAttribute(fused_block_kernel<1>, cudaFuncAttributeMaxDynamicSharedMemorySize, SM_TOTAL + SM_PROF);
    cudaFuncSetAttribute(fused_block_kernel<2>, cudaFuncAttributeMaxDynamicSharedMemorySize, SM_TOTAL + SM_PROF);
    cudaGetSymbolAddress(&mail, g_mail);
    int dev = 0;
    cudaGetDevice(&dev);
    cudaDeviceGetAttribute(&sms, cudaDevAttrMultiProcessorCount, dev);
  }
  const void* cur[8] = {x, wqkv, wo, w1, w3, w2, d_out, w_mod};
  bool same = true;
  for (int i = 0; i < 8; i++) same = same && cached[i] == cur[i];
  if (!same) {
    void *o, *h2, *hh;
    cudaGetSymbolAddress(&hh, g_hh); cudaGetSymbolAddress(&o, g_o);
    h2 = o;
    map_parity(fn, &maps.x, x, 64, 2); map_parity(fn, &maps.out, d_out, 16, 1);
    map2d(fn, &maps.o, o, D_, S_, 128); map2d(fn, &maps.h2, h2, D_, S_, 128);
    {
      const cuuint64_t dims[3] = {512, (cuuint64_t)S_, 7}, strides[2] = {1024, (cuuint64_t)S_ * 1024};
      const cuuint32_t box[3] = {64, 128, 1};
      encode(fn, &maps.hh, hh, 3, dims, strides, box);
    }
    {
      const cuuint64_t dims[4] = {64, 1024, 16, 2}, strides[3] = {3072 * 2, 128, 2048};
      const cuuint64_t dimv[4] = {64, 1024, 8, 2}, stridev[3] = {3072 * 2, 128, 1024};
      const cuuint32_t box[4] = {64, 64, 1, 2};
      encode(fn, &maps.wqk, wqkv, 4, dims, strides, box);
      encode(fn, &maps.wvv, wqkv + 2048, 4, dimv, stridev, box);
      const cuuint64_t dim1[4] = {1024, 128, 8, 2}, stride1[3] = {3072 * 2, 128 * 3072 * 2, 2048};
      const cuuint32_t box1[4] = {64, 16, 4, 2};
      encode(fn, &maps.wq1, wqkv, 4, dim1, stride1, box1);
    }
    map_w2chunk(fn, &maps.wo, wo, D_, D_); map_w2chunk(fn, &maps.w2, w2, D_, F_);
    map2d(fn, &maps.w1, w1, F_, D_, 64); map2d(fn, &maps.w3, w3, F_, D_, 64);
    map2d(fn, &maps.wmod, w_mod, 6 * D_, D_, 256);
    for (int i = 0; i < 8; i++) cached[i] = cur[i];
  }
  if (sms == NCTA + NAUX) {
    fused_block_kernel<0><<<NCTA + NAUX, 384, SM_TOTAL + SM_PROF>>>(x, cvec, w_mod, (Mail*)mail, 0, maps);
  } else {
    fused_block_kernel<1><<<NAUX, 384, SM_TOTAL + SM_PROF>>>(x, cvec, w_mod, (Mail*)mail, 0, maps);
    fused_block_kernel<2><<<NCTA, 384, SM_TOTAL + SM_PROF>>>(x, cvec, w_mod, (Mail*)mail, 0, maps);
  }
}
```

```cpp
#include <cuda.h>
#include <cuda_runtime.h>
#include <cuda_bf16.h>
#include <stdint.h>

namespace {

typedef __nv_bfloat16 bf16;

constexpr int S_ = 2048, D_ = 1024, F_ = 3584;
constexpr int NCTA = 128, NAUX = 4;

__device__ __align__(1024) bf16 g_o[S_ * D_];
__device__ __align__(1024) bf16 g_hh[S_ * F_];
constexpr int FO_EPOCH = 0, FO_CNT = 1;
constexpr int FL_EPOCH = 16 * 32, FL_LN1 = FL_EPOCH + 2, FL_H2 = FL_EPOCH + 3, FL_O = FL_EPOCH + 4;
struct Mail {
  unsigned flags[32 * 32];
  float mod[8 * 6 * D_];
  uint2 ln1[16 * 8 * 16];
  uint4 st2[16 * 8 * 8 * 8];
  uint4 halo[2][16 * 16 * 2 * 4 * 32];
};
__device__ __align__(1024) Mail g_mail;

template <int mode>
__device__ __forceinline__ int cta_role() {
  if (mode) return mode == 1 ? NCTA + (blockIdx.x & 3) : blockIdx.x & 127;
  uint32_t sm;
  asm("mov.u32 %0, %%smid;" : "=r"(sm));
  sm = (sm & ~3u) == 12 ? sm + 108 : (sm & ~3u) == 120 ? sm - 108 : sm;
  const int t = sm >> 1;
  int r;
  if (t < 32) r = (t & 7) * 16 + (t >> 3) * 2 + (sm & 1);
  else if (t < 60) r = (1 + (t - 32) % 7) * 16 + 8 + ((t - 32) / 7) * 2 + (sm & 1);
  else if (t < 62) r = NCTA + sm - 120;
  else r = sm - 116;
  return r;
}
#define PROF(slot, on) do {} while (0)
#define PROFN(slot, on) do {} while (0)
#define PROF_OUT(role, t) do {} while (0)
constexpr uint32_t SM_PROF = 0;

__device__ __forceinline__ uint32_t smem_u32(const void* p) { return (uint32_t)__cvta_generic_to_shared(p); }
#define ELECT "{\n.reg .pred p;\nelect.sync _|p, 0xffffffff;\n@p "
__device__ __forceinline__ void mbar_init_e(uint32_t bar, uint32_t count) {
  asm volatile(ELECT "mbarrier.init.shared::cta.b64 [%0], %1;\n}" :: "r"(bar), "r"(count) : "memory");
}
__device__ __forceinline__ void mbar_expect_tx_e(uint32_t bar, uint32_t bytes) {
  asm volatile(ELECT "mbarrier.arrive.expect_tx.shared::cta.b64 _, [%0], %1;\n}" :: "r"(bar), "r"(bytes) : "memory");
}
__device__ __forceinline__ void mbar_arrive_e(uint32_t bar) {
  asm volatile(ELECT "mbarrier.arrive.shared::cta.b64 _, [%0];\n}" :: "r"(bar) : "memory");
}
__device__ __forceinline__ uint32_t clock32() { uint32_t t; asm volatile("mov.u32 %0, %%clock;" : "=r"(t)); return t; }
#define WAIT_TAIL "setp.ne.and.u32 p, %2, 0, !p;\n@p bra LAB_WAIT;\n}"
__device__ __forceinline__ void mbar_wait(uint32_t bar, uint32_t parity, uint32_t dl) {
  asm volatile("{\n.reg .pred p;\n.reg .b32 t;\nLAB_WAIT:\nmbarrier.try_wait.parity.shared::cta.b64 p, [%0], %1;\n" WAIT_TAIL
               :: "r"(bar), "r"(parity), "r"(dl) : "memory");
}
__device__ __forceinline__ void mbar_sleep(uint32_t bar, uint32_t parity, uint32_t dl) {
  asm volatile("{\n.reg .pred p;\n.reg .b32 t;\nLAB_WAIT:\nmbarrier.try_wait.parity.shared::cta.b64 p, [%0], %1, 20000;\n" WAIT_TAIL
               :: "r"(bar), "r"(parity), "r"(dl) : "memory");
}
__device__ __forceinline__ bool poll_done(bool ok, uint32_t dl) {
  return __all_sync(0xffffffffu, ok || (int)(clock32() - dl) >= 0);
}
__device__ __forceinline__ unsigned ld_relaxed(const unsigned* p) {
  unsigned v; asm volatile("ld.relaxed.gpu.global.u32 %0, [%1];" : "=r"(v) : "l"(p) : "memory"); return v;
}
__device__ __forceinline__ void red_add_e(unsigned* p, unsigned v) {
  asm volatile(ELECT "red.relaxed.gpu.global.add.u32 [%0], %1;\n}" :: "l"(p), "r"(v) : "memory");
}
__device__ __forceinline__ void wait_flag(const unsigned* p, unsigned target, uint32_t dl) {
  asm volatile("{\n.reg .pred p;\n.reg .b32 t;\n"
               "LAB_WAIT:\n"
               "ld.relaxed.gpu.global.u32 t, [%0];\n"
               "sub.s32 t, t, %1;\n"
               "setp.ge.s32 p, t, 0;\n"
               "@p bra LAB_DONE;\n"
               "mov.u32 t, %%clock;\n"
               "sub.s32 t, t, %2;\n"
               "setp.lt.s32 p, t, 0;\n"
               "@p bra LAB_WAIT;\n"
               "LAB_DONE:\n}" :: "l"(p), "r"(target), "r"(dl) : "memory");
}
__device__ __forceinline__ void wait_until(uint32_t t) { while ((int)(clock32() - t) < 0) {} }
__device__ __forceinline__ void fence_proxy_async_smem() { asm volatile("fence.proxy.async.shared::cta;" ::: "memory"); }

constexpr uint64_t EVICT_FIRST = 0x12F0000000000000ull;
template <bool STREAM = false>
__device__ __forceinline__ void tma_load_2d(uint32_t dst, const CUtensorMap* m, uint32_t bar, int c0, int c1) {
  if (STREAM)
    asm volatile(ELECT "cp.async.bulk.tensor.2d.shared::cluster.global.mbarrier::complete_tx::bytes.L2::cache_hint [%0], [%1, {%3, %4}], [%2], %5;\n}"
                 :: "r"(dst), "l"(m), "r"(bar), "r"(c0), "r"(c1), "l"(EVICT_FIRST) : "memory");
  else
    asm volatile(ELECT "cp.async.bulk.tensor.2d.shared::cluster.global.mbarrier::complete_tx::bytes [%0], [%1, {%3, %4}], [%2];\n}"
                 :: "r"(dst), "l"(m), "r"(bar), "r"(c0), "r"(c1) : "memory");
}
template <bool STREAM = false>
__device__ __forceinline__ void tma_load_3d(uint32_t dst, const CUtensorMap* m, uint32_t bar, int c0, int c1, int c2) {
  if (STREAM)
    asm volatile(ELECT "cp.async.bulk.tensor.3d.shared::cluster.global.mbarrier::complete_tx::bytes.L2::cache_hint [%0], [%1, {%3, %4, %5}], [%2], %6;\n}"
                 :: "r"(dst), "l"(m), "r"(bar), "r"(c0), "r"(c1), "r"(c2), "l"(EVICT_FIRST) : "memory");
  else
    asm volatile(ELECT "cp.async.bulk.tensor.3d.shared::cluster.global.mbarrier::complete_tx::bytes [%0], [%1, {%3, %4, %5}], [%2];\n}"
                 :: "r"(dst), "l"(m), "r"(bar), "r"(c0), "r"(c1), "r"(c2) : "memory");
}
template <bool STREAM = false>
__device__ __forceinline__ void tma_load_4d(uint32_t dst, const CUtensorMap* m, uint32_t bar, int c0, int c1, int c2, int c3) {
  if (STREAM)
    asm volatile(ELECT "cp.async.bulk.tensor.4d.shared::cluster.global.mbarrier::complete_tx::bytes.L2::cache_hint [%0], [%1, {%3, %4, %5, %6}], [%2], %7;\n}"
                 :: "r"(dst), "l"(m), "r"(bar), "r"(c0), "r"(c1), "r"(c2), "r"(c3), "l"(EVICT_FIRST) : "memory");
  else
    asm volatile(ELECT "cp.async.bulk.tensor.4d.shared::cluster.global.mbarrier::complete_tx::bytes [%0], [%1, {%3, %4, %5, %6}], [%2];\n}"
                 :: "r"(dst), "l"(m), "r"(bar), "r"(c0), "r"(c1), "r"(c2), "r"(c3) : "memory");
}
__device__ __forceinline__ void tma_store_2d(const CUtensorMap* m, uint32_t src, int c0, int c1) {
  asm volatile(ELECT "cp.async.bulk.tensor.2d.global.shared::cta.bulk_group [%0, {%2, %3}], [%1];\n}"
               :: "l"(m), "r"(src), "r"(c0), "r"(c1) : "memory");
}
__device__ __forceinline__ void tma_store_3d(const CUtensorMap* m, uint32_t src, int c0, int c1, int c2) {
  asm volatile(ELECT "cp.async.bulk.tensor.3d.global.shared::cta.bulk_group [%0, {%2, %3, %4}], [%1];\n}"
               :: "l"(m), "r"(src), "r"(c0), "r"(c1), "r"(c2) : "memory");
}
__device__ __forceinline__ void bulk_load(uint32_t dst, const void* src, uint32_t bytes, uint32_t bar) {
  asm volatile(ELECT "cp.async.bulk.shared::cluster.global.mbarrier::complete_tx::bytes [%0], [%1], %2, [%3];\n}"
               :: "r"(dst), "l"(src), "r"(bytes), "r"(bar) : "memory");
}
__device__ __forceinline__ void bulk_prefetch(const void* src, uint32_t bytes) {
  asm volatile(ELECT "cp.async.bulk.prefetch.L2.global [%0], %1;\n}" :: "l"(src), "r"(bytes) : "memory");
}
__device__ __forceinline__ void bulk_commit() { asm volatile("cp.async.bulk.commit_group;" ::: "memory"); }
__device__ __forceinline__ void bulk_wait0() { asm volatile("cp.async.bulk.wait_group 0;" ::: "memory"); }
__device__ __forceinline__ void bulk_wait_read0() { asm volatile("cp.async.bulk.wait_group.read 0;" ::: "memory"); }
__device__ __forceinline__ void prefetch_tmap(const CUtensorMap* m) { asm volatile(ELECT "prefetch.tensormap [%0];\n}" :: "l"(m) : "memory"); }
__device__ __forceinline__ void wgmma_fence() { asm volatile("wgmma.fence.sync.aligned;" ::: "memory"); }
__device__ __forceinline__ void wgmma_commit() { asm volatile("wgmma.commit_group.sync.aligned;" ::: "memory"); }
template <int N> __device__ __forceinline__ void wgmma_wait() { asm volatile("wgmma.wait_group.sync.aligned %0;" :: "n"(N) : "memory"); }
template <int R> __device__ __forceinline__ void reg_alloc() { asm volatile("setmaxnreg.inc.sync.aligned.u32 %0;" :: "n"(R)); }
template <int R> __device__ __forceinline__ void reg_dealloc() { asm volatile("setmaxnreg.dec.sync.aligned.u32 %0;" :: "n"(R)); }
__device__ __forceinline__ void bar_sync(int id, int n) { asm volatile("bar.sync %0, %1;" :: "r"(id), "r"(n) : "memory"); }
__device__ __forceinline__ void bar_arrive(int id, int n) { asm volatile("bar.arrive %0, %1;" :: "r"(id), "r"(n) : "memory"); }
__device__ __forceinline__ void sched_fence(int zero) {
  asm volatile("{\n.reg .pred p;\n.reg .b32 t;\nsetp.eq.s32 p, %0, 0;\n@p bra.uni LAB_S;\n"
               "LAB_F:\nmov.u32 t, %%clock;\nsetp.eq.u32 p, t, 0;\n@p bra LAB_F;\nLAB_S:\n}" :: "r"(zero) : "memory");
}
template <int N> __device__ __forceinline__ void fence_regs(float (&a)[N]) {
  #pragma unroll
  for (int i = 0; i < N; i++) asm volatile("" : "+f"(a[i]) :: "memory");
}
template <int N> __device__ __forceinline__ void undef_regs(float (&a)[N]) {
  #pragma unroll
  for (int i = 0; i < N; i++) asm volatile("" : "=f"(a[i]));
}

__device__ __forceinline__ uint64_t desc_from_lo(uint32_t lo) { return (uint64_t)lo | ((uint64_t)0x40000040u << 32); }
__device__ __forceinline__ uint32_t pack_bf16(float lo, float hi) {
  uint32_t r; asm("cvt.rn.bf16x2.f32 %0, %1, %2;" : "=r"(r) : "f"(hi), "f"(lo)); return r;
}
__device__ __forceinline__ uint32_t fma_bf2(uint32_t a, uint32_t b, uint32_t c) {
  uint32_t d; asm("fma.rn.bf16x2 %0, %1, %2, %3;" : "=r"(d) : "r"(a), "r"(b), "r"(c)); return d;
}
__device__ __forceinline__ float bf_lo(uint32_t v) { return __uint_as_float(v << 16); }
__device__ __forceinline__ float bf_hi(uint32_t v) { return __uint_as_float(v & 0xFFFF0000u); }
__device__ __forceinline__ float bf16_round(float x) { return bf_lo(pack_bf16(x, 0.f)); }
__device__ __forceinline__ void stmatrix_x4(uint32_t addr, uint32_t r0, uint32_t r1, uint32_t r2, uint32_t r3) {
  asm volatile("stmatrix.sync.aligned.m8n8.x4.shared.b16 [%0], {%1, %2, %3, %4};" :: "r"(addr), "r"(r0), "r"(r1), "r"(r2), "r"(r3) : "memory");
}
__device__ __forceinline__ void stmatrix_x4_t(uint32_t addr, uint32_t r0, uint32_t r1, uint32_t r2, uint32_t r3) {
  asm volatile("stmatrix.sync.aligned.m8n8.x4.trans.shared.b16 [%0], {%1, %2, %3, %4};" :: "r"(addr), "r"(r0), "r"(r1), "r"(r2), "r"(r3) : "memory");
}
__device__ __forceinline__ void stmatrix_x4_if(uint32_t addr, uint32_t r0, uint32_t r1, uint32_t r2, uint32_t r3, bool on) {
  asm volatile("{\n.reg .pred p;\nsetp.ne.b32 p, %5, 0;\n@p stmatrix.sync.aligned.m8n8.x4.shared.b16 [%0], {%1, %2, %3, %4};\n}"
               :: "r"(addr), "r"(r0), "r"(r1), "r"(r2), "r"(r3), "r"((int)on) : "memory");
}
__device__ __forceinline__ void ldmatrix_x4(uint32_t addr, uint32_t& r0, uint32_t& r1, uint32_t& r2, uint32_t& r3) {
  asm volatile("ldmatrix.sync.aligned.m8n8.x4.shared.b16 {%0, %1, %2, %3}, [%4];" : "=r"(r0), "=r"(r1), "=r"(r2), "=r"(r3) : "r"(addr) : "memory");
}
__device__ __forceinline__ void ldmatrix_x4_t(uint32_t addr, uint32_t (&r)[4]) {
  asm volatile("ldmatrix.sync.aligned.m8n8.x4.trans.shared.b16 {%0, %1, %2, %3}, [%4];" : "=r"(r[0]), "=r"(r[1]), "=r"(r[2]), "=r"(r[3]) : "r"(addr) : "memory");
}
__device__ __forceinline__ void st_rlx(void* p, uint32_t a, bool on) {
  asm volatile("{\n.reg .pred p;\nsetp.ne.b32 p, %2, 0;\n@p st.relaxed.gpu.global.u32 [%0], %1;\n}" :: "l"(p), "r"(a), "r"((int)on) : "memory");
}
__device__ __forceinline__ void st_rlx_v2(void* p, uint32_t a, uint32_t b, bool on) {
  asm volatile("{\n.reg .pred p;\nsetp.ne.b32 p, %3, 0;\n@p st.relaxed.gpu.global.v2.u32 [%0], {%1, %2};\n}" :: "l"(p), "r"(a), "r"(b), "r"((int)on) : "memory");
}
__device__ __forceinline__ uint2 ld_rlx_v2(const void* p) {
  uint2 v; asm volatile("ld.relaxed.gpu.global.v2.u32 {%0,%1}, [%2];" : "=r"(v.x), "=r"(v.y) : "l"(p) : "memory"); return v;
}
__device__ __forceinline__ void st_rlx_v4(void* p, uint32_t a, uint32_t b, uint32_t c, uint32_t d, bool on) {
  asm volatile("{\n.reg .pred p;\nsetp.ne.b32 p, %5, 0;\n@p st.relaxed.gpu.global.v4.u32 [%0], {%1, %2, %3, %4};\n}"
               :: "l"(p), "r"(a), "r"(b), "r"(c), "r"(d), "r"((int)on) : "memory");
}
__device__ __forceinline__ void st_nonzero_v4(void* p, uint32_t a, uint32_t b, uint32_t c, uint32_t d, bool on) {
  st_rlx_v4(p, max(a, 1u), max(b, 1u), max(c, 1u), max(d, 1u), on);
}
__device__ __forceinline__ uint32_t min4(const uint4& v) { return min(min(v.x, v.y), min(v.z, v.w)); }
__device__ __forceinline__ uint4 ld_rlx_v4(const void* p) {
  uint4 v; asm volatile("ld.relaxed.gpu.global.v4.u32 {%0,%1,%2,%3}, [%4];" : "=r"(v.x), "=r"(v.y), "=r"(v.z), "=r"(v.w) : "l"(p) : "memory"); return v;
}
__device__ __forceinline__ uint32_t movmatrix_t(uint32_t a) {
  uint32_t d; asm volatile("movmatrix.sync.aligned.m8n8.trans.b16 %0, %1;" : "=r"(d) : "r"(a)); return d;
}
__device__ __forceinline__ void mma16(float (&c)[4], uint32_t a0, uint32_t a1, uint32_t a2, uint32_t a3, uint32_t b0, uint32_t b1) {
  asm volatile("mma.sync.aligned.m16n8k16.row.col.f32.bf16.bf16.f32 {%0,%1,%2,%3}, {%4,%5,%6,%7}, {%8,%9}, {%0,%1,%2,%3};"
               : "+f"(c[0]), "+f"(c[1]), "+f"(c[2]), "+f"(c[3]) : "r"(a0), "r"(a1), "r"(a2), "r"(a3), "r"(b0), "r"(b1));
}
__device__ __forceinline__ void sts128(uint32_t addr, uint32_t a, uint32_t b, uint32_t c, uint32_t d) {
  asm volatile("st.shared.v4.b32 [%0], {%1,%2,%3,%4};" :: "r"(addr), "r"(a), "r"(b), "r"(c), "r"(d) : "memory");
}
__device__ __forceinline__ uint4 lds128(uint32_t addr) {
  uint4 v; asm volatile("ld.shared.v4.b32 {%0,%1,%2,%3}, [%4];" : "=r"(v.x), "=r"(v.y), "=r"(v.z), "=r"(v.w) : "r"(addr) : "memory"); return v;
}
__device__ __forceinline__ uint32_t lds32(uint32_t addr) {
  uint32_t v; asm volatile("ld.shared.b32 %0, [%1];" : "=r"(v) : "r"(addr) : "memory"); return v;
}
__device__ __forceinline__ float2 lds64f(uint32_t addr) {
  float2 v; asm volatile("ld.shared.v2.f32 {%0,%1}, [%2];" : "=f"(v.x), "=f"(v.y) : "r"(addr) : "memory"); return v;
}
__device__ __forceinline__ void sts64(uint32_t addr, uint32_t a, uint32_t b) {
  asm volatile("st.shared.v2.b32 [%0], {%1, %2};" :: "r"(addr), "r"(a), "r"(b) : "memory");
}
__device__ __forceinline__ float fast_ex2(float x) { float y; asm("ex2.approx.ftz.f32 %0, %1;" : "=f"(y) : "f"(x)); return y; }
__device__ __forceinline__ float fast_rcp(float x) { float y; asm("rcp.approx.ftz.f32 %0, %1;" : "=f"(y) : "f"(x)); return y; }
__device__ __forceinline__ float fast_rsqrt(float x) { float y; asm("rsqrt.approx.ftz.f32 %0, %1;" : "=f"(y) : "f"(x)); return y; }
__device__ __forceinline__ float silu_f(float g) { return g * fast_rcp(1.f + fast_ex2(g * -1.4426950408889634f)); }
__device__ __forceinline__ float swiglu(float h, float v) {
  float t; asm("tanh.approx.f32 %0, %1;" : "=f"(t) : "f"(h));
  const float p = h * v;
  return fmaf(p, t, p);
}

__device__ __forceinline__ void wgmma_m64n128k16_ss(float (&d)[64], uint64_t descA, uint64_t descB, int scaleD) {
  asm volatile("{\n.reg .pred p;\nsetp.ne.b32 p, %66, 0;\n"
    "wgmma.mma_async.sync.aligned.m64n128k16.f32.bf16.bf16 "
    "{%0, %1, %2, %3, %4, %5, %6, %7, %8, %9, %10, %11, %12, %13, %14, %15, "
    "%16, %17, %18, %19, %20, %21, %22, %23, %24, %25, %26, %27, %28, %29, %30, %31, "
    "%32, %33, %34, %35, %36, %37, %38, %39, %40, %41, %42, %43, %44, %45, %46, %47, "
    "%48, %49, %50, %51, %52, %53, %54, %55, %56, %57, %58, %59, %60, %61, %62, %63}, "
    "%64, %65, p, 1, 1, 0, 1;\n}\n"
    : "+f"(d[0]), "+f"(d[1]), "+f"(d[2]), "+f"(d[3]), "+f"(d[4]), "+f"(d[5]), "+f"(d[6]), "+f"(d[7]),
      "+f"(d[8]), "+f"(d[9]), "+f"(d[10]), "+f"(d[11]), "+f"(d[12]), "+f"(d[13]), "+f"(d[14]), "+f"(d[15]),
      "+f"(d[16]), "+f"(d[17]), "+f"(d[18]), "+f"(d[19]), "+f"(d[20]), "+f"(d[21]), "+f"(d[22]), "+f"(d[23]),
      "+f"(d[24]), "+f"(d[25]), "+f"(d[26]), "+f"(d[27]), "+f"(d[28]), "+f"(d[29]), "+f"(d[30]), "+f"(d[31]),
      "+f"(d[32]), "+f"(d[33]), "+f"(d[34]), "+f"(d[35]), "+f"(d[36]), "+f"(d[37]), "+f"(d[38]), "+f"(d[39]),
      "+f"(d[40]), "+f"(d[41]), "+f"(d[42]), "+f"(d[43]), "+f"(d[44]), "+f"(d[45]), "+f"(d[46]), "+f"(d[47]),
      "+f"(d[48]), "+f"(d[49]), "+f"(d[50]), "+f"(d[51]), "+f"(d[52]), "+f"(d[53]), "+f"(d[54]), "+f"(d[55]),
      "+f"(d[56]), "+f"(d[57]), "+f"(d[58]), "+f"(d[59]), "+f"(d[60]), "+f"(d[61]), "+f"(d[62]), "+f"(d[63])
    : "l"(descA), "l"(descB), "r"(scaleD));
}
__device__ __forceinline__ void wgmma_m64n256k16_rs(float (&d)[128], uint32_t a0, uint32_t a1, uint32_t a2, uint32_t a3, uint64_t descB, int scaleD) {
  asm volatile("{\n.reg .pred p;\nsetp.ne.b32 p, %133, 0;\n"
    "wgmma.mma_async.sync.aligned.m64n256k16.f32.bf16.bf16 "
    "{%0, %1, %2, %3, %4, %5, %6, %7, %8, %9, %10, %11, %12, %13, %14, %15, "
    "%16, %17, %18, %19, %20, %21, %22, %23, %24, %25, %26, %27, %28, %29, %30, %31, "
    "%32, %33, %34, %35, %36, %37, %38, %39, %40, %41, %42, %43, %44, %45, %46, %47, "
    "%48, %49, %50, %51, %52, %53, %54, %55, %56, %57, %58, %59, %60, %61, %62, %63, "
    "%64, %65, %66, %67, %68, %69, %70, %71, %72, %73, %74, %75, %76, %77, %78, %79, "
    "%80, %81, %82, %83, %84, %85, %86, %87, %88, %89, %90, %91, %92, %93, %94, %95, "
    "%96, %97, %98, %99, %100, %101, %102, %103, %104, %105, %106, %107, %108, %109, %110, %111, "
    "%112, %113, %114, %115, %116, %117, %118, %119, %120, %121, %122, %123, %124, %125, %126, %127}, "
    "{%128, %129, %130, %131}, %132, p, 1, 1, 1;\n}\n"
    : "+f"(d[0]), "+f"(d[1]), "+f"(d[2]), "+f"(d[3]), "+f"(d[4]), "+f"(d[5]), "+f"(d[6]), "+f"(d[7]),
      "+f"(d[8]), "+f"(d[9]), "+f"(d[10]), "+f"(d[11]), "+f"(d[12]), "+f"(d[13]), "+f"(d[14]), "+f"(d[15]),
      "+f"(d[16]), "+f"(d[17]), "+f"(d[18]), "+f"(d[19]), "+f"(d[20]), "+f"(d[21]), "+f"(d[22]), "+f"(d[23]),
      "+f"(d[24]), "+f"(d[25]), "+f"(d[26]), "+f"(d[27]), "+f"(d[28]), "+f"(d[29]), "+f"(d[30]), "+f"(d[31]),
      "+f"(d[32]), "+f"(d[33]), "+f"(d[34]), "+f"(d[35]), "+f"(d[36]), "+f"(d[37]), "+f"(d[38]), "+f"(d[39]),
      "+f"(d[40]), "+f"(d[41]), "+f"(d[42]), "+f"(d[43]), "+f"(d[44]), "+f"(d[45]), "+f"(d[46]), "+f"(d[47]),
      "+f"(d[48]), "+f"(d[49]), "+f"(d[50]), "+f"(d[51]), "+f"(d[52]), "+f"(d[53]), "+f"(d[54]), "+f"(d[55]),
      "+f"(d[56]), "+f"(d[57]), "+f"(d[58]), "+f"(d[59]), "+f"(d[60]), "+f"(d[61]), "+f"(d[62]), "+f"(d[63]),
      "+f"(d[64]), "+f"(d[65]), "+f"(d[66]), "+f"(d[67]), "+f"(d[68]), "+f"(d[69]), "+f"(d[70]), "+f"(d[71]),
      "+f"(d[72]), "+f"(d[73]), "+f"(d[74]), "+f"(d[75]), "+f"(d[76]), "+f"(d[77]), "+f"(d[78]), "+f"(d[79]),
      "+f"(d[80]), "+f"(d[81]), "+f"(d[82]), "+f"(d[83]), "+f"(d[84]), "+f"(d[85]), "+f"(d[86]), "+f"(d[87]),
      "+f"(d[88]), "+f"(d[89]), "+f"(d[90]), "+f"(d[91]), "+f"(d[92]), "+f"(d[93]), "+f"(d[94]), "+f"(d[95]),
      "+f"(d[96]), "+f"(d[97]), "+f"(d[98]), "+f"(d[99]), "+f"(d[100]), "+f"(d[101]), "+f"(d[102]), "+f"(d[103]),
      "+f"(d[104]), "+f"(d[105]), "+f"(d[106]), "+f"(d[107]), "+f"(d[108]), "+f"(d[109]), "+f"(d[110]), "+f"(d[111]),
      "+f"(d[112]), "+f"(d[113]), "+f"(d[114]), "+f"(d[115]), "+f"(d[116]), "+f"(d[117]), "+f"(d[118]), "+f"(d[119]),
      "+f"(d[120]), "+f"(d[121]), "+f"(d[122]), "+f"(d[123]), "+f"(d[124]), "+f"(d[125]), "+f"(d[126]), "+f"(d[127])
    : "r"(a0), "r"(a1), "r"(a2), "r"(a3), "l"(descB), "r"(scaleD));
}

constexpr uint32_t MSLOT = 32768, QSLOT = 49152;
constexpr int NM = 6;
constexpr uint32_t SM_X0 = 3 * QSLOT;
constexpr uint32_t SM_XR = SM_X0 + 16384;
constexpr uint32_t SM_STG = 196608;
constexpr uint32_t SM_XCH = SM_STG + 16384;
constexpr uint32_t SM_BAR = SM_STG + 32768;
constexpr uint32_t SM_VEC = SM_BAR + 512;
constexpr uint32_t SM_MODT = SM_VEC;
constexpr uint32_t SM_TOTAL = SM_VEC + 2048;
constexpr uint32_t B_X = SM_BAR  , B_EQ = B_X + 64, B_EM = B_EQ + 32, B_STREQ = B_EM + 48, B_STH = B_STREQ + 8, B_HREQ = B_STH + 8  , B_LN = B_HREQ + 16,
                   B_FQ = B_LN + 8, B_FM = B_FQ + 32, B_MOD = B_FM + 48  , B_GATE = B_MOD + 64, B_STFREE = B_GATE + 8, B_VEC = B_STFREE + 8  ,
                   B_FLG = B_VEC + 16  , B_H2A = B_FLG + 24, B_HFREE = B_FLG + 96  ,
                   B_RST = B_HFREE + 16, B_END = B_RST + 8;
constexpr int NB_WG = 1  , NB_CONS = 3, NB_ORD = 4  ;
#define TUNE(name, value) constexpr int name = value
TUNE(PF_BYTES, 256);
TUNE(X_GAP, 250);
TUNE(AUX_HOLD, 3200);
TUNE(AUX_URG, 4);
TUNE(AUX_SLOW, 84);
TUNE(AUX_GAP, 500);
TUNE(MSEP, 6);
TUNE(ASPLIT, 2);
TUNE(WPRE, 2);
TUNE(DTAIL, 4);

struct Maps {
  CUtensorMap x, out;
  CUtensorMap o, hh;
  CUtensorMap wqk, wvv, wq1, wo, w1, w3, w2;
  CUtensorMap wmod;
#define MAP_H2 o
};

struct Ring { int st; uint32_t ph; int prev; uint32_t dl;
};
__device__ __forceinline__ void ring_next(Ring& r) { if (++r.st == NM) { r.st = 0; r.ph ^= 1; } }

__device__ __forceinline__ void retire_prev(uint32_t rel, bool on) {
  wgmma_commit();
  wgmma_wait<1>();
  if (on) mbar_arrive_e(rel);
}
struct Nop { __device__ __forceinline__ void operator()() const {} };
template <bool REL = true, class F = Nop>
__device__ __forceinline__ void mma_step(float (&acc)[64], uint32_t a, uint32_t b, bool first, uint32_t rel, F urgent = F()) {
  const uint32_t alo = (a >> 4) + (1u << 16), blo = (b >> 4) + (512u << 16);
  wgmma_fence();
  #pragma unroll
  for (int k = 0; k < 4; k++) {
    wgmma_m64n128k16_ss(acc, desc_from_lo(alo + k * 2), desc_from_lo(blo + k * 128), k > 0 || !first);
    if (k == 0) { retire_prev(rel, REL); urgent(); }
  }
  wgmma_commit();
}
__device__ __forceinline__ uint32_t m_wait(uint32_t sbase, const Ring& r) {
  mbar_wait(sbase + B_FM + 8 * r.st, r.ph, r.dl);
  return sbase + r.st * MSLOT;
}
__device__ __forceinline__ uint32_t m_prev(uint32_t sbase, const Ring& r) { return sbase + B_EM + 8 * r.prev; }
__device__ __forceinline__ void m_next(Ring& r) {
  r.prev = r.st; ring_next(r);
}
__device__ __forceinline__ void m_step(float (&acc)[64], uint32_t sbase, uint32_t wgoff, Ring& r, bool first = false) {
  const uint32_t slot = m_wait(sbase, r);
  mma_step(acc, slot + wgoff, slot + 16384, first, m_prev(sbase, r));
  m_next(r);
}

struct LnRow { uint32_t rs[2], nb[2]; };
__device__ __forceinline__ void ln_row(LnRow& l, int h, float mean, float rstd) {
  l.rs[h] = pack_bf16(rstd, rstd);
  const float nb = -mean * bf_lo(l.rs[h]);
  l.nb[h] = pack_bf16(nb, nb);
}
__device__ __forceinline__ uint32_t ln_mod(uint32_t x, const LnRow& l, int h, uint32_t c1, uint32_t s) {
  return fma_bf2(fma_bf2(x, l.rs[h], l.nb[h]), c1, s);
}

__device__ __forceinline__ uint32_t q_wait(int u, uint32_t sbase, uint32_t dl) {
  mbar_wait(sbase + B_FQ + 8 * (u & 3), (u >> 2) & 1, dl);
  return sbase + (u & 3) * QSLOT;
}
__device__ __forceinline__ uint32_t q_empty(int u, uint32_t sbase) { return sbase + B_EQ + 8 * (u & 3); }
struct Frag4 { uint32_t o[4]; };
__device__ __forceinline__ void q_load(uint32_t (&A)[16], uint4 (&p)[4], int kk, uint32_t tile, const Frag4& f, uint32_t t) {
  ldmatrix_x4(tile + f.o[kk], A[4 * kk], A[4 * kk + 1], A[4 * kk + 2], A[4 * kk + 3]);
  p[kk] = lds128(t + kk * 64);
}
__device__ __forceinline__ void q_norm(uint32_t (&A)[16], const uint4 (&p)[4], int kk, const LnRow& l) {
  A[4 * kk + 0] = ln_mod(A[4 * kk + 0], l, 0, p[kk].x, p[kk].z); A[4 * kk + 1] = ln_mod(A[4 * kk + 1], l, 1, p[kk].x, p[kk].z);
  A[4 * kk + 2] = ln_mod(A[4 * kk + 2], l, 0, p[kk].y, p[kk].w); A[4 * kk + 3] = ln_mod(A[4 * kk + 3], l, 1, p[kk].y, p[kk].w);
}
template <bool NEXT>
__device__ __forceinline__ void q_step_rs(float (&acc)[128], uint32_t (&A)[16], uint32_t (&N)[16], uint4 (&p)[4], int u, uint32_t sbase,
                                          const Frag4& f, uint32_t tab, const LnRow& l, uint32_t rot, bool keep, bool first, uint32_t dl, int wg, int zero) {
  const uint32_t slot = first ? sbase : q_wait(u, sbase, dl);
  const uint32_t blo = ((slot + 16384) >> 4) + (512u << 16) + rot * 128 + (zero << (u >> 2)), t = tab + ((u + 1) & 7) * 256;
  #pragma unroll
  for (int kk = 0; kk < 4; kk++) q_norm(A, p, kk, l);
  #pragma unroll
  for (int i = 0; i < 16; i++) asm volatile("" : "+r"(A[i]));
  if (!first) sched_fence(zero);
  if (first) {
    mbar_wait(sbase + B_GATE, 0, dl);
    PROF(6, threadIdx.x == 0);
  }
  if (!(first && wg == 0)) bar_sync(NB_ORD + wg, 256);
  wgmma_fence();
  #pragma unroll
  for (int kk = 0; kk < 4; kk++) {
    wgmma_m64n256k16_rs(acc, A[4 * kk], A[4 * kk + 1], A[4 * kk + 2], A[4 * kk + 3], desc_from_lo(blo ^ (kk * 128)), kk > 0 || !first);
    if (kk == 0) retire_prev(q_empty(u - 1, sbase), !first);
    if (NEXT && kk == 1) {
      if ((u & 1) && u < MSEP) mbar_wait(sbase + B_MOD + 4 * (u + 1), 0, dl);
      #pragma unroll
      for (int q = 0; q < 4; q++) q_load(N, p, q, slot, f, t);
    }
    if (kk == 3 && (NEXT || wg == 0)) bar_arrive(NB_ORD + (wg ^ 1), 256);
    if (kk == 1) stmatrix_x4_if(sbase + SM_STG + (u >> 3) * 16384 + (f.o[0] ^ (((u >> 1 & 3) ^ rot) << 5)), A[0], A[1], A[2], A[3], keep);
  }
  wgmma_commit();
}

typedef uint32_t Frag8[8];
template <int N> __device__ __forceinline__ void pack_half(Frag8& f, const float (&acc)[N], int off, int half) {
  #pragma unroll
  for (int e = 0; e < 8; e++) { f[e] = pack_bf16(acc[off + 4 * e + 2 * half], acc[off + 4 * e + 2 * half + 1]); asm volatile("" : "+r"(f[e])); }
}
__device__ __forceinline__ void transpose8(Frag8& f) {
  #pragma unroll
  for (int e = 0; e < 8; e++) f[e] = movmatrix_t(f[e]);
}
__device__ __forceinline__ void attn_send(const Frag8& f, int kv, uint32_t xch, int warp, uint4* halo_out, bool has_next) {
  if (warp == 3) {
    st_nonzero_v4(halo_out + kv * 64, f[0], f[1], f[2], f[3], has_next); st_nonzero_v4(halo_out + kv * 64 + 32, f[4], f[5], f[6], f[7], has_next);
  } else {
    sts128(xch + 2048 + kv * 1024, f[0], f[1], f[2], f[3]); sts128(xch + 2048 + kv * 1024 + 512, f[4], f[5], f[6], f[7]);
  }
}
template <int N>
__device__ __forceinline__ void attn_recv(uint4* p, int first, uint32_t xch, int wg, int warp, const uint4* halo_in, bool has_prev) {
  bar_sync(NB_WG + wg, 128);
  #pragma unroll
  for (int e = 0; e < N; e++)
    asm volatile("{\n.reg .pred p, q;\nsetp.ne.b32 p, %6, 0;\nsetp.ne.b32 q, %7, 0;\n"
                 "mov.b32 %0, 0;\nmov.b32 %1, 0;\nmov.b32 %2, 0;\nmov.b32 %3, 0;\n"
                 "@p ld.shared.v4.b32 {%0,%1,%2,%3}, [%4];\n@q ld.relaxed.gpu.global.v4.u32 {%0,%1,%2,%3}, [%5];\n}"
                 : "=&r"(p[e].x), "=&r"(p[e].y), "=&r"(p[e].z), "=&r"(p[e].w)
                 : "r"(xch + (first + e) * 512), "l"(halo_in + (first + e) * 32), "r"((int)(warp > 0)), "r"((int)(warp == 0 && has_prev)) : "memory");
}
template <int N>
__device__ __forceinline__ void attn_check(uint4* p, int first, bool remote, const uint4* halo_in, uint32_t dl) {
  if (remote) {
    while (true) {
      uint32_t m = ~0u;
      #pragma unroll
      for (int e = 0; e < N; e++) m = min(m, min4(p[e]));
      if (poll_done(m != 0, dl)) break;
      #pragma unroll
      for (int e = 0; e < N; e++) p[e] = ld_rlx_v4(halo_in + (first + e) * 32);
    }
  }
}
template <int SPLIT, class F>
__device__ __forceinline__ void attn_core(const Frag8& qA, const Frag8& qB, const Frag8& kA, const Frag8& kB, const Frag8& vA, const Frag8& vB,
                                          const uint4* kP, const uint4* vP, bool noprev, int lane, float (&o)[2][5][4], F late) {
  const int g = lane >> 2, qd = lane & 3;
  const bool s0 = 2 * qd > g, s1 = 2 * qd + 1 > g;
  const uint32_t msk = (s0 ? 0xFFFFu : 0u) | (s1 ? 0xFFFF0000u : 0u);
  float s[2][3][4];
  uint32_t pr[2][2];
  auto scores = [&](int h, int nb) {
    s[h][nb][0] = s[h][nb][1] = s[h][nb][2] = s[h][nb][3] = 0.f;
    #pragma unroll
    for (int kk = 0; kk < 2; kk++) {
      const int e = 4 * h + 2 * kk;
      mma16(s[h][nb], qA[e], qB[e], qA[e + 1], qB[e + 1], nb == 1 ? kA[e] : nb == 2 ? kB[e] : kk ? kP[h].z : kP[h].x,
            nb == 1 ? kA[e + 1] : nb == 2 ? kB[e + 1] : kk ? kP[h].w : kP[h].y);
    }
  };
  auto rows = [&](int h, int y) {
    constexpr float SC = 0.17677669529663687f * 1.4426950408889634f;
    const float l0 = s0 ? (y == 0 && noprev ? -INFINITY : s[h][y][2 * y]) : s[h][y + 1][2 * y];
    const float l1 = s1 ? (y == 0 && noprev ? -INFINITY : s[h][y][2 * y + 1]) : s[h][y + 1][2 * y + 1];
    float m = fmaxf(l0, l1);
    m = fmaxf(m, __shfl_xor_sync(0xffffffffu, m, 1));
    m = fmaxf(m, __shfl_xor_sync(0xffffffffu, m, 2));
    const uint32_t p = pr[h][y] = pack_bf16(fast_ex2((l0 - m) * SC), fast_ex2((l1 - m) * SC));
    #pragma unroll
    for (int m2 = 0; m2 < 2; m2++) {
      const int e = 4 * h + 2 * m2;
      float (&d)[4] = o[h][2 * m2 + y];
      d[0] = d[1] = d[2] = d[3] = 0.f;
      if (y == 0) mma16(d, m2 ? vP[h].z : vP[h].x, m2 ? vP[h].w : vP[h].y, vA[e], vA[e + 1], p & msk, p & ~msk);
      else mma16(d, vA[e], vA[e + 1], vB[e], vB[e + 1], p & msk, p & ~msk);
    }
  };
  #pragma unroll
  for (int h = 0; h < 2; h++) { scores(h, 1); scores(h, 2); if (SPLIT == 0) scores(h, 0); }
  if (SPLIT == 2) { rows(0, 1); rows(1, 1); }
  if (SPLIT) { late(); scores(0, 0); scores(1, 0); }
  #pragma unroll
  for (int h = 0; h < 2; h++) {
    if (SPLIT < 2) rows(h, 1);
    rows(h, 0);
    o[h][4][0] = o[h][4][1] = o[h][4][2] = o[h][4][3] = 0.f;
    mma16(o[h][4], 0x3F803F80u, 0u, 0u, 0x3F803F80u, pr[h][0], pr[h][1]);
  }
}
__device__ __forceinline__ void attn_store(const float (&o)[2][5][4], int h, uint32_t sbase, const Frag4& f) {
  float r[4];
  #pragma unroll
  for (int e = 0; e < 4; e++) r[e] = fast_rcp(o[h][4][e]);
  #pragma unroll
  for (int m = 0; m < 2; m++) {
    const float (&lo)[4] = o[h][2 * m], (&hi)[4] = o[h][2 * m + 1];
    stmatrix_x4_t(sbase + SM_STG + f.o[2 * h + m], pack_bf16(lo[0] * r[0], lo[1] * r[1]), pack_bf16(hi[0] * r[2], hi[1] * r[3]),
                  pack_bf16(lo[2] * r[0], lo[3] * r[1]), pack_bf16(hi[2] * r[2], hi[3] * r[3]));
  }
}

__device__ __forceinline__ void request_store(uint32_t bar) {
  fence_proxy_async_smem();
  mbar_arrive_e(bar);
}

__device__ __forceinline__ void g_quad(float (&a0)[64], float (&a1)[64], uint32_t rel2, uint32_t sbase, uint32_t wgoff, Ring& r) {
  const uint32_t x = m_wait(sbase, r);
  mma_step(a0, x + wgoff, x + 16384, false, m_prev(sbase, r), [&] { if (rel2) mbar_arrive_e(rel2); });
  m_next(r);
  const uint32_t xe = m_prev(sbase, r), y = m_wait(sbase, r);
  mma_step<false>(a1, x + wgoff, y, false, 0);
  m_next(r);
  const uint32_t z = m_wait(sbase, r);
  mma_step(a1, z + wgoff, y + 16384, false, xe);
  mma_step(a0, z + wgoff, z + 16384, false, m_prev(sbase, r));
  m_next(r);
}
template <int T>
__device__ __forceinline__ void g_piece(float (&prv)[64], int jj, int use, uint32_t sbase, const Frag4& f, uint32_t dl) {
  if (jj == 0) { mbar_wait(sbase + B_HFREE + 8 * T, use & 1, dl); fence_regs(prv); PROF(33 + 2 * use + T, threadIdx.x == 0); }
  uint32_t p[4];
  #pragma unroll
  for (int e = 0; e < 4; e++) {
    const int i = jj * 8 + e * 2;
    p[e] = pack_bf16(swiglu(prv[i], prv[i + 32]), swiglu(prv[i + 1], prv[i + 33]));
  }
  stmatrix_x4(sbase + SM_STG + T * 16384 + f.o[jj], p[0], p[1], p[2], p[3]);
  if (jj == 3) request_store(sbase + B_HREQ + 8 * T);
}
template <bool REL2, bool Q, class F>
__device__ __forceinline__ uint32_t g_ppqq(float (&p)[64], float (&q)[64], bool firstq, uint32_t rel2, uint32_t sbase, uint32_t wgoff, Ring& r, F after) {
  const uint32_t x = m_wait(sbase, r);
  mma_step(p, x + wgoff, x + 16384, false, m_prev(sbase, r), [&] { if (REL2) mbar_arrive_e(rel2); });
  m_next(r);
  after(0);
  const uint32_t xe = m_prev(sbase, r), z = m_wait(sbase, r);
  mma_step<!Q>(p, z + wgoff, z + 16384, false, xe);
  m_next(r);
  after(1);
  if (!Q) return 0;
  const uint32_t ze = m_prev(sbase, r), y = m_wait(sbase, r);
  mma_step<false>(q, x + wgoff, y, firstq, 0);
  after(2);
  mma_step(q, z + wgoff, y + 16384, false, xe);
  m_next(r);
  after(3);
  return ze;
}

__device__ __forceinline__ uint32_t bad2(uint32_t a, uint32_t b, unsigned par) {
  uint32_t d; asm("lop3.b32 %0, %1, %2, %3, 0x7E;" : "=r"(d) : "r"(a), "r"(b), "r"(par)); return d;
}
__device__ __forceinline__ uint32_t bad4(const uint4& v, unsigned par) { return bad2(v.x, v.y, par) | bad2(v.z, v.w, par); }
__device__ __forceinline__ uint32_t hi_halves(uint32_t lo, uint32_t hi) { return __byte_perm(lo, hi, 0x7632); }

__device__ __forceinline__ void gather_table(const float* src, uint32_t dst, uint32_t bar, unsigned par, uint32_t dl) {
  asm volatile("{\n.reg .pred p, e;\n.reg .b32 s<4>, c<4>, t<4>, w<4>;\n"
               "elect.sync _|e, 0xffffffff;\n"
               "LAB_POLL:\n"
               "ld.relaxed.gpu.global.v4.u32 {s0, s1, s2, s3}, [%0];\n"
               "ld.relaxed.gpu.global.v4.u32 {c0, c1, c2, c3}, [%0 + 4096];\n"
               "prmt.b32 w0, c0, c1, 0x7632;\nprmt.b32 w1, c2, c3, 0x7632;\nprmt.b32 w2, s0, s1, 0x7632;\nprmt.b32 w3, s2, s3, 0x7632;\n"
               "st.shared.v4.b32 [%1], {w0, w1, w2, w3};\n"
               "lop3.b32 t0, s0, s1, %3, 0x7E;\nlop3.b32 t1, s2, s3, %3, 0x7E;\nlop3.b32 t2, c0, c1, %3, 0x7E;\nlop3.b32 t3, c2, c3, %3, 0x7E;\n"
               "lop3.b32 t0, t0, t1, 1, 0xA8;\nlop3.b32 t2, t2, t3, 1, 0xA8;\n"
               "or.b32 t0, t0, t2;\n"
               "setp.eq.u32 p, t0, 0;\n"
               "vote.sync.all.pred p, p, 0xffffffff;\n"
               "@p bra.uni LAB_OK;\n"
               "mov.u32 t0, %%clock;\nsub.s32 t0, t0, %4;\nsetp.lt.s32 p, t0, 0;\n"
               "vote.sync.all.pred p, p, 0xffffffff;\n"
               "@p bra.uni LAB_POLL;\n"
               "LAB_OK:\n"
               "@e mbarrier.arrive.shared::cta.b64 _, [%2];\n}"
               :: "l"(src), "r"(dst), "r"(bar), "r"(par), "r"(dl) : "memory");
}

__device__ __forceinline__ int aux_col(int a, int u) { return u < 8 ? (a & 1) * 1024 + (2 * u + (a >> 1)) * 64 : 2048 + ((u - 8) * 4 + a) * 64; }
constexpr int NA = 7;
constexpr uint32_t A_FULL = SM_BAR, A_EMPTY = SM_BAR + 64, A_SUM = SM_BAR + 128, A_FREE = SM_BAR + 136, SM_RED = SM_VEC;
__device__ __forceinline__ void aux_role(const Maps& maps, const bf16* __restrict__ cvec, Mail* mail0, int zero, int a, uint32_t sbase, int wid) {
  const int tid = threadIdx.x, lane = tid & 31;
  const uint32_t dl = (clock32() + 800000000u) | 1;
  int st = 0; uint32_t ph = 0;
  if (wid == 8) {
    prefetch_tmap(&maps.wmod);
    #pragma unroll
    for (int i = 0; i < 18; i++) mbar_init_e(sbase + A_FULL + 8 * i, i < 8 ? 1 : i < 17 ? 8 : 2);
    fence_proxy_async_smem();
    bar_arrive(0, 352);
    PROF(39, lane == 0);
    #pragma unroll
    for (int i = 0; i < NA; i++) {
      mbar_expect_tx_e(sbase + A_FULL + 8 * i, 32768);
      tma_load_2d(sbase + i * MSLOT, &maps.wmod, sbase + A_FULL + 8 * i, aux_col(a, i >> 2), (i & 3) * 256);
    }
    PROF(40, lane == 0);
    #pragma unroll 1
    for (int i = NA; i < 96; i++) {
      if (i >= AUX_SLOW) wait_until(clock32() + AUX_GAP);
      if (i == 8) wait_until(dl - 800000000u + AUX_HOLD);
      mbar_wait(sbase + A_EMPTY + 8 * st, ph, dl);
      mbar_expect_tx_e(sbase + A_FULL + 8 * st, 32768);
      tma_load_2d<true>(sbase + st * MSLOT, &maps.wmod, sbase + A_FULL + 8 * st, aux_col(a, i >> 2), (i & 3) * 256);
      if (++st == NA) { st = 0; ph ^= 1; }
    }
  } else if (wid < 8) {
    const int g = lane >> 2, qd = lane & 3;
    uint32_t sc[16];
    const uint2 c = *reinterpret_cast<const uint2*>(cvec + tid * 4);
    sts64(sbase + SM_RED + tid * 8, pack_bf16(silu_f(bf_lo(c.x)), silu_f(bf_hi(c.x))), pack_bf16(silu_f(bf_lo(c.y)), silu_f(bf_hi(c.y))));
    bar_sync(0, 352);
    #pragma unroll
    for (int i = 0; i < 16; i++) sc[i] = lds32(sbase + SM_RED + ((i >> 2) * 256 + wid * 32 + (i & 3) * 8 + qd * 2) * 2);
    bar_sync(NB_CONS, 256);
    PROF(38, tid == 0);
    const uint32_t aoff = (wid * 32 + (lane & 7) + (lane >> 4) * 8) * 128 + ((((lane >> 3) & 1) ^ (lane & 7)) << 4);
    uint32_t w[2][8][4];
    auto fetch = [&](uint32_t (&f)[8][4]) {
      mbar_wait(sbase + A_FULL + 8 * st, ph, dl);
      #pragma unroll
      for (int e = 0; e < 8; e++) ldmatrix_x4_t((sbase + st * MSLOT + aoff + (e >> 2) * 2048) ^ ((e & 3) << 5), f[e]);
      if (++st == NA) { st = 0; ph ^= 1; }
    };
    #pragma unroll 1
    for (int u = 0; u < 24; u++) {
      float acc[4][4];
      #pragma unroll
      for (int m = 0; m < 4; m++) acc[m][0] = acc[m][1] = acc[m][2] = acc[m][3] = 0.f;
      fetch(w[0]);
      #pragma unroll
      for (int q = 0; q < 4; q++) {
        PROF(30 + (u & 1) * 4 + q, u < 2 && tid == 0);
        const uint32_t rel = sbase + A_EMPTY + 8 * (st == 0 ? NA - 1 : st - 1);
        if (q < 3) fetch(w[(q + 1) & 1]);
        uint32_t dep = 0;
        #pragma unroll
        for (int e = 0; e < 8; e++) dep |= w[q & 1][e][0];
        mbar_arrive_e(rel + (dep & zero));
        if (q == 1) mbar_wait(sbase + A_FREE, (u & 1) ^ 1, dl);
        #pragma unroll
        for (int e = 0; e < 8; e++) {
          const uint32_t (&f)[4] = w[q & 1][e];
          mma16(acc[e & 3], f[0], f[1], f[2], f[3], sc[4 * q + 2 * (e >> 2)], sc[4 * q + 2 * (e >> 2) + 1]);
        }
      }
      const float v0 = qd & 2 ? (qd & 1 ? acc[3][0] : acc[2][0]) : (qd & 1 ? acc[1][0] : acc[0][0]);
      const float v1 = qd & 2 ? (qd & 1 ? acc[3][2] : acc[2][2]) : (qd & 1 ? acc[1][2] : acc[0][2]);
      sts64(sbase + SM_RED + wid * 256 + (qd * 8 + g) * 8, __float_as_uint(v0), __float_as_uint(v1));
      mbar_arrive_e(sbase + A_SUM);
      if (u < AUX_URG) mbar_wait(sbase + A_FREE, u & 1, dl);
    }
  } else if (wid < 11) {
    float* const mail = &mail0->mod[(wid - 9) * 4 * 6 * D_ + 2 * lane];
    unsigned par = ld_relaxed(&mail0->flags[FL_EPOCH + (lane >> 5)]);
    bar_sync(0, 352);
    par = (par + 1) & 1;
    #pragma unroll 1
    for (int u = 0; u < 24; u++) {
      const int col = aux_col(a, u);
      const float add = (col >> 10) == 1 || (col >> 10) == 4 ? 1.f : 0.f;
      const float mul = col < 3 * D_ ? 1.f : col < 5 * D_ ? 0.5f : 2.f;
      mbar_wait(sbase + A_SUM, u & 1, dl);
      float2 v[8];
      #pragma unroll
      for (int w = 0; w < 8; w++) v[w] = lds64f(sbase + SM_RED + w * 256 + lane * 8);
      const float t0 = ((v[0].x + v[1].x) + (v[2].x + v[3].x)) + ((v[4].x + v[5].x) + (v[6].x + v[7].x));
      const float t1 = ((v[0].y + v[1].y) + (v[2].y + v[3].y)) + ((v[4].y + v[5].y) + (v[6].y + v[7].y));
      mbar_arrive_e(sbase + A_FREE + (__float_as_uint(t0 + t1) & zero));
      const uint32_t w = pack_bf16((add + bf16_round(t0)) * mul, (add + bf16_round(t1)) * mul), o = __shfl_xor_sync(0xffffffffu, w, 1);
      const uint32_t m0 = (lane & 1) ? (o & 0xFFFF0000u) : (w << 16), m1 = (lane & 1) ? (w & 0xFFFF0000u) : (o << 16);
      #pragma unroll
      for (int c = 0; c < 4; c++) st_rlx_v2(mail + c * 6 * D_ + col, m0 | par, m1 | par, true);
      PROF(1 + u, tid == 288);
    }
    const int t = a * 64 + tid - 288;
    #pragma unroll 1
    for (int i = t; i < 16 * 16 * 256; i += 256) mail0->halo[par ^ 1][i] = make_uint4(0, 0, 0, 0);
  }
}

template <int MODE>
__global__ void __launch_bounds__(384, 1)
fused_block_kernel(const bf16* __restrict__ x, const bf16* __restrict__ cvec, const bf16* __restrict__ wmod, Mail* mail0, int zero,
                   const __grid_constant__ Maps maps) {
  extern __shared__ __align__(1024) uint8_t smem_raw[];
  const uint32_t sbase = smem_u32(smem_raw);
  const int tid = threadIdx.x, lane = tid & 31;
  PROFN(0, tid == 0);
  const int wid = __shfl_sync(0xffffffffu, tid >> 5, 0);
  const int b = cta_role<MODE>();
  if (b >= NCTA) { aux_role(maps, cvec, mail0, zero, b - NCTA, sbase, wid); return; }
  const int jg = b >> 6, mb = jg ? 31 - (b >> 2) : (b >> 2), j = 4 * jg + (b & 3);
  const uint32_t dl = (clock32() + 800000000u) | 1;
  unsigned* const flags = &mail0->flags[mb * 32];
  const int row0 = mb * 128;

  if (wid >= 8) {
    if (wid == 8) {
      #pragma unroll
      for (int i = 0; i < 8; i++) mbar_init_e(sbase + B_X + 8 * i, 1);
      fence_proxy_async_smem();
      mbar_expect_tx_e(sbase + B_X, 4096);
      bulk_load(sbase + SM_XR, x + (size_t)(row0 + j * 16) * D_, 4096, sbase + B_X);
    } else if (wid == 11) {
      #pragma unroll
      for (int i = 0; i < 11; i++) prefetch_tmap(&maps.x + i);
    } else if (wid == 9) {
      #pragma unroll
      for (uint32_t bar = B_EQ; bar < B_FM; bar += 8) mbar_init_e(sbase + bar, bar < B_FQ ? 8 : bar == B_FQ + 8 || bar == B_FQ + 24 ? 2 : 1);
      fence_proxy_async_smem();
    } else {
      #pragma unroll
      for (uint32_t bar = B_FM; bar < B_END; bar += 8) mbar_init_e(sbase + bar, 1);
      fence_proxy_async_smem();
    }
    bar_sync(0, 384);
    reg_dealloc<40>();
    PROF(92, tid == 256);
    if (wid == 8) {
      uint32_t tnext = clock32();
      #pragma unroll 1
      for (int q = 1; q < 8; q++) {
        wait_until(tnext);
        mbar_expect_tx_e(sbase + B_X + 8 * q, 4096);
        bulk_load(sbase + SM_XR + q * 4096, x + (size_t)(row0 + j * 16 + 2 * q) * D_, 4096, sbase + B_X + 8 * q);
        tnext += X_GAP;
      }
      #pragma unroll 1
      for (int u = 0; u < 16; u++) {
        const int st = u & 3;
        if (u == 1) mbar_wait(sbase + B_X + 56, 0, dl);
        if (u == 2) { mbar_wait(sbase + B_GATE, 0, dl); PROFN(60, lane == 0); }
        if (u == 3) mbar_wait(sbase + B_EQ, 0, dl);
        mbar_wait(sbase + B_EQ + 8 * st, ((u >> 2) & 1) ^ 1, dl);
        const uint32_t slot = sbase + st * QSLOT, fb = sbase + B_FQ + 8 * st;
        mbar_expect_tx_e(fb, u == 0 ? 65536 : u == 15 ? 32768 : 49152);
        if ((u & 1) && (u < MSEP || u == 15)) mbar_arrive_e(fb);
        if (u == 0) tma_load_3d(sbase + SM_X0, &maps.x, fb, 0, mb * 64, 0);
        tma_load_4d<true>(slot + 16384, &maps.wqk, fb, 0, u * 64, j, 0);
        tma_load_4d<true>(slot + 32768, &maps.wvv, fb, 0, u * 64, j, 0);
        if (u < 15) tma_load_3d(slot, &maps.x, fb, u * 64 + 64, mb * 64, 0);
      }
      const unsigned e1 = 1 + ld_relaxed(flags + FO_EPOCH);
      Ring r{0, 1, 0, dl};
      uint32_t slot, fb;
      auto acquire = [&](uint32_t bytes) {
        mbar_wait(sbase + B_EM + 8 * r.st, r.ph, dl);
        slot = sbase + r.st * MSLOT; fb = sbase + B_FM + 8 * r.st;
        mbar_expect_tx_e(fb, bytes);
        ring_next(r);
      };
      #pragma unroll 1
      for (int kt = 0; kt < 16; kt++) {
        if (kt < 5) mbar_wait(sbase + B_EQ + 8 * (kt - (kt >= 2)), 1, dl);
        if ((kt & 7) == 0) { PROF(46, lane == 0 && kt == 8); mbar_wait(sbase + B_FLG + kt, 0, dl); PROF(47, lane == 0 && kt == 8); }
        acquire(32768);
        tma_load_4d<true>(slot + 16384, &maps.wq1, fb, (j + 8) * 64, (kt & 1) * 64 + (kt & 6) * 8, (kt >> 3) * 4, 0);
        tma_load_3d(slot, &maps.hh, fb, (kt & 7) * 64, row0, kt >> 3);
      }
      PROF(82, lane == 0);
      mbar_wait(sbase + B_FLG + 16, 0, dl);
      PROF(83, lane == 0);
      #pragma unroll 1
      for (int kt = 0; kt < 8; kt++) {
        if (kt == 4) {
          acquire(32768);
          tma_load_3d(slot, &maps.x, fb, j * 128, mb * 64, 0);
          tma_load_3d(slot + 16384, &maps.x, fb, j * 128 + 64, mb * 64, 0);
        }
        acquire(32768);
        tma_load_3d<true>(slot + 16384, &maps.wo, fb, 0, kt * 64, 2 * j);
        tma_load_2d(slot, &maps.o, fb, kt * 64, row0);
      }
      acquire(16384);
      tma_load_3d<true>(slot + 16384, &maps.wo, fb, 0, (8 + j) * 64, 2 * j);
      const uint32_t oth = (0x2107654u + (0x1110000u << (4 * (j & 3)) & 0x1110000u)) ^ ((j & 4) ? 0x4444444u : 0u);
      auto deferred = [&](const CUtensorMap* map, const unsigned* flag, Ring ra, int n, int col0, int step) {
        uint32_t dst = sbase + ra.st * MSLOT, bar = sbase + B_FM + 8 * ra.st, col = col0 + (~j & 4) * step;
        asm volatile("" : "+r"(dst), "+r"(bar), "+r"(col));
        wait_flag(flag, e1 * NCTA, dl);
        tma_load_2d(dst, map, bar, col, row0);
        #pragma unroll 1
        for (int i = 1; i < n; i++) { ring_next(ra); tma_load_2d(sbase + ra.st * MSLOT, map, sbase + B_FM + 8 * ra.st, col + i * step, row0); }
      };
      {
        const Ring ra = r;
        #pragma unroll 1
        for (int i = 0; i < 7; i++) {
          const int kt = 8 + (oth >> (4 * i) & 7);
          acquire(32768);
          tma_load_3d<true>(slot + 16384, &maps.wo, fb, 0, kt * 64, 2 * j);
          if (i == WPRE - 1) { deferred(&maps.o, &mail0->flags[FL_O], ra, WPRE, 512, 64); PROFN(61, lane == 0); }
          if (i >= WPRE) tma_load_2d(slot, &maps.o, fb, kt * 64, row0);
        }
      }
      uint64_t ord = (uint64_t)(2 * oth) | (uint64_t)(2 * oth + 0x1111111u) << 28;
      auto load_b = [&](uint32_t dst, int col, int kt) {
        tma_load_2d<true>(dst, &maps.w1, fb, col, kt * 64);
        tma_load_2d<true>(dst + 8192, &maps.w3, fb, col, kt * 64);
      };
      Ring ra = r;
      #pragma unroll 1
      for (int i = -2; i < 5; i++) {
        const int kt = i < 0 ? 2 * j + i + 2 : 2 * ((~j & 4) + min(i, 3));
        if (i == 0) ra = r;
        acquire(32768);
        load_b(slot + 16384, i < 0 || i == 3 ? (8 + j) * 64 : j * 64, kt);
        if (i < 0 || i == 3) load_b(slot, i < 0 ? j * 64 : (8 + j) * 64, i < 0 ? kt : kt - 2);
      }
      deferred(&maps.MAP_H2, &mail0->flags[FL_H2], ra, 3, 0, 128);
      tma_load_2d(slot, &maps.MAP_H2, fb, ((~j & 4) + 3) * 128, row0);
      PROFN(62, lane == 0);
      mbar_arrive_e(sbase + B_H2A);
      #pragma unroll 1
      for (int q = 2; q < 31; q++) {
        const int pr = q >> 3, w = q & 7, col = (16 * pr + j) * 64 + (w == 7 ? 512 : 0), y = pr == 3 ? 0 : w == 0 || w >= 6 ? 2 : 1;
        if (q == 7) ord = (j & 4) ? 0xFEDCBA9875316420ull : 0x76543210FDB9ECA8ull;
        const uint32_t kk = (uint32_t)(ord >> (w == 7 ? 0 : 8 * w + (pr == 0 ? 0 : 8)));
        const int k0 = kk & 15, k1 = kk >> 4 & 15;
        #pragma unroll
        for (int t = 1; t <= 2; t++) {
          if (t == 2 && q == 3) mbar_wait(sbase + B_FLG + 32, 0, dl);
          acquire(32768);
          load_b(slot + 16384, col, t == 1 ? k0 : k1);
          tma_load_2d(slot, &maps.MAP_H2, fb, (t == 1 ? k0 : k1) * 64, row0);
          if (t == y) {
            acquire(32768);
            load_b(slot, col + 512, k0);
            load_b(slot + 16384, col + 512, k1);
          }
        }
      }
      #pragma unroll 1
      for (int kt = 0; kt < 56; kt++) {
        if ((kt & 7) == 0) mbar_wait(sbase + B_FLG + 40 + kt, 0, dl);
        acquire(32768);
        tma_load_3d(slot + 16384, &maps.w2, fb, 0, kt * 64, 2 * j);
        tma_load_3d(slot, &maps.hh, fb, (kt & 7) * 64, row0, kt >> 3);
      }
    } else {
      const unsigned e1 = 1 + ld_relaxed(wid == 9 ? flags + FO_EPOCH : &mail0->flags[FL_EPOCH]), par = e1 & 1;
      if (wid == 9) {
        #pragma unroll 1
        for (int n = 0; n < 12; n++) {
          if (n == 4) {
            mbar_wait(sbase + B_STH, 0, dl);
            tma_store_2d(&maps.MAP_H2, sbase + SM_STG, j * 128, row0);
            bulk_commit();
            bulk_wait0();
            red_add_e(&mail0->flags[FL_H2], 1);
            PROF(84, lane == 0);
            mbar_wait(sbase + B_H2A, 0, dl);
          }
          if (n == 3) mbar_wait(sbase + B_RST, 0, dl);
          const int ht = (n - 5) & 1;
          if (n >= 1 && n <= 4) mbar_wait(sbase + B_STREQ, n & 1, dl);
          else mbar_sleep(n == 0 ? sbase + B_STREQ : sbase + B_HREQ + 8 * ht, n == 0 ? 0 : ((n - 5) >> 1) & 1, dl);
          if (n == 0) fence_proxy_async_smem();
          if (n == 2 || n == 3) tma_store_2d(&maps.o, sbase + SM_STG, (j + 8 * (n - 2)) * 64, row0);
          else if (n == 4) tma_store_2d(&maps.MAP_H2, sbase + SM_STG + 16384, j * 128 + 64, row0);
          else tma_store_3d(&maps.hh, sbase + SM_STG + (n < 2 ? n : ht) * 16384, j * 64, row0, n < 2 ? n : n - 5);
          bulk_commit();
          bulk_wait0();
          red_add_e(n == 3 ? &mail0->flags[FL_O] : flags + FO_CNT + n, 1);
          mbar_arrive_e(n < 4 ? sbase + B_STFREE : sbase + B_HFREE + 8 * ht);
          if (n == 4) mbar_arrive_e(sbase + B_HFREE);
          PROFN(70 + n, lane == 0 && n > 0); PROF(85, lane == 0 && n == 0);
          if (n != 3) { wait_flag(flags + FO_CNT + n, e1 * 8, dl); mbar_arrive_e(sbase + B_FLG + 8 * n); }
        }
      } else {
        const float* const mail = &mail0->mod[(b & 7) * 6 * D_ + lane * 4];
        if (wid == 10) {
          #pragma unroll 1
          for (int p = 0; p < 8; p++) {
            if (p >= 2) mbar_wait(p == 2 ? q_empty(0, sbase) : q_empty(2 * p - 5, sbase), p == 2 ? 0 : ((2 * p - 5) >> 2) & 1, dl);
            gather_table(mail + p * 128, sbase + SM_MODT + (p & 3) * 512 + ((lane * 16) ^ ((j >> 1) << 6)), 2 * p - 1 < MSEP ? sbase + B_MOD + 8 * p : sbase + B_FQ + 8 * ((2 * p - 1) & 3), par, dl);
            PROF(63 + p, lane == 0 && p < 7);
          }
          const uint32_t vdst = sbase + SM_VEC + (lane >> 3) * 64 + (lane & 3) * 16 + ((lane >> 2) & 1) * 8;
          #pragma unroll 1
          for (int v = 0; v < 2; v++) {
            mbar_sleep(sbase + B_FLG + 16 + 24 * v, 0, dl);
            uint4 m[3];
            while (true) {
              #pragma unroll
              for (int e = 0; e < 3; e++) m[e] = ld_rlx_v4(mail + (2 + v + e) * 1024 + j * 128);
              if (poll_done(((bad4(m[0], par) | bad4(m[1], par) | bad4(m[2], par)) & 1) == 0, dl)) break;
              __nanosleep(200);
            }
            #pragma unroll
            for (int e = 0; e < 3; e++) sts64(vdst + (v + e) * 256, hi_halves(m[e].x, m[e].y), hi_halves(m[e].z, m[e].w));
            mbar_arrive_e(sbase + B_VEC + 8 * v);
            PROF(70, lane == 0 && v == 0);
          }
        } else {
          mbar_wait(sbase + B_LN, 0, dl);
          red_add_e(&mail0->flags[FL_LN1], 1);
          wait_flag(&mail0->flags[FL_LN1], e1 * NCTA, dl);
          mbar_arrive_e(sbase + B_GATE);
          PROF(41, lane == 0);
          mbar_sleep(sbase + B_FLG, 0, dl);
          #pragma unroll
          for (int e = 0; e < 2; e++) st_rlx_v4(mail0->st2 + ((mb * 8 + e * 4 + (lane >> 3)) * 8 + j) * 8 + (lane & 7), 0, 0, 0, 0, true);
          __threadfence();
          mbar_arrive_e(sbase + B_RST);
          PROF(86, lane == 0);
        }
      }
    }
  } else {
    const int wg = wid >> 2, warp = wid & 3;
    const int g = lane >> 2, qd = lane & 3;
    bulk_prefetch(wmod + (size_t)(b * 8 + wid) * (6 * D_), PF_BYTES);
    bulk_prefetch(wmod + (size_t)(b * 8 + wid) * (6 * D_) + D_, PF_BYTES);
    bar_sync(0, 384);
    bulk_prefetch(wmod + (size_t)(b * 8 + wid) * (6 * D_) + PF_BYTES / 2, PF_BYTES);
    bulk_prefetch(wmod + (size_t)(b * 8 + wid) * (6 * D_) + PF_BYTES / 2 + D_, PF_BYTES);
    const unsigned e1 = 1 + ld_relaxed(flags + FO_EPOCH), par = e1 & 1;
    reg_alloc<232>();
    PROF(1, tid == 0);
    const uint32_t wgoff = wg * 8192;
    const uint32_t frag0 = wid * 2048 + (lane & 15) * 128 + (((lane >> 4) ^ (lane & 7)) << 4);
    const uint32_t slab = sbase + SM_STG + wid * 2048;

    LnRow ln;
    {
      uint2* const lmail = &mail0->ln1[(mb * 8 + (wid & 1) * 4 + (j >> 1)) * 16 + (j & 1) * 8 + (wid >> 1) + (lane & 1) * 4];
      float sm = 0.f, qm = 0.f, so = 0.f, qo = 0.f;
      #pragma unroll
      for (int h = 0; h < 2; h++) {
        sm = so; qm = qo;
        float s[2] = {0.f, 0.f}, q2[2] = {0.f, 0.f};
        mbar_wait(sbase + B_X + 8 * (4 * h + (wid >> 1)), 0, dl);
        PROF(3, tid == 224); PROF(93, tid == 0);
        #pragma unroll
        for (int c = 0; c < 4; c++) {
          const uint4 v = lds128(sbase + SM_XR + h * 16384 + wid * 2048 + c * 512 + lane * 16);
          const uint32_t vv[4] = {v.x, v.y, v.z, v.w};
          #pragma unroll
          for (int e = 0; e < 4; e++) {
            const float lo = bf_lo(vv[e]), hi = bf_hi(vv[e]);
            s[0] += lo; s[1] += hi; q2[0] = fmaf(lo, lo, q2[0]); q2[1] = fmaf(hi, hi, q2[1]);
          }
        }
        so = s[0] + s[1]; qo = q2[0] + q2[1];
      }
      const bool odd = lane & 1;
      { const float a = odd ? so : sm, c = odd ? qo : qm;
        sm = a + __shfl_xor_sync(0xffffffffu, odd ? sm : so, 1); qm = c + __shfl_xor_sync(0xffffffffu, odd ? qm : qo, 1); }
      #pragma unroll
      for (int o = 2; o < 32; o <<= 1) { sm += __shfl_xor_sync(0xffffffffu, sm, o); qm += __shfl_xor_sync(0xffffffffu, qm, o); }
      sm *= (1.f / D_);
      ln_row(ln, 0, sm, fast_rsqrt(fmaxf(qm * (1.f / D_) - sm * sm, 0.f) + 1e-5f));
      st_rlx_v2(lmail, (ln.rs[0] << 16) | par, (ln.nb[0] << 16) | par, lane < 2);
      mbar_arrive_e(sbase + B_LN);
      PROF(4, tid == 224);
    }

    uint4* const halo_out = mail0->halo[par] + ((mb * 16 + j) * 2 + wg) * 128 + lane;
    const uint4* const halo_in = halo_out - 16 * 256;
    const uint32_t xch = sbase + SM_XCH + (tid >> 5) * 2048 + lane * 16;
    const bool noprev = mb == 0 && warp == 0, remote = mb > 0 && warp == 0;
    float a0[64], a1[64];
    uint32_t x2[32];
    Ring r{zero, 0, 0, dl};
    Frag8 qA, qB, kA, kB, vA, vB, wA, wB;
    {
      float acc[128];
      uint32_t A0[16], A1[16];
      undef_regs(acc);
      const uint32_t tab = sbase + SM_MODT + qd * 16;
      uint4 p[4];
      const uint32_t rot = j >> 1;
      Frag4 fq;
      #pragma unroll
      for (int q = 0; q < 4; q++) fq.o[q] = frag0 ^ ((q ^ rot) << 5);
      mbar_wait(sbase + B_LN, 0, dl);
      const uint2* const lin = &mail0->ln1[(mb * 8 + wid) * 16 + g];
      uint2 v0, v1;
      q_wait(0, sbase, dl);
      #pragma unroll
      for (int kk = 0; kk < 4; kk++) ldmatrix_x4(sbase + SM_X0 + fq.o[kk], A0[4 * kk], A0[4 * kk + 1], A0[4 * kk + 2], A0[4 * kk + 3]);
      do { v0 = ld_rlx_v2(lin); v1 = ld_rlx_v2(lin + 8); } while (!poll_done(((bad2(v0.x, v0.y, par) | bad2(v1.x, v1.y, par)) & 1) == 0, dl));
      ln.rs[0] = hi_halves(v0.x, v0.x); ln.nb[0] = hi_halves(v0.y, v0.y); ln.rs[1] = hi_halves(v1.x, v1.x); ln.nb[1] = hi_halves(v1.y, v1.y);
      mbar_wait(sbase + B_MOD, 0, dl);
      #pragma unroll
      for (int kk = 0; kk < 4; kk++) p[kk] = lds128(tab + kk * 64);
      PROF(5, tid == 0);
      q_step_rs<true>(acc, A0, A1, p, 0, sbase, fq, tab, ln, rot, !(j & 1), true, dl, wg, zero);
      #pragma unroll
      for (int u = 1; u < 15; u += 2) {
        q_step_rs<true>(acc, A1, A0, p, u, sbase, fq, tab, ln, rot, j & 1, false, dl, wg, zero);
        q_step_rs<true>(acc, A0, A1, p, u + 1, sbase, fq, tab, ln, rot, !(j & 1), false, dl, wg, zero);
        if (u == 7) mbar_arrive_e(sbase + B_STREQ);
      }
      q_step_rs<false>(acc, A1, A0, p, 15, sbase, fq, tab, ln, rot, j & 1, false, dl, wg, zero);
      PROF(7, tid == 0);
      mbar_wait(sbase + B_STFREE, 0, dl);
      request_store(sbase + B_STREQ);
      wgmma_wait<0>();
      undef_regs(a0);
      { const uint32_t slot = m_wait(sbase, r); mma_step(a0, slot + wgoff, slot + 16384, true, q_empty(15, sbase)); m_next(r); }
      fence_regs(acc);
      PROF(8, tid == 0);
      sched_fence(zero);
      pack_half(vB, acc, 64, 1); transpose8(vB);
      m_step(a0, sbase, wgoff, r);
      sched_fence(zero);
      pack_half(kB, acc, 32, 1);
      attn_send(vB, 1, xch - 16384, warp, halo_out, mb < 15); attn_send(kB, 0, xch - 16384, warp, halo_out, mb < 15);
      m_step(a0, sbase, wgoff, r);
      sched_fence(zero);
      pack_half(qA, acc, 0, 0); pack_half(qB, acc, 0, 1); pack_half(kA, acc, 32, 0); pack_half(wB, acc, 96, 1); pack_half(wA, acc, 96, 0);
      m_step(a0, sbase, wgoff, r);
      sched_fence(zero);
      pack_half(vA, acc, 64, 0); transpose8(vA);
    }
    uint4 wP[2];
    Frag4 frag;
    #pragma unroll
    for (int q = 0; q < 4; q++) frag.o[q] = frag0 ^ (q << 5);
    {
      m_step(a0, sbase, wgoff, r);
      uint4 pv[4];
      attn_recv<4>(pv, 0, xch - 16384, wg, warp, halo_in, mb > 0);
      m_step(a0, sbase, wgoff, r);
      mbar_wait(sbase + B_STFREE, 1, dl);
      transpose8(wB);
      m_step(a0, sbase, wgoff, r);
      attn_check<4>(pv, 0, remote, halo_in, dl);
      wgmma_wait<0>();
      PROF(9, tid == 0);
      float o[2][5][4];
      sched_fence(zero);
      attn_core<0>(qA, qB, kA, kB, vA, vB, pv, pv + 2, noprev, lane, o, Nop());
      attn_store(o, 0, sbase, frag);
      attn_store(o, 1, sbase, frag);
      request_store(sbase + B_STREQ);
      bar_sync(NB_CONS, 256);
      PROF(10, tid == 0);
      m_step(a0, sbase, wgoff, r);
      sched_fence(zero);
      attn_send(wB, 1, xch, warp, halo_out + 8 * 256, mb < 15);
      m_step(a0, sbase, wgoff, r);
      sched_fence(zero);
      transpose8(wA);
      #pragma unroll 1
      for (int i = 9; i < 15; i++) m_step(a0, sbase, wgoff, r);
      attn_recv<2>(wP, 2, xch, wg, warp, halo_in + 8 * 256, mb > 0);
      m_step(a0, sbase, wgoff, r);
    }
    {
      undef_regs(a1);
      {
        const uint32_t slot = m_wait(sbase, r);
        mma_step(a1, slot + wgoff, slot + 16384, true, m_prev(sbase, r), [&] {
          fence_regs(a0);
          pack_half(kB, a0, 32, 1);
          attn_send(kB, 0, xch, warp, halo_out + 8 * 256, mb < 15);
        });
        m_next(r);
      }
      PROF(14, tid == 0);
      sched_fence(zero);
      pack_half(kA, a0, 32, 0); pack_half(qA, a0, 0, 0); pack_half(qB, a0, 0, 1);
      m_step(a1, sbase, wgoff, r);
      attn_check<2>(wP, 2, remote, halo_in + 8 * 256, dl);
      uint4 kP[2];
      attn_recv<2>(kP, 0, xch, wg, warp, halo_in + 8 * 256, mb > 0);
      m_step(a1, sbase, wgoff, r);
      if (ASPLIT == 0) attn_check<2>(kP, 0, remote, halo_in + 8 * 256, dl);
      wgmma_wait<0>();
      PROF(15, tid == 0);
      float o[2][5][4];
      mbar_wait(sbase + B_STFREE, 0, dl);
      attn_core<ASPLIT>(qA, qB, kA, kB, wA, wB, kP, wP, noprev, lane, o, [&] { attn_check<2>(kP, 0, remote, halo_in + 8 * 256, dl); });
      attn_store(o, 0, sbase, frag);
      attn_store(o, 1, sbase, frag);
      request_store(sbase + B_STREQ);
      bar_sync(NB_CONS, 256);
      PROF(16, tid == 0);
      auto residual = [&] {
        const uint32_t xs = m_wait(sbase, r), xe = sbase + B_EM + 8 * r.st;
        ring_next(r);
        #pragma unroll
        for (int t = 0; t < 2; t++) {
          #pragma unroll
          for (int jj = 4 * t; jj < 4 * t + 4; jj++) ldmatrix_x4(xs + t * 16384 + frag.o[jj & 3], x2[4 * jj], x2[4 * jj + 1], x2[4 * jj + 2], x2[4 * jj + 3]);
          if (t == 1) {
            uint32_t dep = 0;
            #pragma unroll
            for (int jj = 0; jj < 8; jj++) dep |= x2[4 * jj];
            mbar_arrive_e(xe + (dep & zero));
          }
          m_step(a1, sbase, wgoff, r);
        }
      };
      m_step(a1, sbase, wgoff, r);
      residual();
      #pragma unroll 1
      for (int i = 6; i < 8; i++) m_step(a1, sbase, wgoff, r);
      mma_step(a1, sbase + SM_STG + wgoff, m_wait(sbase, r) + 16384, false, m_prev(sbase, r));
      m_next(r);
      PROF(17, tid == 0);
      #pragma unroll 1
      for (int i = 0; i < 7; i++) { m_step(a1, sbase, wgoff, r); PROF(42, tid == 0 && i == 0); }
      PROF(45, tid == 0);
      uint4* sm = mail0->st2 + (mb * 8 + wid) * 64 + g;
      asm volatile("" : "+l"(sm));
      mbar_wait(sbase + B_VEC, 0, dl);
      mbar_wait(sbase + B_STFREE, 1, dl);
      const uint32_t vec = sbase + SM_VEC + qd * 16;
      uint4 ga[4];
      #pragma unroll
      for (int q = 0; q < 4; q++) ga[q] = lds128(vec + q * 64);
      wgmma_wait<0>();
      mbar_arrive_e(m_prev(sbase, r));
      fence_regs(a1);
      PROF(18, tid == 0);
      float gl[4] = {0.f, 0.f, 0.f, 0.f}, gh[4] = {0.f, 0.f, 0.f, 0.f};
      #pragma unroll
      for (int jj = 0; jj < 8; jj++) {
        uint32_t* v = &x2[4 * jj];
        const uint32_t wl = (jj & 1) ? ga[jj >> 1].z : ga[jj >> 1].x, wh = (jj & 1) ? ga[jj >> 1].w : ga[jj >> 1].y;
        #pragma unroll
        for (int e = 0; e < 4; e++) v[e] = fma_bf2(e & 2 ? wh : wl, pack_bf16(a1[8 * jj + 2 * e], a1[8 * jj + 2 * e + 1]), v[e]);
        mma16(gl, v[0], 0x3F803F80u, v[2], 0x3F803F80u, v[0], v[2]);
        mma16(gh, v[1], 0x3F803F80u, v[3], 0x3F803F80u, v[1], v[3]);
      }
      st_nonzero_v4(sm + j * 8, __float_as_uint(g & 1 ? gl[3] : gl[2]), __float_as_uint(g & 1 ? gl[1] : gl[0]),
                __float_as_uint(g & 1 ? gh[3] : gh[2]), __float_as_uint(g & 1 ? gh[1] : gh[0]), qd == (g >> 1));
      float s[2], q2[2];
      PROF(19, tid == 0);
      uint4 sb[4], cb[4];
      #pragma unroll
      for (int q = 0; q < 4; q++) { sb[q] = lds128(vec + 256 + q * 64); cb[q] = lds128(vec + 512 + q * 64); }
      uint4 p0, p1;
      while (true) {
        p0 = ld_rlx_v4(sm + qd * 16); p1 = ld_rlx_v4(sm + qd * 16 + 8);
        if (poll_done(min(min4(p0), min4(p1)) != 0, dl)) break;
      }
      PROF(20, tid == 0);
      s[0] = __uint_as_float(p0.x) + __uint_as_float(p1.x); q2[0] = __uint_as_float(p0.y) + __uint_as_float(p1.y);
      s[1] = __uint_as_float(p0.z) + __uint_as_float(p1.z); q2[1] = __uint_as_float(p0.w) + __uint_as_float(p1.w);
      #pragma unroll
      for (int o2 = 1; o2 <= 2; o2 <<= 1)
        #pragma unroll
        for (int h = 0; h < 2; h++) { s[h] += __shfl_xor_sync(0xffffffffu, s[h], o2); q2[h] += __shfl_xor_sync(0xffffffffu, q2[h], o2); }
      #pragma unroll
      for (int h = 0; h < 2; h++) {
        const float m = s[h] * (1.f / D_);
        ln_row(ln, h, m, fast_rsqrt(fmaxf(q2[h] * (1.f / D_) - m * m, 0.f) + 1e-5f));
      }
      #pragma unroll
      for (int jj = 0; jj < 8; jj++) {
        const uint32_t cl = (jj & 1) ? cb[jj >> 1].z : cb[jj >> 1].x, ch = (jj & 1) ? cb[jj >> 1].w : cb[jj >> 1].y;
        const uint32_t sl = (jj & 1) ? sb[jj >> 1].z : sb[jj >> 1].x, sh = (jj & 1) ? sb[jj >> 1].w : sb[jj >> 1].y;
        stmatrix_x4(sbase + SM_STG + (jj >> 2) * 16384 + frag.o[jj & 3], ln_mod(x2[4 * jj], ln, 0, cl, sl), ln_mod(x2[4 * jj + 1], ln, 1, cl, sl),
                    ln_mod(x2[4 * jj + 2], ln, 0, ch, sh), ln_mod(x2[4 * jj + 3], ln, 1, ch, sh));
        if (jj == 3) { request_store(sbase + B_STH); sched_fence(zero); }
      }
      request_store(sbase + B_STREQ);
      bar_sync(NB_WG + wg, 128);
      PROF(21, tid == 0);
    }

    undef_regs(a0);
    #pragma unroll
    for (int t = 0; t < 2; t++) {
      const uint32_t slot = m_wait(sbase, r);
      if (t == 0) mma_step<false>(a0, sbase + SM_STG + wgoff, slot, true, 0);
      else mma_step(a0, sbase + SM_STG + 16384 + wgoff, slot, false, m_prev(sbase, r));
      mma_step<false>(a1, sbase + SM_STG + t * 16384 + wgoff, slot + 16384, t == 0, 0);
      m_next(r);
    }
    PROF(22, tid == 0);
    #pragma unroll 1
    for (int i = 0; i < 2; i++) m_step(a0, sbase, wgoff, r);
    uint32_t held = 0;
    #pragma unroll 1
    for (int pr = 0; pr < 3; pr++) {
      #pragma unroll 1
      for (int i = 0; i < 5; i++) { g_quad(a0, a1, held, sbase, wgoff, r); held = 0; }
      held = g_ppqq<false, true>(a0, a1, false, 0, sbase, wgoff, r, [&](int i) { if (i >= 2) g_piece<0>(a0, i - 2, pr, sbase, frag, dl); });
      held = g_ppqq<true, true>(a1, a0, true, held, sbase, wgoff, r,
                                [&](int i) { if (i < 2) g_piece<0>(a0, i + 2, pr, sbase, frag, dl); else g_piece<1>(a1, i - 2, pr, sbase, frag, dl); });
      if (pr == 2) break;
      held = g_ppqq<true, true>(a0, a1, true, held, sbase, wgoff, r, [&](int i) { if (i < 2) g_piece<1>(a1, i + 2, pr, sbase, frag, dl); });
    }
    g_ppqq<true, false>(a0, a1, false, held, sbase, wgoff, r, [&](int i) { g_piece<1>(a1, i + 2, 2, sbase, frag, dl); });
    #pragma unroll 1
    for (int i = 4; i < 15; i++) m_step(a0, sbase, wgoff, r);
    m_step(a0, sbase, wgoff, r);
    #pragma unroll
    for (int jj = 0; jj < 4; jj++) { m_step(a1, sbase, wgoff, r, jj == 0); g_piece<0>(a0, jj, 3, sbase, frag, dl); }
    #pragma unroll 1
    for (int i = 4; i < 56 - DTAIL; i++) m_step(a1, sbase, wgoff, r);
    if (DTAIL) {
      if (wg == 1) { wgmma_wait<0>(); mbar_arrive_e(m_prev(sbase, r)); bar_sync(NB_ORD, 256); }
      #pragma unroll 1
      for (int i = 0; i < DTAIL; i++) {
        const uint32_t slot = m_wait(sbase, r);
        const uint32_t alo = ((slot + wgoff) >> 4) + (1u << 16), blo = ((slot + 16384) >> 4) + (512u << 16);
        wgmma_fence();
        #pragma unroll
        for (int k = 0; k < 4; k++) wgmma_m64n128k16_ss(a1, desc_from_lo(alo + k * 2), desc_from_lo(blo + k * 128), true);
        wgmma_commit();
        ring_next(r);
      }
      if (wg == 0) bar_arrive(NB_ORD, 256);
    }
    {
      mbar_wait(sbase + B_HFREE, 0, dl);
      mbar_wait(sbase + B_HFREE + 8, 1, dl);
      mbar_wait(sbase + B_VEC + 8, 0, dl);
      uint4 gb[4];
      #pragma unroll
      for (int q = 0; q < 4; q++) gb[q] = lds128(sbase + SM_VEC + 768 + qd * 16 + q * 64);
      wgmma_wait<0>();
      fence_regs(a1);
      PROF(50, tid == 128);
      #pragma unroll
      for (int t = 0; t < 2; t++) {
        #pragma unroll
        for (int jj = 4 * t; jj < 4 * t + 4; jj++) {
          const uint32_t gl = (jj & 1) ? gb[jj >> 1].z : gb[jj >> 1].x, gh = (jj & 1) ? gb[jj >> 1].w : gb[jj >> 1].y;
          const int i = 8 * jj;
          stmatrix_x4(sbase + SM_STG + t * 16384 + frag.o[jj & 3],
                      fma_bf2(gl, pack_bf16(a1[i], a1[i + 1]), x2[4 * jj]), fma_bf2(gl, pack_bf16(a1[i + 2], a1[i + 3]), x2[4 * jj + 1]),
                      fma_bf2(gh, pack_bf16(a1[i + 4], a1[i + 5]), x2[4 * jj + 2]), fma_bf2(gh, pack_bf16(a1[i + 6], a1[i + 7]), x2[4 * jj + 3]));
        }
        fence_proxy_async_smem();
        tma_store_3d(&maps.out, slab + t * 16384, j * 128 + t * 64, mb * 64 + warp * 16, wg);
      }
      bulk_commit();
      st_rlx(tid == 0 ? flags + FO_EPOCH : &mail0->flags[FL_EPOCH], e1, j == 0 && (tid == 0 || (tid == 1 && mb == 0)));
      bulk_wait_read0();
      PROFN(51, tid == 128);
    }
  }
}

typedef CUresult (*PFN_encodeTiled)(CUtensorMap*, CUtensorMapDataType, cuuint32_t, void*, const cuuint64_t*, const cuuint64_t*,
                                    const cuuint32_t*, const cuuint32_t*, CUtensorMapInterleave, CUtensorMapSwizzle,
                                    CUtensorMapL2promotion, CUtensorMapFloatOOBfill);

void encode(PFN_encodeTiled fn, CUtensorMap* m, const void* ptr, int rank, const cuuint64_t* dims, const cuuint64_t* strides,
            const cuuint32_t* box) {
  const cuuint32_t es[5] = {1, 1, 1, 1, 1};
  fn(m, CU_TENSOR_MAP_DATA_TYPE_BFLOAT16, rank, const_cast<void*>(ptr), dims, strides, box, es, CU_TENSOR_MAP_INTERLEAVE_NONE,
     CU_TENSOR_MAP_SWIZZLE_128B, CU_TENSOR_MAP_L2_PROMOTION_L2_256B, CU_TENSOR_MAP_FLOAT_OOB_FILL_NONE);
}
void map2d(PFN_encodeTiled fn, CUtensorMap* m, const void* ptr, int cols, int rows, int boxrows) {
  const cuuint64_t dims[2] = {(cuuint64_t)cols, (cuuint64_t)rows}, strides[1] = {(cuuint64_t)cols * 2};
  const cuuint32_t box[2] = {64, (cuuint32_t)boxrows};
  encode(fn, m, ptr, 2, dims, strides, box);
}
void map_w2chunk(PFN_encodeTiled fn, CUtensorMap* m, const void* ptr, int cols, int rows) {
  const cuuint64_t dims[3] = {64, (cuuint64_t)rows, (cuuint64_t)cols / 64}, strides[2] = {(cuuint64_t)cols * 2, 128};
  const cuuint32_t box[3] = {64, 64, 2};
  encode(fn, m, ptr, 3, dims, strides, box);
}
void map_parity(PFN_encodeTiled fn, CUtensorMap* m, const void* ptr, int boxpairs, int boxpar) {
  const cuuint64_t dims[3] = {D_, S_ / 2, 2}, strides[2] = {D_ * 4, D_ * 2};
  const cuuint32_t box[3] = {64, (cuuint32_t)boxpairs, (cuuint32_t)boxpar};
  encode(fn, m, ptr, 3, dims, strides, box);
}

}

extern "C" void kernel_launch(void* const* d_in, const int* in_sizes, int n_in, void* d_out, int out_size) {
  (void)in_sizes; (void)n_in; (void)out_size;
  const bf16* x = (const bf16*)d_in[0];
  const bf16* wqkv = (const bf16*)d_in[1];
  const bf16* wo = (const bf16*)d_in[2];
  const bf16* w1 = (const bf16*)d_in[4];
  const bf16* w3 = (const bf16*)d_in[5];
  const bf16* w2 = (const bf16*)d_in[6];
  const bf16* cvec = (const bf16*)d_in[7];
  const bf16* w_mod = (const bf16*)d_in[8];

  static PFN_encodeTiled fn = nullptr;
  static Maps maps;
  static const void* cached[8] = {};
  static int sms = 0;
  static void* mail = nullptr;
  if (!fn) {
    void* p = nullptr; cudaDriverEntryPointQueryResult st;
    cudaGetDriverEntryPoint("cuTensorMapEncodeTiled", &p, cudaEnableDefault, &st);
    fn = (PFN_encodeTiled)p;
    cudaFuncSetAttribute(fused_block_kernel<0>, cudaFuncAttributeMaxDynamicSharedMemorySize, SM_TOTAL + SM_PROF);
    cudaFuncSetAttribute(fused_block_kernel<1>, cudaFuncAttributeMaxDynamicSharedMemorySize, SM_TOTAL + SM_PROF);
    cudaFuncSetAttribute(fused_block_kernel<2>, cudaFuncAttributeMaxDynamicSharedMemorySize, SM_TOTAL + SM_PROF);
    cudaGetSymbolAddress(&mail, g_mail);
    int dev = 0;
    cudaGetDevice(&dev);
    cudaDeviceGetAttribute(&sms, cudaDevAttrMultiProcessorCount, dev);
  }
  const void* cur[8] = {x, wqkv, wo, w1, w3, w2, d_out, w_mod};
  bool same = true;
  for (int i = 0; i < 8; i++) same = same && cached[i] == cur[i];
  if (!same) {
    void *o, *hh;
    cudaGetSymbolAddress(&hh, g_hh); cudaGetSymbolAddress(&o, g_o);
    map_parity(fn, &maps.x, x, 64, 2); map_parity(fn, &maps.out, d_out, 16, 1);
    map2d(fn, &maps.o, o, D_, S_, 128);
    {
      const cuuint64_t dims[3] = {512, (cuuint64_t)S_, 7}, strides[2] = {1024, (cuuint64_t)S_ * 1024};
      const cuuint32_t box[3] = {64, 128, 1};
      encode(fn, &maps.hh, hh, 3, dims, strides, box);
    }
    {
      const cuuint64_t dims[4] = {64, 1024, 16, 2}, strides[3] = {3072 * 2, 128, 2048};
      const cuuint64_t dimv[4] = {64, 1024, 8, 2}, stridev[3] = {3072 * 2, 128, 1024};
      const cuuint32_t box[4] = {64, 64, 1, 2};
      encode(fn, &maps.wqk, wqkv, 4, dims, strides, box);
      encode(fn, &maps.wvv, wqkv + 2048, 4, dimv, stridev, box);
      const cuuint64_t dim1[4] = {1024, 128, 8, 2}, stride1[3] = {3072 * 2, 128 * 3072 * 2, 2048};
      const cuuint32_t box1[4] = {64, 16, 4, 2};
      encode(fn, &maps.wq1, wqkv, 4, dim1, stride1, box1);
    }
    map_w2chunk(fn, &maps.wo, wo, D_, D_); map_w2chunk(fn, &maps.w2, w2, D_, F_);
    map2d(fn, &maps.w1, w1, F_, D_, 64); map2d(fn, &maps.w3, w3, F_, D_, 64);
    map2d(fn, &maps.wmod, w_mod, 6 * D_, D_, 256);
    for (int i = 0; i < 8; i++) cached[i] = cur[i];
  }
  if (sms == NCTA + NAUX) {
    fused_block_kernel<0><<<NCTA + NAUX, 384, SM_TOTAL + SM_PROF>>>(x, cvec, w_mod, (Mail*)mail, 0, maps);
  } else {
    fused_block_kernel<1><<<NAUX, 384, SM_TOTAL + SM_PROF>>>(x, cvec, w_mod, (Mail*)mail, 0, maps);
    fused_block_kernel<2><<<NCTA, 384, SM_TOTAL + SM_PROF>>>(x, cvec, w_mod, (Mail*)mail, 0, maps);
  }
}
```

```cpp
#include <cuda.h>
#include <cuda_runtime.h>
#include <cuda_bf16.h>
#include <stdint.h>

namespace {

typedef __nv_bfloat16 bf16;

constexpr int S_ = 2048, D_ = 1024, F_ = 3584;
constexpr int NCTA = 128, NAUX = 4;

__device__ __align__(1024) bf16 g_o[S_ * D_];
__device__ __align__(1024) bf16 g_hh[S_ * F_];
constexpr int FO_EPOCH = 0, FO_CNT = 1;
constexpr int FL_EPOCH = 16 * 32, FL_LN1 = FL_EPOCH + 2, FL_O = FL_EPOCH + 3, FL_H2 = FL_EPOCH + 4;
struct Mail {
  unsigned flags[32 * 32];
  float mod[8 * 6 * D_];
  uint2 ln1[16 * 8 * 16];
  uint4 st2[16 * 8 * 8 * 8];
  uint4 halo[2][16 * 16 * 2 * 4 * 32];
};
__device__ __align__(1024) Mail g_mail;

template <int mode>
__device__ __forceinline__ int cta_role() {
  if (mode) return mode == 1 ? NCTA + (blockIdx.x & 3) : blockIdx.x & 127;
  uint32_t sm;
  asm("mov.u32 %0, %%smid;" : "=r"(sm));
  sm = (sm & ~3u) == 12 ? sm + 108 : (sm & ~3u) == 120 ? sm - 108 : sm;
  const int t = sm >> 1;
  int r;
  if (t < 32) r = (t & 7) * 16 + (t >> 3) * 2 + (sm & 1);
  else if (t < 60) r = (1 + (t - 32) % 7) * 16 + 8 + ((t - 32) / 7) * 2 + (sm & 1);
  else if (t < 62) r = NCTA + sm - 120;
  else r = sm - 116;
  return r;
}
#define PROF(slot, on) do {} while (0)
#define PROFN(slot, on) do {} while (0)
#define PROF_OUT(role, t) do {} while (0)
constexpr uint32_t SM_PROF = 0;

__device__ __forceinline__ uint32_t smem_u32(const void* p) { return (uint32_t)__cvta_generic_to_shared(p); }
#define ELECT "{\n.reg .pred p;\nelect.sync _|p, 0xffffffff;\n@p "
__device__ __forceinline__ void mbar_init_e(uint32_t bar, uint32_t count) {
  asm volatile(ELECT "mbarrier.init.shared::cta.b64 [%0], %1;\n}" :: "r"(bar), "r"(count) : "memory");
}
__device__ __forceinline__ void mbar_expect_tx_e(uint32_t bar, uint32_t bytes) {
  asm volatile(ELECT "mbarrier.arrive.expect_tx.shared::cta.b64 _, [%0], %1;\n}" :: "r"(bar), "r"(bytes) : "memory");
}
__device__ __forceinline__ void mbar_arrive_e(uint32_t bar) {
  asm volatile(ELECT "mbarrier.arrive.shared::cta.b64 _, [%0];\n}" :: "r"(bar) : "memory");
}
__device__ __forceinline__ uint32_t clock32() { uint32_t t; asm volatile("mov.u32 %0, %%clock;" : "=r"(t)); return t; }
#define WAIT_TAIL "setp.ne.and.u32 p, %2, 0, !p;\n@p bra LAB_WAIT;\n}"
__device__ __forceinline__ void mbar_wait(uint32_t bar, uint32_t parity, uint32_t dl) {
  asm volatile("{\n.reg .pred p;\n.reg .b32 t;\nLAB_WAIT:\nmbarrier.try_wait.parity.shared::cta.b64 p, [%0], %1;\n" WAIT_TAIL
               :: "r"(bar), "r"(parity), "r"(dl) : "memory");
}
__device__ __forceinline__ void mbar_sleep(uint32_t bar, uint32_t parity, uint32_t dl) {
  asm volatile("{\n.reg .pred p;\n.reg .b32 t;\nLAB_WAIT:\nmbarrier.try_wait.parity.shared::cta.b64 p, [%0], %1, 20000;\n" WAIT_TAIL
               :: "r"(bar), "r"(parity), "r"(dl) : "memory");
}
__device__ __forceinline__ bool poll_done(bool ok, uint32_t dl) {
  return __all_sync(0xffffffffu, ok || (int)(clock32() - dl) >= 0);
}
__device__ __forceinline__ unsigned ld_relaxed(const unsigned* p) {
  unsigned v; asm volatile("ld.relaxed.gpu.global.u32 %0, [%1];" : "=r"(v) : "l"(p) : "memory"); return v;
}
__device__ __forceinline__ void red_add_e(unsigned* p, unsigned v) {
  asm volatile(ELECT "red.relaxed.gpu.global.add.u32 [%0], %1;\n}" :: "l"(p), "r"(v) : "memory");
}
__device__ __forceinline__ void wait_flag(const unsigned* p, unsigned target, uint32_t dl) {
  asm volatile("{\n.reg .pred p;\n.reg .b32 t;\n"
               "LAB_WAIT:\n"
               "ld.relaxed.gpu.global.u32 t, [%0];\n"
               "sub.s32 t, t, %1;\n"
               "setp.ge.s32 p, t, 0;\n"
               "@p bra LAB_DONE;\n"
               "mov.u32 t, %%clock;\n"
               "sub.s32 t, t, %2;\n"
               "setp.lt.s32 p, t, 0;\n"
               "@p bra LAB_WAIT;\n"
               "LAB_DONE:\n}" :: "l"(p), "r"(target), "r"(dl) : "memory");
}
__device__ __forceinline__ void wait_until(uint32_t t) { while ((int)(clock32() - t) < 0) {} }
__device__ __forceinline__ void fence_proxy_async_smem() { asm volatile("fence.proxy.async.shared::cta;" ::: "memory"); }

constexpr uint64_t EVICT_FIRST = 0x12F0000000000000ull;
template <bool STREAM = false>
__device__ __forceinline__ void tma_load_2d(uint32_t dst, const CUtensorMap* m, uint32_t bar, int c0, int c1) {
  if (STREAM)
    asm volatile(ELECT "cp.async.bulk.tensor.2d.shared::cluster.global.mbarrier::complete_tx::bytes.L2::cache_hint [%0], [%1, {%3, %4}], [%2], %5;\n}"
                 :: "r"(dst), "l"(m), "r"(bar), "r"(c0), "r"(c1), "l"(EVICT_FIRST) : "memory");
  else
    asm volatile(ELECT "cp.async.bulk.tensor.2d.shared::cluster.global.mbarrier::complete_tx::bytes [%0], [%1, {%3, %4}], [%2];\n}"
                 :: "r"(dst), "l"(m), "r"(bar), "r"(c0), "r"(c1) : "memory");
}
template <bool STREAM = false>
__device__ __forceinline__ void tma_load_3d(uint32_t dst, const CUtensorMap* m, uint32_t bar, int c0, int c1, int c2) {
  if (STREAM)
    asm volatile(ELECT "cp.async.bulk.tensor.3d.shared::cluster.global.mbarrier::complete_tx::bytes.L2::cache_hint [%0], [%1, {%3, %4, %5}], [%2], %6;\n}"
                 :: "r"(dst), "l"(m), "r"(bar), "r"(c0), "r"(c1), "r"(c2), "l"(EVICT_FIRST) : "memory");
  else
    asm volatile(ELECT "cp.async.bulk.tensor.3d.shared::cluster.global.mbarrier::complete_tx::bytes [%0], [%1, {%3, %4, %5}], [%2];\n}"
                 :: "r"(dst), "l"(m), "r"(bar), "r"(c0), "r"(c1), "r"(c2) : "memory");
}
template <bool STREAM = false>
__device__ __forceinline__ void tma_load_4d(uint32_t dst, const CUtensorMap* m, uint32_t bar, int c0, int c1, int c2, int c3) {
  if (STREAM)
    asm volatile(ELECT "cp.async.bulk.tensor.4d.shared::cluster.global.mbarrier::complete_tx::bytes.L2::cache_hint [%0], [%1, {%3, %4, %5, %6}], [%2], %7;\n}"
                 :: "r"(dst), "l"(m), "r"(bar), "r"(c0), "r"(c1), "r"(c2), "r"(c3), "l"(EVICT_FIRST) : "memory");
  else
    asm volatile(ELECT "cp.async.bulk.tensor.4d.shared::cluster.global.mbarrier::complete_tx::bytes [%0], [%1, {%3, %4, %5, %6}], [%2];\n}"
                 :: "r"(dst), "l"(m), "r"(bar), "r"(c0), "r"(c1), "r"(c2), "r"(c3) : "memory");
}
__device__ __forceinline__ void tma_store_2d(const CUtensorMap* m, uint32_t src, int c0, int c1) {
  asm volatile(ELECT "cp.async.bulk.tensor.2d.global.shared::cta.bulk_group [%0, {%2, %3}], [%1];\n}"
               :: "l"(m), "r"(src), "r"(c0), "r"(c1) : "memory");
}
__device__ __forceinline__ void tma_store_3d(const CUtensorMap* m, uint32_t src, int c0, int c1, int c2) {
  asm volatile(ELECT "cp.async.bulk.tensor.3d.global.shared::cta.bulk_group [%0, {%2, %3, %4}], [%1];\n}"
               :: "l"(m), "r"(src), "r"(c0), "r"(c1), "r"(c2) : "memory");
}
__device__ __forceinline__ void bulk_load(uint32_t dst, const void* src, uint32_t bytes, uint32_t bar) {
  asm volatile(ELECT "cp.async.bulk.shared::cluster.global.mbarrier::complete_tx::bytes [%0], [%1], %2, [%3];\n}"
               :: "r"(dst), "l"(src), "r"(bytes), "r"(bar) : "memory");
}
__device__ __forceinline__ void bulk_prefetch(const void* src, uint32_t bytes) {
  asm volatile(ELECT "cp.async.bulk.prefetch.L2.global [%0], %1;\n}" :: "l"(src), "r"(bytes) : "memory");
}
__device__ __forceinline__ void bulk_commit() { asm volatile("cp.async.bulk.commit_group;" ::: "memory"); }
__device__ __forceinline__ void bulk_wait0() { asm volatile("cp.async.bulk.wait_group 0;" ::: "memory"); }
__device__ __forceinline__ void bulk_wait_read0() { asm volatile("cp.async.bulk.wait_group.read 0;" ::: "memory"); }
__device__ __forceinline__ void prefetch_tmap(const CUtensorMap* m) { asm volatile(ELECT "prefetch.tensormap [%0];\n}" :: "l"(m) : "memory"); }
__device__ __forceinline__ void wgmma_fence() { asm volatile("wgmma.fence.sync.aligned;" ::: "memory"); }
__device__ __forceinline__ void wgmma_commit() { asm volatile("wgmma.commit_group.sync.aligned;" ::: "memory"); }
template <int N> __device__ __forceinline__ void wgmma_wait() { asm volatile("wgmma.wait_group.sync.aligned %0;" :: "n"(N) : "memory"); }
template <int R> __device__ __forceinline__ void reg_alloc() { asm volatile("setmaxnreg.inc.sync.aligned.u32 %0;" :: "n"(R)); }
template <int R> __device__ __forceinline__ void reg_dealloc() { asm volatile("setmaxnreg.dec.sync.aligned.u32 %0;" :: "n"(R)); }
__device__ __forceinline__ void bar_sync(int id, int n) { asm volatile("bar.sync %0, %1;" :: "r"(id), "r"(n) : "memory"); }
__device__ __forceinline__ void bar_arrive(int id, int n) { asm volatile("bar.arrive %0, %1;" :: "r"(id), "r"(n) : "memory"); }
__device__ __forceinline__ void sched_fence(int zero) {
  asm volatile("{\n.reg .pred p;\n.reg .b32 t;\nsetp.eq.s32 p, %0, 0;\n@p bra.uni LAB_S;\n"
               "LAB_F:\nmov.u32 t, %%clock;\nsetp.eq.u32 p, t, 0;\n@p bra LAB_F;\nLAB_S:\n}" :: "r"(zero) : "memory");
}
template <int N> __device__ __forceinline__ void fence_regs(float (&a)[N]) {
  #pragma unroll
  for (int i = 0; i < N; i++) asm volatile("" : "+f"(a[i]) :: "memory");
}
template <int N> __device__ __forceinline__ void undef_regs(float (&a)[N]) {
  #pragma unroll
  for (int i = 0; i < N; i++) asm volatile("" : "=f"(a[i]));
}

__device__ __forceinline__ uint64_t desc_from_lo(uint32_t lo) { return (uint64_t)lo | ((uint64_t)0x40000040u << 32); }
__device__ __forceinline__ uint32_t pack_bf16(float lo, float hi) {
  uint32_t r; asm("cvt.rn.bf16x2.f32 %0, %1, %2;" : "=r"(r) : "f"(hi), "f"(lo)); return r;
}
__device__ __forceinline__ uint32_t fma_bf2(uint32_t a, uint32_t b, uint32_t c) {
  uint32_t d; asm("fma.rn.bf16x2 %0, %1, %2, %3;" : "=r"(d) : "r"(a), "r"(b), "r"(c)); return d;
}
__device__ __forceinline__ float bf_lo(uint32_t v) { return __uint_as_float(v << 16); }
__device__ __forceinline__ float bf_hi(uint32_t v) { return __uint_as_float(v & 0xFFFF0000u); }
__device__ __forceinline__ float bf16_round(float x) { return bf_lo(pack_bf16(x, 0.f)); }
__device__ __forceinline__ void stmatrix_x4(uint32_t addr, uint32_t r0, uint32_t r1, uint32_t r2, uint32_t r3) {
  asm volatile("stmatrix.sync.aligned.m8n8.x4.shared.b16 [%0], {%1, %2, %3, %4};" :: "r"(addr), "r"(r0), "r"(r1), "r"(r2), "r"(r3) : "memory");
}
__device__ __forceinline__ void stmatrix_x4_t(uint32_t addr, uint32_t r0, uint32_t r1, uint32_t r2, uint32_t r3) {
  asm volatile("stmatrix.sync.aligned.m8n8.x4.trans.shared.b16 [%0], {%1, %2, %3, %4};" :: "r"(addr), "r"(r0), "r"(r1), "r"(r2), "r"(r3) : "memory");
}
__device__ __forceinline__ void stmatrix_x4_if(uint32_t addr, uint32_t r0, uint32_t r1, uint32_t r2, uint32_t r3, bool on) {
  asm volatile("{\n.reg .pred p;\nsetp.ne.b32 p, %5, 0;\n@p stmatrix.sync.aligned.m8n8.x4.shared.b16 [%0], {%1, %2, %3, %4};\n}"
               :: "r"(addr), "r"(r0), "r"(r1), "r"(r2), "r"(r3), "r"((int)on) : "memory");
}
__device__ __forceinline__ void ldmatrix_x4(uint32_t addr, uint32_t& r0, uint32_t& r1, uint32_t& r2, uint32_t& r3) {
  asm volatile("ldmatrix.sync.aligned.m8n8.x4.shared.b16 {%0, %1, %2, %3}, [%4];" : "=r"(r0), "=r"(r1), "=r"(r2), "=r"(r3) : "r"(addr) : "memory");
}
__device__ __forceinline__ void ldmatrix_x4_t(uint32_t addr, uint32_t (&r)[4]) {
  asm volatile("ldmatrix.sync.aligned.m8n8.x4.trans.shared.b16 {%0, %1, %2, %3}, [%4];" : "=r"(r[0]), "=r"(r[1]), "=r"(r[2]), "=r"(r[3]) : "r"(addr) : "memory");
}
__device__ __forceinline__ void st_rlx(void* p, uint32_t a, bool on) {
  asm volatile("{\n.reg .pred p;\nsetp.ne.b32 p, %2, 0;\n@p st.relaxed.gpu.global.u32 [%0], %1;\n}" :: "l"(p), "r"(a), "r"((int)on) : "memory");
}
__device__ __forceinline__ void st_rlx_v2(void* p, uint32_t a, uint32_t b, bool on) {
  asm volatile("{\n.reg .pred p;\nsetp.ne.b32 p, %3, 0;\n@p st.relaxed.gpu.global.v2.u32 [%0], {%1, %2};\n}" :: "l"(p), "r"(a), "r"(b), "r"((int)on) : "memory");
}
__device__ __forceinline__ uint2 ld_rlx_v2(const void* p) {
  uint2 v; asm volatile("ld.relaxed.gpu.global.v2.u32 {%0,%1}, [%2];" : "=r"(v.x), "=r"(v.y) : "l"(p) : "memory"); return v;
}
__device__ __forceinline__ void st_rlx_v4(void* p, uint32_t a, uint32_t b, uint32_t c, uint32_t d, bool on) {
  asm volatile("{\n.reg .pred p;\nsetp.ne.b32 p, %5, 0;\n@p st.relaxed.gpu.global.v4.u32 [%0], {%1, %2, %3, %4};\n}"
               :: "l"(p), "r"(a), "r"(b), "r"(c), "r"(d), "r"((int)on) : "memory");
}
__device__ __forceinline__ void st_nonzero_v4(void* p, uint32_t a, uint32_t b, uint32_t c, uint32_t d, bool on) {
  st_rlx_v4(p, max(a, 1u), max(b, 1u), max(c, 1u), max(d, 1u), on);
}
__device__ __forceinline__ uint32_t min4(const uint4& v) { return min(min(v.x, v.y), min(v.z, v.w)); }
__device__ __forceinline__ uint4 ld_rlx_v4(const void* p) {
  uint4 v; asm volatile("ld.relaxed.gpu.global.v4.u32 {%0,%1,%2,%3}, [%4];" : "=r"(v.x), "=r"(v.y), "=r"(v.z), "=r"(v.w) : "l"(p) : "memory"); return v;
}
__device__ __forceinline__ uint32_t movmatrix_t(uint32_t a) {
  uint32_t d; asm volatile("movmatrix.sync.aligned.m8n8.trans.b16 %0, %1;" : "=r"(d) : "r"(a)); return d;
}
__device__ __forceinline__ void mma16(float (&c)[4], uint32_t a0, uint32_t a1, uint32_t a2, uint32_t a3, uint32_t b0, uint32_t b1) {
  asm volatile("mma.sync.aligned.m16n8k16.row.col.f32.bf16.bf16.f32 {%0,%1,%2,%3}, {%4,%5,%6,%7}, {%8,%9}, {%0,%1,%2,%3};"
               : "+f"(c[0]), "+f"(c[1]), "+f"(c[2]), "+f"(c[3]) : "r"(a0), "r"(a1), "r"(a2), "r"(a3), "r"(b0), "r"(b1));
}
__device__ __forceinline__ void sts128(uint32_t addr, uint32_t a, uint32_t b, uint32_t c, uint32_t d) {
  asm volatile("st.shared.v4.b32 [%0], {%1,%2,%3,%4};" :: "r"(addr), "r"(a), "r"(b), "r"(c), "r"(d) : "memory");
}
__device__ __forceinline__ uint4 lds128(uint32_t addr) {
  uint4 v; asm volatile("ld.shared.v4.b32 {%0,%1,%2,%3}, [%4];" : "=r"(v.x), "=r"(v.y), "=r"(v.z), "=r"(v.w) : "r"(addr) : "memory"); return v;
}
__device__ __forceinline__ uint32_t lds32(uint32_t addr) {
  uint32_t v; asm volatile("ld.shared.b32 %0, [%1];" : "=r"(v) : "r"(addr) : "memory"); return v;
}
__device__ __forceinline__ float2 lds64f(uint32_t addr) {
  float2 v; asm volatile("ld.shared.v2.f32 {%0,%1}, [%2];" : "=f"(v.x), "=f"(v.y) : "r"(addr) : "memory"); return v;
}
__device__ __forceinline__ void sts64(uint32_t addr, uint32_t a, uint32_t b) {
  asm volatile("st.shared.v2.b32 [%0], {%1, %2};" :: "r"(addr), "r"(a), "r"(b) : "memory");
}
__device__ __forceinline__ float fast_ex2(float x) { float y; asm("ex2.approx.ftz.f32 %0, %1;" : "=f"(y) : "f"(x)); return y; }
__device__ __forceinline__ float fast_rcp(float x) { float y; asm("rcp.approx.ftz.f32 %0, %1;" : "=f"(y) : "f"(x)); return y; }
__device__ __forceinline__ float fast_rsqrt(float x) { float y; asm("rsqrt.approx.ftz.f32 %0, %1;" : "=f"(y) : "f"(x)); return y; }
__device__ __forceinline__ float silu_f(float g) { return g * fast_rcp(1.f + fast_ex2(g * -1.4426950408889634f)); }
__device__ __forceinline__ float swiglu(float h, float v) {
  float t; asm("tanh.approx.f32 %0, %1;" : "=f"(t) : "f"(h));
  const float p = h * v;
  return fmaf(p, t, p);
}

__device__ __forceinline__ void wgmma_m64n128k16_ss(float (&d)[64], uint64_t descA, uint64_t descB, int scaleD) {
  asm volatile("{\n.reg .pred p;\nsetp.ne.b32 p, %66, 0;\n"
    "wgmma.mma_async.sync.aligned.m64n128k16.f32.bf16.bf16 "
    "{%0, %1, %2, %3, %4, %5, %6, %7, %8, %9, %10, %11, %12, %13, %14, %15, "
    "%16, %17, %18, %19, %20, %21, %22, %23, %24, %25, %26, %27, %28, %29, %30, %31, "
    "%32, %33, %34, %35, %36, %37, %38, %39, %40, %41, %42, %43, %44, %45, %46, %47, "
    "%48, %49, %50, %51, %52, %53, %54, %55, %56, %57, %58, %59, %60, %61, %62, %63}, "
    "%64, %65, p, 1, 1, 0, 1;\n}\n"
    : "+f"(d[0]), "+f"(d[1]), "+f"(d[2]), "+f"(d[3]), "+f"(d[4]), "+f"(d[5]), "+f"(d[6]), "+f"(d[7]),
      "+f"(d[8]), "+f"(d[9]), "+f"(d[10]), "+f"(d[11]), "+f"(d[12]), "+f"(d[13]), "+f"(d[14]), "+f"(d[15]),
      "+f"(d[16]), "+f"(d[17]), "+f"(d[18]), "+f"(d[19]), "+f"(d[20]), "+f"(d[21]), "+f"(d[22]), "+f"(d[23]),
      "+f"(d[24]), "+f"(d[25]), "+f"(d[26]), "+f"(d[27]), "+f"(d[28]), "+f"(d[29]), "+f"(d[30]), "+f"(d[31]),
      "+f"(d[32]), "+f"(d[33]), "+f"(d[34]), "+f"(d[35]), "+f"(d[36]), "+f"(d[37]), "+f"(d[38]), "+f"(d[39]),
      "+f"(d[40]), "+f"(d[41]), "+f"(d[42]), "+f"(d[43]), "+f"(d[44]), "+f"(d[45]), "+f"(d[46]), "+f"(d[47]),
      "+f"(d[48]), "+f"(d[49]), "+f"(d[50]), "+f"(d[51]), "+f"(d[52]), "+f"(d[53]), "+f"(d[54]), "+f"(d[55]),
      "+f"(d[56]), "+f"(d[57]), "+f"(d[58]), "+f"(d[59]), "+f"(d[60]), "+f"(d[61]), "+f"(d[62]), "+f"(d[63])
    : "l"(descA), "l"(descB), "r"(scaleD));
}
__device__ __forceinline__ void wgmma_m64n256k16_rs(float (&d)[128], uint32_t a0, uint32_t a1, uint32_t a2, uint32_t a3, uint64_t descB, int scaleD) {
  asm volatile("{\n.reg .pred p;\nsetp.ne.b32 p, %133, 0;\n"
    "wgmma.mma_async.sync.aligned.m64n256k16.f32.bf16.bf16 "
    "{%0, %1, %2, %3, %4, %5, %6, %7, %8, %9, %10, %11, %12, %13, %14, %15, "
    "%16, %17, %18, %19, %20, %21, %22, %23, %24, %25, %26, %27, %28, %29, %30, %31, "
    "%32, %33, %34, %35, %36, %37, %38, %39, %40, %41, %42, %43, %44, %45, %46, %47, "
    "%48, %49, %50, %51, %52, %53, %54, %55, %56, %57, %58, %59, %60, %61, %62, %63, "
    "%64, %65, %66, %67, %68, %69, %70, %71, %72, %73, %74, %75, %76, %77, %78, %79, "
    "%80, %81, %82, %83, %84, %85, %86, %87, %88, %89, %90, %91, %92, %93, %94, %95, "
    "%96, %97, %98, %99, %100, %101, %102, %103, %104, %105, %106, %107, %108, %109, %110, %111, "
    "%112, %113, %114, %115, %116, %117, %118, %119, %120, %121, %122, %123, %124, %125, %126, %127}, "
    "{%128, %129, %130, %131}, %132, p, 1, 1, 1;\n}\n"
    : "+f"(d[0]), "+f"(d[1]), "+f"(d[2]), "+f"(d[3]), "+f"(d[4]), "+f"(d[5]), "+f"(d[6]), "+f"(d[7]),
      "+f"(d[8]), "+f"(d[9]), "+f"(d[10]), "+f"(d[11]), "+f"(d[12]), "+f"(d[13]), "+f"(d[14]), "+f"(d[15]),
      "+f"(d[16]), "+f"(d[17]), "+f"(d[18]), "+f"(d[19]), "+f"(d[20]), "+f"(d[21]), "+f"(d[22]), "+f"(d[23]),
      "+f"(d[24]), "+f"(d[25]), "+f"(d[26]), "+f"(d[27]), "+f"(d[28]), "+f"(d[29]), "+f"(d[30]), "+f"(d[31]),
      "+f"(d[32]), "+f"(d[33]), "+f"(d[34]), "+f"(d[35]), "+f"(d[36]), "+f"(d[37]), "+f"(d[38]), "+f"(d[39]),
      "+f"(d[40]), "+f"(d[41]), "+f"(d[42]), "+f"(d[43]), "+f"(d[44]), "+f"(d[45]), "+f"(d[46]), "+f"(d[47]),
      "+f"(d[48]), "+f"(d[49]), "+f"(d[50]), "+f"(d[51]), "+f"(d[52]), "+f"(d[53]), "+f"(d[54]), "+f"(d[55]),
      "+f"(d[56]), "+f"(d[57]), "+f"(d[58]), "+f"(d[59]), "+f"(d[60]), "+f"(d[61]), "+f"(d[62]), "+f"(d[63]),
      "+f"(d[64]), "+f"(d[65]), "+f"(d[66]), "+f"(d[67]), "+f"(d[68]), "+f"(d[69]), "+f"(d[70]), "+f"(d[71]),
      "+f"(d[72]), "+f"(d[73]), "+f"(d[74]), "+f"(d[75]), "+f"(d[76]), "+f"(d[77]), "+f"(d[78]), "+f"(d[79]),
      "+f"(d[80]), "+f"(d[81]), "+f"(d[82]), "+f"(d[83]), "+f"(d[84]), "+f"(d[85]), "+f"(d[86]), "+f"(d[87]),
      "+f"(d[88]), "+f"(d[89]), "+f"(d[90]), "+f"(d[91]), "+f"(d[92]), "+f"(d[93]), "+f"(d[94]), "+f"(d[95]),
      "+f"(d[96]), "+f"(d[97]), "+f"(d[98]), "+f"(d[99]), "+f"(d[100]), "+f"(d[101]), "+f"(d[102]), "+f"(d[103]),
      "+f"(d[104]), "+f"(d[105]), "+f"(d[106]), "+f"(d[107]), "+f"(d[108]), "+f"(d[109]), "+f"(d[110]), "+f"(d[111]),
      "+f"(d[112]), "+f"(d[113]), "+f"(d[114]), "+f"(d[115]), "+f"(d[116]), "+f"(d[117]), "+f"(d[118]), "+f"(d[119]),
      "+f"(d[120]), "+f"(d[121]), "+f"(d[122]), "+f"(d[123]), "+f"(d[124]), "+f"(d[125]), "+f"(d[126]), "+f"(d[127])
    : "r"(a0), "r"(a1), "r"(a2), "r"(a3), "l"(descB), "r"(scaleD));
}

constexpr uint32_t MSLOT = 32768, QSLOT = 49152;
constexpr int NM = 6;
constexpr uint32_t SM_X0 = 3 * QSLOT;
constexpr uint32_t SM_XR = SM_X0 + 16384;
constexpr uint32_t SM_STG = 196608;
constexpr uint32_t SM_XCH = SM_STG + 16384;
constexpr uint32_t SM_BAR = SM_STG + 32768;
constexpr uint32_t SM_VEC = SM_BAR + 512;
constexpr uint32_t SM_MODT = SM_VEC;
constexpr uint32_t SM_TOTAL = SM_VEC + 2048;
constexpr uint32_t B_X = SM_BAR  , B_EQ = B_X + 64, B_EM = B_EQ + 32, B_STREQ = B_EM + 48, B_HREQ = B_STREQ + 8  , B_LN = B_HREQ + 16,
                   B_FQ = B_LN + 8, B_FM = B_FQ + 32, B_MOD = B_FM + 48  , B_GATE = B_MOD + 64, B_STFREE = B_GATE + 8, B_VEC = B_STFREE + 8  ,
                   B_FLG = B_VEC + 16  , B_H2A = B_FLG + 24, B_HFREE = B_FLG + 96  ,
                   B_RST = B_HFREE + 16, B_F1 = B_RST + 8  , B_STH = B_F1 + 24  , B_END = B_STH + 16;
static_assert(B_END <= SM_VEC, "barriers");
constexpr int NB_WG = 1  , NB_CONS = 3, NB_ORD = 4  ;
#define TUNE(name, value) constexpr int name = value
TUNE(PF_BYTES, 256);
TUNE(X_GAP, 250);
TUNE(AUX_HOLD, 3200);
TUNE(AUX_URG, 4);
TUNE(AUX_SLOW, 84);
TUNE(AUX_GAP, 500);
TUNE(MSEP, 6);
TUNE(ASPLIT, 2);
TUNE(WTAIL, 4);
TUNE(WPRE, 2);
TUNE(DTAIL, 4);

struct Maps {
  CUtensorMap x, out;
  CUtensorMap h64;
  CUtensorMap o, hh;
  CUtensorMap wqk, wvv, wq1, wo, w1, w3, w2;
  CUtensorMap wmod;
#define MAP_H2 o
};

struct Ring { int st; uint32_t ph; int prev; uint32_t dl;
};
__device__ __forceinline__ void ring_next(Ring& r) { if (++r.st == NM) { r.st = 0; r.ph ^= 1; } }

__device__ __forceinline__ void retire_prev(uint32_t rel, bool on) {
  wgmma_commit();
  wgmma_wait<1>();
  if (on) mbar_arrive_e(rel);
}
struct Nop { __device__ __forceinline__ void operator()() const {} };
template <bool REL = true, class F = Nop>
__device__ __forceinline__ void mma_step(float (&acc)[64], uint32_t a, uint32_t b, bool first, uint32_t rel, F urgent = F()) {
  const uint32_t alo = (a >> 4) + (1u << 16), blo = (b >> 4) + (512u << 16);
  wgmma_fence();
  #pragma unroll
  for (int k = 0; k < 4; k++) {
    wgmma_m64n128k16_ss(acc, desc_from_lo(alo + k * 2), desc_from_lo(blo + k * 128), k > 0 || !first);
    if (k == 0) { retire_prev(rel, REL); urgent(); }
  }
  wgmma_commit();
}
template <bool REL>
__device__ __forceinline__ void mma_solo(float (&acc)[64], uint32_t a, uint32_t b, bool first, uint32_t rel) {
  const uint32_t alo = (a >> 4) + (1u << 16), blo = (b >> 4) + (512u << 16);
  wgmma_fence();
  #pragma unroll
  for (int k = 0; k < 4; k++) wgmma_m64n128k16_ss(acc, desc_from_lo(alo + k * 2), desc_from_lo(blo + k * 128), k > 0 || !first);
  if (REL) retire_prev(rel, true); else wgmma_commit();
}
__device__ __forceinline__ uint32_t m_wait(uint32_t sbase, const Ring& r) {
  mbar_wait(sbase + B_FM + 8 * r.st, r.ph, r.dl);
  return sbase + r.st * MSLOT;
}
__device__ __forceinline__ uint32_t m_prev(uint32_t sbase, const Ring& r) { return sbase + B_EM + 8 * r.prev; }
__device__ __forceinline__ void m_next(Ring& r) {
  r.prev = r.st; ring_next(r);
}
__device__ __forceinline__ void m_step(float (&acc)[64], uint32_t sbase, uint32_t wgoff, Ring& r, bool first = false) {
  const uint32_t slot = m_wait(sbase, r);
  mma_step(acc, slot + wgoff, slot + 16384, first, m_prev(sbase, r));
  m_next(r);
}

struct LnRow { uint32_t rs[2], nb[2]; };
__device__ __forceinline__ void ln_row(LnRow& l, int h, float mean, float rstd) {
  l.rs[h] = pack_bf16(rstd, rstd);
  const float nb = -mean * bf_lo(l.rs[h]);
  l.nb[h] = pack_bf16(nb, nb);
}
__device__ __forceinline__ uint32_t ln_mod(uint32_t x, const LnRow& l, int h, uint32_t c1, uint32_t s) {
  return fma_bf2(fma_bf2(x, l.rs[h], l.nb[h]), c1, s);
}

__device__ __forceinline__ uint32_t q_wait(int u, uint32_t sbase, uint32_t dl) {
  mbar_wait(sbase + B_FQ + 8 * (u & 3), (u >> 2) & 1, dl);
  return sbase + (u & 3) * QSLOT;
}
__device__ __forceinline__ uint32_t q_empty(int u, uint32_t sbase) { return sbase + B_EQ + 8 * (u & 3); }
struct Frag4 { uint32_t o[4]; };
__device__ __forceinline__ void q_load(uint32_t (&A)[16], uint4 (&p)[4], int kk, uint32_t tile, const Frag4& f, uint32_t t) {
  ldmatrix_x4(tile + f.o[kk], A[4 * kk], A[4 * kk + 1], A[4 * kk + 2], A[4 * kk + 3]);
  p[kk] = lds128(t + kk * 64);
}
__device__ __forceinline__ void q_norm(uint32_t (&A)[16], const uint4 (&p)[4], int kk, const LnRow& l) {
  A[4 * kk + 0] = ln_mod(A[4 * kk + 0], l, 0, p[kk].x, p[kk].z); A[4 * kk + 1] = ln_mod(A[4 * kk + 1], l, 1, p[kk].x, p[kk].z);
  A[4 * kk + 2] = ln_mod(A[4 * kk + 2], l, 0, p[kk].y, p[kk].w); A[4 * kk + 3] = ln_mod(A[4 * kk + 3], l, 1, p[kk].y, p[kk].w);
}
template <bool NEXT>
__device__ __forceinline__ void q_step_rs(float (&acc)[128], uint32_t (&A)[16], uint32_t (&N)[16], uint4 (&p)[4], int u, uint32_t sbase,
                                          const Frag4& f, uint32_t tab, const LnRow& l, uint32_t rot, bool keep, bool first, uint32_t dl, int wg, int zero) {
  const uint32_t slot = first ? sbase : q_wait(u, sbase, dl);
  const uint32_t blo = ((slot + 16384) >> 4) + (512u << 16) + rot * 128 + (zero << (u >> 2)), t = tab + ((u + 1) & 7) * 256;
  #pragma unroll
  for (int kk = 0; kk < 4; kk++) q_norm(A, p, kk, l);
  #pragma unroll
  for (int i = 0; i < 16; i++) asm volatile("" : "+r"(A[i]));
  if (!first) sched_fence(zero);
  if (first) {
    mbar_wait(sbase + B_GATE, 0, dl);
    PROF(6, threadIdx.x == 0);
  }
  if (!(first && wg == 0)) bar_sync(NB_ORD + wg, 256);
  wgmma_fence();
  #pragma unroll
  for (int kk = 0; kk < 4; kk++) {
    wgmma_m64n256k16_rs(acc, A[4 * kk], A[4 * kk + 1], A[4 * kk + 2], A[4 * kk + 3], desc_from_lo(blo ^ (kk * 128)), kk > 0 || !first);
    if (kk == 0) retire_prev(q_empty(u - 1, sbase), !first);
    if (NEXT && kk == 1) {
      if ((u & 1) && u < MSEP) mbar_wait(sbase + B_MOD + 4 * (u + 1), 0, dl);
      #pragma unroll
      for (int q = 0; q < 4; q++) q_load(N, p, q, slot, f, t);
    }
    if (kk == 3 && (NEXT || wg == 0)) bar_arrive(NB_ORD + (wg ^ 1), 256);
    if (kk == 1) stmatrix_x4_if(sbase + SM_STG + (u >> 3) * 16384 + (f.o[0] ^ (((u >> 1 & 3) ^ rot) << 5)), A[0], A[1], A[2], A[3], keep);
  }
  wgmma_commit();
}

typedef uint32_t Frag8[8];
template <int N> __device__ __forceinline__ void pack_half(Frag8& f, const float (&acc)[N], int off, int half) {
  #pragma unroll
  for (int e = 0; e < 8; e++) { f[e] = pack_bf16(acc[off + 4 * e + 2 * half], acc[off + 4 * e + 2 * half + 1]); asm volatile("" : "+r"(f[e])); }
}
__device__ __forceinline__ void transpose8(Frag8& f) {
  #pragma unroll
  for (int e = 0; e < 8; e++) f[e] = movmatrix_t(f[e]);
}
__device__ __forceinline__ void attn_send(const Frag8& f, int kv, uint32_t xch, int warp, uint4* halo_out, bool has_next) {
  if (warp == 3) {
    st_nonzero_v4(halo_out + kv * 64, f[0], f[1], f[2], f[3], has_next); st_nonzero_v4(halo_out + kv * 64 + 32, f[4], f[5], f[6], f[7], has_next);
  } else {
    sts128(xch + 2048 + kv * 1024, f[0], f[1], f[2], f[3]); sts128(xch + 2048 + kv * 1024 + 512, f[4], f[5], f[6], f[7]);
  }
}
template <int N>
__device__ __forceinline__ void attn_recv(uint4* p, int first, uint32_t xch, int wg, int warp, const uint4* halo_in, bool has_prev) {
  bar_sync(NB_WG + wg, 128);
  #pragma unroll
  for (int e = 0; e < N; e++)
    asm volatile("{\n.reg .pred p, q;\nsetp.ne.b32 p, %6, 0;\nsetp.ne.b32 q, %7, 0;\n"
                 "mov.b32 %0, 0;\nmov.b32 %1, 0;\nmov.b32 %2, 0;\nmov.b32 %3, 0;\n"
                 "@p ld.shared.v4.b32 {%0,%1,%2,%3}, [%4];\n@q ld.relaxed.gpu.global.v4.u32 {%0,%1,%2,%3}, [%5];\n}"
                 : "=&r"(p[e].x), "=&r"(p[e].y), "=&r"(p[e].z), "=&r"(p[e].w)
                 : "r"(xch + (first + e) * 512), "l"(halo_in + (first + e) * 32), "r"((int)(warp > 0)), "r"((int)(warp == 0 && has_prev)) : "memory");
}
template <int N>
__device__ __forceinline__ void attn_check(uint4* p, int first, bool remote, const uint4* halo_in, uint32_t dl) {
  if (remote) {
    while (true) {
      uint32_t m = ~0u;
      #pragma unroll
      for (int e = 0; e < N; e++) m = min(m, min4(p[e]));
      if (poll_done(m != 0, dl)) break;
      #pragma unroll
      for (int e = 0; e < N; e++) p[e] = ld_rlx_v4(halo_in + (first + e) * 32);
    }
  }
}
template <int SPLIT, class F>
__device__ __forceinline__ void attn_core(const Frag8& qA, const Frag8& qB, const Frag8& kA, const Frag8& kB, const Frag8& vA, const Frag8& vB,
                                          const uint4* kP, const uint4* vP, bool noprev, int lane, float (&o)[2][5][4], F late) {
  const int g = lane >> 2, qd = lane & 3;
  const bool s0 = 2 * qd > g, s1 = 2 * qd + 1 > g;
  const uint32_t msk = (s0 ? 0xFFFFu : 0u) | (s1 ? 0xFFFF0000u : 0u);
  float s[2][3][4];
  uint32_t pr[2][2];
  auto scores = [&](int h, int nb) {
    s[h][nb][0] = s[h][nb][1] = s[h][nb][2] = s[h][nb][3] = 0.f;
    #pragma unroll
    for (int kk = 0; kk < 2; kk++) {
      const int e = 4 * h + 2 * kk;
      mma16(s[h][nb], qA[e], qB[e], qA[e + 1], qB[e + 1], nb == 1 ? kA[e] : nb == 2 ? kB[e] : kk ? kP[h].z : kP[h].x,
            nb == 1 ? kA[e + 1] : nb == 2 ? kB[e + 1] : kk ? kP[h].w : kP[h].y);
    }
  };
  auto rows = [&](int h, int y) {
    constexpr float SC = 0.17677669529663687f * 1.4426950408889634f;
    const float l0 = s0 ? (y == 0 && noprev ? -INFINITY : s[h][y][2 * y]) : s[h][y + 1][2 * y];
    const float l1 = s1 ? (y == 0 && noprev ? -INFINITY : s[h][y][2 * y + 1]) : s[h][y + 1][2 * y + 1];
    float m = fmaxf(l0, l1);
    m = fmaxf(m, __shfl_xor_sync(0xffffffffu, m, 1));
    m = fmaxf(m, __shfl_xor_sync(0xffffffffu, m, 2));
    const uint32_t p = pr[h][y] = pack_bf16(fast_ex2((l0 - m) * SC), fast_ex2((l1 - m) * SC));
    #pragma unroll
    for (int m2 = 0; m2 < 2; m2++) {
      const int e = 4 * h + 2 * m2;
      float (&d)[4] = o[h][2 * m2 + y];
      d[0] = d[1] = d[2] = d[3] = 0.f;
      if (y == 0) mma16(d, m2 ? vP[h].z : vP[h].x, m2 ? vP[h].w : vP[h].y, vA[e], vA[e + 1], p & msk, p & ~msk);
      else mma16(d, vA[e], vA[e + 1], vB[e], vB[e + 1], p & msk, p & ~msk);
    }
  };
  #pragma unroll
  for (int h = 0; h < 2; h++) { scores(h, 1); scores(h, 2); if (SPLIT == 0) scores(h, 0); }
  if (SPLIT == 2) { rows(0, 1); rows(1, 1); }
  if (SPLIT) { late(); scores(0, 0); scores(1, 0); }
  #pragma unroll
  for (int h = 0; h < 2; h++) {
    if (SPLIT < 2) rows(h, 1);
    rows(h, 0);
    o[h][4][0] = o[h][4][1] = o[h][4][2] = o[h][4][3] = 0.f;
    mma16(o[h][4], 0x3F803F80u, 0u, 0u, 0x3F803F80u, pr[h][0], pr[h][1]);
  }
}
__device__ __forceinline__ void attn_store(const float (&o)[2][5][4], int h, uint32_t sbase, const Frag4& f) {
  float r[4];
  #pragma unroll
  for (int e = 0; e < 4; e++) r[e] = fast_rcp(o[h][4][e]);
  #pragma unroll
  for (int m = 0; m < 2; m++) {
    const float (&lo)[4] = o[h][2 * m], (&hi)[4] = o[h][2 * m + 1];
    stmatrix_x4_t(sbase + SM_STG + f.o[2 * h + m], pack_bf16(lo[0] * r[0], lo[1] * r[1]), pack_bf16(hi[0] * r[2], hi[1] * r[3]),
                  pack_bf16(lo[2] * r[0], lo[3] * r[1]), pack_bf16(hi[2] * r[2], hi[3] * r[3]));
  }
}

__device__ __forceinline__ void request_store(uint32_t bar) {
  fence_proxy_async_smem();
  mbar_arrive_e(bar);
}

__device__ __forceinline__ void g_quad(float (&a0)[64], float (&a1)[64], uint32_t rel2, uint32_t sbase, uint32_t wgoff, Ring& r) {
  const uint32_t x = m_wait(sbase, r);
  mma_step(a0, x + wgoff, x + 16384, false, m_prev(sbase, r), [&] { if (rel2) mbar_arrive_e(rel2); });
  m_next(r);
  const uint32_t xe = m_prev(sbase, r), y = m_wait(sbase, r);
  mma_step<false>(a1, x + wgoff, y, false, 0);
  m_next(r);
  const uint32_t z = m_wait(sbase, r);
  mma_step(a1, z + wgoff, y + 16384, false, xe);
  mma_step(a0, z + wgoff, z + 16384, false, m_prev(sbase, r));
  m_next(r);
}
template <int T>
__device__ __forceinline__ void g_piece(float (&prv)[64], int jj, int use, uint32_t sbase, const Frag4& f, uint32_t dl) {
  if (jj == 0) { mbar_wait(sbase + B_HFREE + 8 * T, use & 1, dl); fence_regs(prv); PROF(33 + 2 * use + T, threadIdx.x == 0); }
  uint32_t p[4];
  #pragma unroll
  for (int e = 0; e < 4; e++) {
    const int i = jj * 8 + e * 2;
    p[e] = pack_bf16(swiglu(prv[i], prv[i + 32]), swiglu(prv[i + 1], prv[i + 33]));
  }
  stmatrix_x4(sbase + SM_STG + T * 16384 + f.o[jj], p[0], p[1], p[2], p[3]);
  if (jj == 3) request_store(sbase + B_HREQ + 8 * T);
}
template <bool REL2, bool Q, class F>
__device__ __forceinline__ uint32_t g_ppqq(float (&p)[64], float (&q)[64], bool firstq, uint32_t rel2, uint32_t sbase, uint32_t wgoff, Ring& r, F after) {
  const uint32_t x = m_wait(sbase, r);
  mma_step(p, x + wgoff, x + 16384, false, m_prev(sbase, r), [&] { if (REL2) mbar_arrive_e(rel2); });
  m_next(r);
  after(0);
  const uint32_t xe = m_prev(sbase, r), z = m_wait(sbase, r);
  mma_step<!Q>(p, z + wgoff, z + 16384, false, xe);
  m_next(r);
  after(1);
  if (!Q) return 0;
  const uint32_t ze = m_prev(sbase, r), y = m_wait(sbase, r);
  mma_step<false>(q, x + wgoff, y, firstq, 0);
  after(2);
  mma_step(q, z + wgoff, y + 16384, false, xe);
  m_next(r);
  after(3);
  return ze;
}

__device__ __forceinline__ uint32_t bad2(uint32_t a, uint32_t b, unsigned par) {
  uint32_t d; asm("lop3.b32 %0, %1, %2, %3, 0x7E;" : "=r"(d) : "r"(a), "r"(b), "r"(par)); return d;
}
__device__ __forceinline__ uint32_t bad4(const uint4& v, unsigned par) { return bad2(v.x, v.y, par) | bad2(v.z, v.w, par); }
__device__ __forceinline__ uint32_t hi_halves(uint32_t lo, uint32_t hi) { return __byte_perm(lo, hi, 0x7632); }

__device__ __forceinline__ void gather_table(const float* src, uint32_t dst, uint32_t bar, unsigned par, uint32_t dl) {
  asm volatile("{\n.reg .pred p, e;\n.reg .b32 s<4>, c<4>, t<4>, w<4>;\n"
               "elect.sync _|e, 0xffffffff;\n"
               "LAB_POLL:\n"
               "ld.relaxed.gpu.global.v4.u32 {s0, s1, s2, s3}, [%0];\n"
               "ld.relaxed.gpu.global.v4.u32 {c0, c1, c2, c3}, [%0 + 4096];\n"
               "prmt.b32 w0, c0, c1, 0x7632;\nprmt.b32 w1, c2, c3, 0x7632;\nprmt.b32 w2, s0, s1, 0x7632;\nprmt.b32 w3, s2, s3, 0x7632;\n"
               "st.shared.v4.b32 [%1], {w0, w1, w2, w3};\n"
               "lop3.b32 t0, s0, s1, %3, 0x7E;\nlop3.b32 t1, s2, s3, %3, 0x7E;\nlop3.b32 t2, c0, c1, %3, 0x7E;\nlop3.b32 t3, c2, c3, %3, 0x7E;\n"
               "lop3.b32 t0, t0, t1, 1, 0xA8;\nlop3.b32 t2, t2, t3, 1, 0xA8;\n"
               "or.b32 t0, t0, t2;\n"
               "setp.eq.u32 p, t0, 0;\n"
               "vote.sync.all.pred p, p, 0xffffffff;\n"
               "@p bra.uni LAB_OK;\n"
               "mov.u32 t0, %%clock;\nsub.s32 t0, t0, %4;\nsetp.lt.s32 p, t0, 0;\n"
               "vote.sync.all.pred p, p, 0xffffffff;\n"
               "@p bra.uni LAB_POLL;\n"
               "LAB_OK:\n"
               "@e mbarrier.arrive.shared::cta.b64 _, [%2];\n}"
               :: "l"(src), "r"(dst), "r"(bar), "r"(par), "r"(dl) : "memory");
}

__device__ __forceinline__ int aux_col(int a, int u) { return u < 8 ? (a & 1) * 1024 + (2 * u + (a >> 1)) * 64 : 2048 + ((u - 8) * 4 + a) * 64; }
constexpr int NA = 7;
constexpr uint32_t A_FULL = SM_BAR, A_EMPTY = SM_BAR + 64, A_SUM = SM_BAR + 128, A_FREE = SM_BAR + 136, SM_RED = SM_VEC;
__device__ __forceinline__ void aux_role(const Maps& maps, const bf16* __restrict__ cvec, Mail* mail0, int zero, int a, uint32_t sbase, int wid) {
  const int tid = threadIdx.x, lane = tid & 31;
  const uint32_t dl = (clock32() + 800000000u) | 1;
  int st = 0; uint32_t ph = 0;
  if (wid == 8) {
    prefetch_tmap(&maps.wmod);
    #pragma unroll
    for (int i = 0; i < 18; i++) mbar_init_e(sbase + A_FULL + 8 * i, i < 8 ? 1 : i < 17 ? 8 : 2);
    fence_proxy_async_smem();
    bar_arrive(0, 352);
    PROF(39, lane == 0);
    #pragma unroll
    for (int i = 0; i < NA; i++) {
      mbar_expect_tx_e(sbase + A_FULL + 8 * i, 32768);
      tma_load_2d(sbase + i * MSLOT, &maps.wmod, sbase + A_FULL + 8 * i, aux_col(a, i >> 2), (i & 3) * 256);
    }
    PROF(40, lane == 0);
    #pragma unroll 1
    for (int i = NA; i < 96; i++) {
      if (i >= AUX_SLOW) wait_until(clock32() + AUX_GAP);
      if (i == 8) wait_until(dl - 800000000u + AUX_HOLD);
      mbar_wait(sbase + A_EMPTY + 8 * st, ph, dl);
      mbar_expect_tx_e(sbase + A_FULL + 8 * st, 32768);
      tma_load_2d<true>(sbase + st * MSLOT, &maps.wmod, sbase + A_FULL + 8 * st, aux_col(a, i >> 2), (i & 3) * 256);
      if (++st == NA) { st = 0; ph ^= 1; }
    }
  } else if (wid < 8) {
    const int g = lane >> 2, qd = lane & 3;
    uint32_t sc[16];
    const uint2 c = *reinterpret_cast<const uint2*>(cvec + tid * 4);
    sts64(sbase + SM_RED + tid * 8, pack_bf16(silu_f(bf_lo(c.x)), silu_f(bf_hi(c.x))), pack_bf16(silu_f(bf_lo(c.y)), silu_f(bf_hi(c.y))));
    bar_sync(0, 352);
    #pragma unroll
    for (int i = 0; i < 16; i++) sc[i] = lds32(sbase + SM_RED + ((i >> 2) * 256 + wid * 32 + (i & 3) * 8 + qd * 2) * 2);
    bar_sync(NB_CONS, 256);
    PROF(38, tid == 0);
    const uint32_t aoff = (wid * 32 + (lane & 7) + (lane >> 4) * 8) * 128 + ((((lane >> 3) & 1) ^ (lane & 7)) << 4);
    uint32_t w[2][8][4];
    auto fetch = [&](uint32_t (&f)[8][4]) {
      mbar_wait(sbase + A_FULL + 8 * st, ph, dl);
      #pragma unroll
      for (int e = 0; e < 8; e++) ldmatrix_x4_t((sbase + st * MSLOT + aoff + (e >> 2) * 2048) ^ ((e & 3) << 5), f[e]);
      if (++st == NA) { st = 0; ph ^= 1; }
    };
    #pragma unroll 1
    for (int u = 0; u < 24; u++) {
      float acc[4][4];
      #pragma unroll
      for (int m = 0; m < 4; m++) acc[m][0] = acc[m][1] = acc[m][2] = acc[m][3] = 0.f;
      fetch(w[0]);
      #pragma unroll
      for (int q = 0; q < 4; q++) {
        PROF(30 + (u & 1) * 4 + q, u < 2 && tid == 0);
        const uint32_t rel = sbase + A_EMPTY + 8 * (st == 0 ? NA - 1 : st - 1);
        if (q < 3) fetch(w[(q + 1) & 1]);
        uint32_t dep = 0;
        #pragma unroll
        for (int e = 0; e < 8; e++) dep |= w[q & 1][e][0];
        mbar_arrive_e(rel + (dep & zero));
        if (q == 1) mbar_wait(sbase + A_FREE, (u & 1) ^ 1, dl);
        #pragma unroll
        for (int e = 0; e < 8; e++) {
          const uint32_t (&f)[4] = w[q & 1][e];
          mma16(acc[e & 3], f[0], f[1], f[2], f[3], sc[4 * q + 2 * (e >> 2)], sc[4 * q + 2 * (e >> 2) + 1]);
        }
      }
      const float v0 = qd & 2 ? (qd & 1 ? acc[3][0] : acc[2][0]) : (qd & 1 ? acc[1][0] : acc[0][0]);
      const float v1 = qd & 2 ? (qd & 1 ? acc[3][2] : acc[2][2]) : (qd & 1 ? acc[1][2] : acc[0][2]);
      sts64(sbase + SM_RED + wid * 256 + (qd * 8 + g) * 8, __float_as_uint(v0), __float_as_uint(v1));
      mbar_arrive_e(sbase + A_SUM);
      if (u < AUX_URG) mbar_wait(sbase + A_FREE, u & 1, dl);
    }
  } else if (wid < 11) {
    float* const mail = &mail0->mod[(wid - 9) * 4 * 6 * D_ + 2 * lane];
    unsigned par = ld_relaxed(&mail0->flags[FL_EPOCH + (lane >> 5)]);
    bar_sync(0, 352);
    par = (par + 1) & 1;
    #pragma unroll 1
    for (int u = 0; u < 24; u++) {
      const int col = aux_col(a, u);
      const float add = (col >> 10) == 1 || (col >> 10) == 4 ? 1.f : 0.f;
      const float mul = col < 3 * D_ ? 1.f : col < 5 * D_ ? 0.5f : 2.f;
      mbar_wait(sbase + A_SUM, u & 1, dl);
      float2 v[8];
      #pragma unroll
      for (int w = 0; w < 8; w++) v[w] = lds64f(sbase + SM_RED + w * 256 + lane * 8);
      const float t0 = ((v[0].x + v[1].x) + (v[2].x + v[3].x)) + ((v[4].x + v[5].x) + (v[6].x + v[7].x));
      const float t1 = ((v[0].y + v[1].y) + (v[2].y + v[3].y)) + ((v[4].y + v[5].y) + (v[6].y + v[7].y));
      mbar_arrive_e(sbase + A_FREE + (__float_as_uint(t0 + t1) & zero));
      const uint32_t w = pack_bf16((add + bf16_round(t0)) * mul, (add + bf16_round(t1)) * mul), o = __shfl_xor_sync(0xffffffffu, w, 1);
      const uint32_t m0 = (lane & 1) ? (o & 0xFFFF0000u) : (w << 16), m1 = (lane & 1) ? (w & 0xFFFF0000u) : (o << 16);
      #pragma unroll
      for (int c = 0; c < 4; c++) st_rlx_v2(mail + c * 6 * D_ + col, m0 | par, m1 | par, true);
      PROF(1 + u, tid == 288);
    }
    const int t = a * 64 + tid - 288;
    #pragma unroll 1
    for (int i = t; i < 16 * 16 * 256; i += 256) mail0->halo[par ^ 1][i] = make_uint4(0, 0, 0, 0);
  }
}

template <int MODE>
__global__ void __launch_bounds__(384, 1)
fused_block_kernel(const bf16* __restrict__ x, const bf16* __restrict__ cvec, const bf16* __restrict__ wmod, Mail* mail0, int zero,
                   const __grid_constant__ Maps maps) {
  extern __shared__ __align__(1024) uint8_t smem_raw[];
  const uint32_t sbase = smem_u32(smem_raw);
  const int tid = threadIdx.x, lane = tid & 31;
  PROFN(0, tid == 0);
  const int wid = __shfl_sync(0xffffffffu, tid >> 5, 0);
  const int b = cta_role<MODE>();
  if (b >= NCTA) { aux_role(maps, cvec, mail0, zero, b - NCTA, sbase, wid); return; }
  const int jg = b >> 6, mb = jg ? 31 - (b >> 2) : (b >> 2), j = 4 * jg + (b & 3);
  const uint32_t dl = (clock32() + 800000000u) | 1;
  unsigned* const flags = &mail0->flags[mb * 32];
  const int row0 = mb * 128;

  if (wid >= 8) {
    if (wid == 8) {
      #pragma unroll
      for (int i = 0; i < 8; i++) mbar_init_e(sbase + B_X + 8 * i, 1);
      fence_proxy_async_smem();
      mbar_expect_tx_e(sbase + B_X, 4096);
      bulk_load(sbase + SM_XR, x + (size_t)(row0 + j * 16) * D_, 4096, sbase + B_X);
    } else if (wid == 11) {
      #pragma unroll
      for (int i = 0; i < 12; i++) prefetch_tmap(&maps.x + i);
    } else if (wid == 9) {
      #pragma unroll
      for (uint32_t bar = B_EQ; bar < B_FM; bar += 8) mbar_init_e(sbase + bar, bar < B_FQ ? 8 : bar == B_FQ + 8 || bar == B_FQ + 24 ? 2 : 1);
      fence_proxy_async_smem();
    } else {
      #pragma unroll
      for (uint32_t bar = B_FM; bar < B_END; bar += 8) mbar_init_e(sbase + bar, bar < B_STH ? 1 : 4);
      fence_proxy_async_smem();
    }
    bar_sync(0, 384);
    reg_dealloc<40>();
    PROF(92, tid == 256);
    if (wid == 8) {
      uint32_t tnext = clock32();
      #pragma unroll 1
      for (int q = 1; q < 8; q++) {
        wait_until(tnext);
        mbar_expect_tx_e(sbase + B_X + 8 * q, 4096);
        bulk_load(sbase + SM_XR + q * 4096, x + (size_t)(row0 + j * 16 + 2 * q) * D_, 4096, sbase + B_X + 8 * q);
        tnext += X_GAP;
      }
      #pragma unroll 1
      for (int u = 0; u < 16; u++) {
        const int st = u & 3;
        if (u == 1) mbar_wait(sbase + B_X + 56, 0, dl);
        if (u == 2) { mbar_wait(sbase + B_GATE, 0, dl); PROFN(60, lane == 0); }
        if (u == 3) mbar_wait(sbase + B_EQ, 0, dl);
        mbar_wait(sbase + B_EQ + 8 * st, ((u >> 2) & 1) ^ 1, dl);
        const uint32_t slot = sbase + st * QSLOT, fb = sbase + B_FQ + 8 * st;
        mbar_expect_tx_e(fb, u == 0 ? 65536 : u == 15 ? 32768 : 49152);
        if ((u & 1) && (u < MSEP || u == 15)) mbar_arrive_e(fb);
        if (u == 0) tma_load_3d(sbase + SM_X0, &maps.x, fb, 0, mb * 64, 0);
        tma_load_4d<true>(slot + 16384, &maps.wqk, fb, 0, u * 64, j, 0);
        tma_load_4d<true>(slot + 32768, &maps.wvv, fb, 0, u * 64, j, 0);
        if (u < 15) tma_load_3d(slot, &maps.x, fb, u * 64 + 64, mb * 64, 0);
      }
      const unsigned e1 = 1 + ld_relaxed(flags + FO_EPOCH);
      Ring r{0, 1, 0, dl};
      uint32_t slot, fb;
      auto acquire = [&](uint32_t bytes) {
        mbar_wait(sbase + B_EM + 8 * r.st, r.ph, dl);
        slot = sbase + r.st * MSLOT; fb = sbase + B_FM + 8 * r.st;
        mbar_expect_tx_e(fb, bytes);
        ring_next(r);
      };
      #pragma unroll 1
      for (int kt = 0; kt < 16; kt++) {
        if (kt < 5) mbar_wait(sbase + B_EQ + 8 * (kt - (kt >= 2)), 1, dl);
        if ((kt & 7) == 0) { PROF(46, lane == 0 && kt == 8); mbar_wait(sbase + B_FLG + kt, 0, dl); PROF(47, lane == 0 && kt == 8); }
        acquire(32768);
        tma_load_4d<true>(slot + 16384, &maps.wq1, fb, (j + 8) * 64, (kt & 1) * 64 + (kt & 6) * 8, (kt >> 3) * 4, 0);
        tma_load_3d(slot, &maps.hh, fb, (kt & 7) * 64, row0, kt >> 3);
      }
      PROF(82, lane == 0);
      mbar_wait(sbase + B_FLG + 16, 0, dl);
      PROF(83, lane == 0);
      #pragma unroll 1
      for (int kt = 0; kt < 8; kt++) {
        if (kt == 4) {
          acquire(32768);
          tma_load_3d(slot, &maps.x, fb, j * 128, mb * 64, 0);
          tma_load_3d(slot + 16384, &maps.x, fb, j * 128 + 64, mb * 64, 0);
        }
        acquire(32768);
        tma_load_3d<true>(slot + 16384, &maps.wo, fb, 0, kt * 64, 2 * j);
        tma_load_2d(slot, &maps.o, fb, kt * 64, row0);
      }
      acquire(16384);
      tma_load_3d<true>(slot + 16384, &maps.wo, fb, 0, (8 + j) * 64, 2 * j);
      const uint32_t oth = (0x2107654u + (0x1110000u << (4 * (j & 3)) & 0x1110000u)) ^ ((j & 4) ? 0x4444444u : 0u);
      auto deferred = [&](const CUtensorMap* map, const unsigned* flag, Ring ra, int n, int col0, int step) {
        uint32_t dst = sbase + ra.st * MSLOT, bar = sbase + B_FM + 8 * ra.st, col = col0 + (~j & 4) * step;
        asm volatile("" : "+r"(dst), "+r"(bar), "+r"(col));
        wait_flag(flag, e1 * NCTA, dl);
        tma_load_2d(dst, map, bar, col, row0);
        #pragma unroll 1
        for (int i = 1; i < n; i++) { ring_next(ra); tma_load_2d(sbase + ra.st * MSLOT, map, sbase + B_FM + 8 * ra.st, col + i * step, row0); }
      };
      {
        const Ring ra = r;
        #pragma unroll 1
        for (int i = 0; i < 7; i++) {
          const int kt = 8 + (oth >> (4 * i) & 7);
          acquire(32768);
          tma_load_3d<true>(slot + 16384, &maps.wo, fb, 0, kt * 64, 2 * j);
          if (i == WPRE - 1) { deferred(&maps.o, &mail0->flags[FL_O], ra, WPRE, 512, 64); PROFN(61, lane == 0); }
          if (i >= WPRE) tma_load_2d(slot, &maps.o, fb, kt * 64, row0);
        }
      }
      uint64_t ord = (uint64_t)(2 * oth) | (uint64_t)(2 * oth + 0x1111111u) << 28;
      auto load_b = [&](uint32_t dst, int col, int kt) {
        tma_load_2d<true>(dst, &maps.w1, fb, col, kt * 64);
        tma_load_2d<true>(dst + 8192, &maps.w3, fb, col, kt * 64);
      };
      Ring ra = r;
      #pragma unroll 1
      for (int i = -2; i < 5; i++) {
        const int kt = i < 0 ? 2 * j + i + 2 : 2 * ((~j & 4) + min(i, 3));
        if (i == 0) ra = r;
        if (i == 4) { deferred(&maps.h64, &mail0->flags[FL_H2], ra, 3, 0, 128); PROF(89, lane == 0); }
        acquire(i >= 0 && i < 3 ? 24576 : 32768);
        load_b(slot + 16384, i < 0 || i == 3 ? (8 + j) * 64 : j * 64, kt);
        if (i < 0 || i == 3) load_b(slot, i < 0 ? j * 64 : (8 + j) * 64, i < 0 ? kt : kt - 2);
      }
      #pragma unroll
      for (int i = 0; i < 3; i++) mbar_expect_tx_e(sbase + B_F1 + 8 * i, 8192);
      wait_flag(&mail0->flags[FL_H2 + 1], e1 * NCTA, dl);
      #pragma unroll 1
      for (int i = 0; i < 3; i++) { tma_load_2d(sbase + ra.st * MSLOT + 8192, &maps.h64, sbase + B_F1 + 8 * i, ((~j & 4) + i) * 128, row0 + 64); ring_next(ra); }
      tma_load_2d(slot, &maps.MAP_H2, fb, ((~j & 4) + 3) * 128, row0);
      PROFN(62, lane == 0);
      mbar_arrive_e(sbase + B_H2A);
      #pragma unroll 1
      for (int q = 2; q < 31; q++) {
        const int pr = q >> 3, w = q & 7, col = (16 * pr + j) * 64 + (w == 7 ? 512 : 0), y = pr == 3 ? 0 : w == 0 || w >= 6 ? 2 : 1;
        if (q == 7) ord = (j & 4) ? 0xFEDCBA9875316420ull : 0x76543210FDB9ECA8ull;
        const uint32_t kk = (uint32_t)(ord >> (w == 7 ? 0 : 8 * w + (pr == 0 ? 0 : 8)));
        const int k0 = kk & 15, k1 = kk >> 4 & 15;
        #pragma unroll
        for (int t = 1; t <= 2; t++) {
          if (t == 2 && q == 3) mbar_wait(sbase + B_FLG + 32, 0, dl);
          acquire(32768);
          load_b(slot + 16384, col, t == 1 ? k0 : k1);
          tma_load_2d(slot, &maps.MAP_H2, fb, (t == 1 ? k0 : k1) * 64, row0);
          if (t == y) {
            acquire(32768);
            load_b(slot, col + 512, k0);
            load_b(slot + 16384, col + 512, k1);
          }
        }
      }
      #pragma unroll 1
      for (int kt = 0; kt < 56; kt++) {
        if ((kt & 7) == 0) mbar_wait(sbase + B_FLG + 40 + kt, 0, dl);
        acquire(32768);
        tma_load_3d(slot + 16384, &maps.w2, fb, 0, kt * 64, 2 * j);
        tma_load_3d(slot, &maps.hh, fb, (kt & 7) * 64, row0, kt >> 3);
      }
    } else {
      const unsigned e1 = 1 + ld_relaxed(wid == 9 ? flags + FO_EPOCH : &mail0->flags[FL_EPOCH]), par = e1 & 1;
      auto publish_h2a = [&](int w) {
        mbar_wait(sbase + B_STH + 8 * w, 0, dl);
        tma_store_2d(&maps.h64, sbase + SM_STG + w * 8192, j * 128, row0 + w * 64);
        bulk_commit();
        bulk_wait0();
        red_add_e(&mail0->flags[FL_H2 + w], 1);
        PROF(84 + 4 * w, lane == 0);
      };
      if (wid == 9) {
        #pragma unroll 1
        for (int n = 0; n < 12; n++) {
          if (n == 4) {
            publish_h2a(0);
            mbar_wait(sbase + B_H2A, 0, dl);
          }
          if (n == 3) mbar_wait(sbase + B_RST, 0, dl);
          const int ht = (n - 5) & 1;
          if (n >= 1 && n <= 4) mbar_wait(sbase + B_STREQ, n & 1, dl);
          else mbar_sleep(n == 0 ? sbase + B_STREQ : sbase + B_HREQ + 8 * ht, n == 0 ? 0 : ((n - 5) >> 1) & 1, dl);
          if (n == 0) fence_proxy_async_smem();
          if (n == 2 || n == 3) tma_store_2d(&maps.o, sbase + SM_STG, (j + 8 * (n - 2)) * 64, row0);
          else if (n == 4) tma_store_2d(&maps.MAP_H2, sbase + SM_STG + 16384, j * 128 + 64, row0);
          else tma_store_3d(&maps.hh, sbase + SM_STG + (n < 2 ? n : ht) * 16384, j * 64, row0, n < 2 ? n : n - 5);
          bulk_commit();
          bulk_wait0();
          red_add_e(n == 3 ? &mail0->flags[FL_O] : flags + FO_CNT + n, 1);
          mbar_arrive_e(n < 4 ? sbase + B_STFREE : sbase + B_HFREE + 8 * ht);
          if (n == 4) mbar_arrive_e(sbase + B_HFREE);
          PROFN(70 + n, lane == 0 && n > 0); PROF(85, lane == 0 && n == 0);
          if (n != 3) { wait_flag(flags + FO_CNT + n, e1 * 8, dl); mbar_arrive_e(sbase + B_FLG + 8 * n); }
        }
      } else {
        const float* const mail = &mail0->mod[(b & 7) * 6 * D_ + lane * 4];
        if (wid == 10) {
          #pragma unroll 1
          for (int p = 0; p < 8; p++) {
            if (p >= 2) mbar_wait(p == 2 ? q_empty(0, sbase) : q_empty(2 * p - 5, sbase), p == 2 ? 0 : ((2 * p - 5) >> 2) & 1, dl);
            gather_table(mail + p * 128, sbase + SM_MODT + (p & 3) * 512 + ((lane * 16) ^ ((j >> 1) << 6)), 2 * p - 1 < MSEP ? sbase + B_MOD + 8 * p : sbase + B_FQ + 8 * ((2 * p - 1) & 3), par, dl);
            PROF(63 + p, lane == 0 && p < 7);
          }
          const uint32_t vdst = sbase + SM_VEC + (lane >> 3) * 64 + (lane & 3) * 16 + ((lane >> 2) & 1) * 8;
          #pragma unroll 1
          for (int v = 0; v < 2; v++) {
            mbar_sleep(sbase + B_FLG + 16 + 24 * v, 0, dl);
            uint4 m[3];
            while (true) {
              #pragma unroll
              for (int e = 0; e < 3; e++) m[e] = ld_rlx_v4(mail + (2 + v + e) * 1024 + j * 128);
              if (poll_done(((bad4(m[0], par) | bad4(m[1], par) | bad4(m[2], par)) & 1) == 0, dl)) break;
              __nanosleep(200);
            }
            #pragma unroll
            for (int e = 0; e < 3; e++) sts64(vdst + (v + e) * 256, hi_halves(m[e].x, m[e].y), hi_halves(m[e].z, m[e].w));
            if (v == 0) sts128(sbase + SM_VEC + 1024 + lane * 16, m[0].x & ~1u, m[0].y & ~1u, m[0].z & ~1u, m[0].w & ~1u);
            mbar_arrive_e(sbase + B_VEC + 8 * v);
            PROF(70, lane == 0 && v == 0);
          }
        } else {
          mbar_wait(sbase + B_LN, 0, dl);
          red_add_e(&mail0->flags[FL_LN1], 1);
          wait_flag(&mail0->flags[FL_LN1], e1 * NCTA, dl);
          mbar_arrive_e(sbase + B_GATE);
          PROF(41, lane == 0);
          mbar_sleep(sbase + B_FLG, 0, dl);
          #pragma unroll
          for (int e = 0; e < 2; e++) st_rlx_v4(mail0->st2 + ((mb * 8 + e * 4 + (lane >> 3)) * 8 + j) * 8 + (lane & 7), 0, 0, 0, 0, true);
          __threadfence();
          mbar_arrive_e(sbase + B_RST);
          PROF(86, lane == 0);
          mbar_sleep(sbase + B_VEC, 0, dl);
          publish_h2a(1);
        }
      }
    }
  } else {
    const int wg = wid >> 2, warp = wid & 3;
    const int g = lane >> 2, qd = lane & 3;
    bulk_prefetch(wmod + (size_t)(b * 8 + wid) * (6 * D_), PF_BYTES);
    bulk_prefetch(wmod + (size_t)(b * 8 + wid) * (6 * D_) + D_, PF_BYTES);
    bar_sync(0, 384);
    bulk_prefetch(wmod + (size_t)(b * 8 + wid) * (6 * D_) + PF_BYTES / 2, PF_BYTES);
    bulk_prefetch(wmod + (size_t)(b * 8 + wid) * (6 * D_) + PF_BYTES / 2 + D_, PF_BYTES);
    const unsigned e1 = 1 + ld_relaxed(flags + FO_EPOCH), par = e1 & 1;
    reg_alloc<232>();
    PROF(1, tid == 0);
    const uint32_t wgoff = wg * 8192;
    const uint32_t frag0 = wid * 2048 + (lane & 15) * 128 + (((lane >> 4) ^ (lane & 7)) << 4);
    const uint32_t slab = sbase + SM_STG + wid * 2048;

    LnRow ln;
    {
      uint2* const lmail = &mail0->ln1[(mb * 8 + (wid & 1) * 4 + (j >> 1)) * 16 + (j & 1) * 8 + (wid >> 1) + (lane & 1) * 4];
      float sm = 0.f, qm = 0.f, so = 0.f, qo = 0.f;
      #pragma unroll
      for (int h = 0; h < 2; h++) {
        sm = so; qm = qo;
        float s[2] = {0.f, 0.f}, q2[2] = {0.f, 0.f};
        mbar_wait(sbase + B_X + 8 * (4 * h + (wid >> 1)), 0, dl);
        PROF(3, tid == 224); PROF(93, tid == 0);
        #pragma unroll
        for (int c = 0; c < 4; c++) {
          const uint4 v = lds128(sbase + SM_XR + h * 16384 + wid * 2048 + c * 512 + lane * 16);
          const uint32_t vv[4] = {v.x, v.y, v.z, v.w};
          #pragma unroll
          for (int e = 0; e < 4; e++) {
            const float lo = bf_lo(vv[e]), hi = bf_hi(vv[e]);
            s[0] += lo; s[1] += hi; q2[0] = fmaf(lo, lo, q2[0]); q2[1] = fmaf(hi, hi, q2[1]);
          }
        }
        so = s[0] + s[1]; qo = q2[0] + q2[1];
      }
      const bool odd = lane & 1;
      { const float a = odd ? so : sm, c = odd ? qo : qm;
        sm = a + __shfl_xor_sync(0xffffffffu, odd ? sm : so, 1); qm = c + __shfl_xor_sync(0xffffffffu, odd ? qm : qo, 1); }
      #pragma unroll
      for (int o = 2; o < 32; o <<= 1) { sm += __shfl_xor_sync(0xffffffffu, sm, o); qm += __shfl_xor_sync(0xffffffffu, qm, o); }
      sm *= (1.f / D_);
      ln_row(ln, 0, sm, fast_rsqrt(fmaxf(qm * (1.f / D_) - sm * sm, 0.f) + 1e-5f));
      st_rlx_v2(lmail, (ln.rs[0] << 16) | par, (ln.nb[0] << 16) | par, lane < 2);
      mbar_arrive_e(sbase + B_LN);
      PROF(4, tid == 224);
    }

    uint4* const halo_out = mail0->halo[par] + ((mb * 16 + j) * 2 + wg) * 128 + lane;
    const uint4* const halo_in = halo_out - 16 * 256;
    const uint32_t xch = sbase + SM_XCH + (tid >> 5) * 2048 + lane * 16;
    const bool noprev = mb == 0 && warp == 0, remote = mb > 0 && warp == 0;
    float a0[64], a1[64];
    uint32_t x2[32];
    Ring r{zero, 0, 0, dl};
    Frag8 qA, qB, kA, kB, vA, vB, wA, wB;
    {
      float acc[128];
      uint32_t A0[16], A1[16];
      undef_regs(acc);
      const uint32_t tab = sbase + SM_MODT + qd * 16;
      uint4 p[4];
      const uint32_t rot = j >> 1;
      Frag4 fq;
      #pragma unroll
      for (int q = 0; q < 4; q++) fq.o[q] = frag0 ^ ((q ^ rot) << 5);
      mbar_wait(sbase + B_LN, 0, dl);
      const uint2* const lin = &mail0->ln1[(mb * 8 + wid) * 16 + g];
      uint2 v0, v1;
      q_wait(0, sbase, dl);
      #pragma unroll
      for (int kk = 0; kk < 4; kk++) ldmatrix_x4(sbase + SM_X0 + fq.o[kk], A0[4 * kk], A0[4 * kk + 1], A0[4 * kk + 2], A0[4 * kk + 3]);
      do { v0 = ld_rlx_v2(lin); v1 = ld_rlx_v2(lin + 8); } while (!poll_done(((bad2(v0.x, v0.y, par) | bad2(v1.x, v1.y, par)) & 1) == 0, dl));
      ln.rs[0] = hi_halves(v0.x, v0.x); ln.nb[0] = hi_halves(v0.y, v0.y); ln.rs[1] = hi_halves(v1.x, v1.x); ln.nb[1] = hi_halves(v1.y, v1.y);
      mbar_wait(sbase + B_MOD, 0, dl);
      #pragma unroll
      for (int kk = 0; kk < 4; kk++) p[kk] = lds128(tab + kk * 64);
      PROF(5, tid == 0);
      q_step_rs<true>(acc, A0, A1, p, 0, sbase, fq, tab, ln, rot, !(j & 1), true, dl, wg, zero);
      #pragma unroll
      for (int u = 1; u < 15; u += 2) {
        q_step_rs<true>(acc, A1, A0, p, u, sbase, fq, tab, ln, rot, j & 1, false, dl, wg, zero);
        q_step_rs<true>(acc, A0, A1, p, u + 1, sbase, fq, tab, ln, rot, !(j & 1), false, dl, wg, zero);
        if (u == 7) mbar_arrive_e(sbase + B_STREQ);
      }
      q_step_rs<false>(acc, A1, A0, p, 15, sbase, fq, tab, ln, rot, j & 1, false, dl, wg, zero);
      PROF(7, tid == 0);
      mbar_wait(sbase + B_STFREE, 0, dl);
      request_store(sbase + B_STREQ);
      wgmma_wait<0>();
      undef_regs(a0);
      { const uint32_t slot = m_wait(sbase, r); mma_step(a0, slot + wgoff, slot + 16384, true, q_empty(15, sbase)); m_next(r); }
      fence_regs(acc);
      PROF(8, tid == 0);
      sched_fence(zero);
      pack_half(vB, acc, 64, 1); transpose8(vB);
      m_step(a0, sbase, wgoff, r);
      sched_fence(zero);
      pack_half(kB, acc, 32, 1);
      attn_send(vB, 1, xch - 16384, warp, halo_out, mb < 15); attn_send(kB, 0, xch - 16384, warp, halo_out, mb < 15);
      m_step(a0, sbase, wgoff, r);
      sched_fence(zero);
      pack_half(qA, acc, 0, 0); pack_half(qB, acc, 0, 1); pack_half(kA, acc, 32, 0); pack_half(wB, acc, 96, 1); pack_half(wA, acc, 96, 0);
      m_step(a0, sbase, wgoff, r);
      sched_fence(zero);
      pack_half(vA, acc, 64, 0); transpose8(vA);
    }
    uint4 wP[2];
    Frag4 frag;
    #pragma unroll
    for (int q = 0; q < 4; q++) frag.o[q] = frag0 ^ (q << 5);
    {
      m_step(a0, sbase, wgoff, r);
      uint4 pv[4];
      attn_recv<4>(pv, 0, xch - 16384, wg, warp, halo_in, mb > 0);
      m_step(a0, sbase, wgoff, r);
      mbar_wait(sbase + B_STFREE, 1, dl);
      transpose8(wB);
      m_step(a0, sbase, wgoff, r);
      attn_check<4>(pv, 0, remote, halo_in, dl);
      wgmma_wait<0>();
      PROF(9, tid == 0);
      float o[2][5][4];
      sched_fence(zero);
      attn_core<0>(qA, qB, kA, kB, vA, vB, pv, pv + 2, noprev, lane, o, Nop());
      attn_store(o, 0, sbase, frag);
      attn_store(o, 1, sbase, frag);
      request_store(sbase + B_STREQ);
      bar_sync(NB_CONS, 256);
      PROF(10, tid == 0);
      m_step(a0, sbase, wgoff, r);
      sched_fence(zero);
      attn_send(wB, 1, xch, warp, halo_out + 8 * 256, mb < 15);
      m_step(a0, sbase, wgoff, r);
      sched_fence(zero);
      transpose8(wA);
      #pragma unroll 1
      for (int i = 9; i < 15; i++) m_step(a0, sbase, wgoff, r);
      attn_recv<2>(wP, 2, xch, wg, warp, halo_in + 8 * 256, mb > 0);
      m_step(a0, sbase, wgoff, r);
    }
    {
      undef_regs(a1);
      {
        const uint32_t slot = m_wait(sbase, r);
        mma_step(a1, slot + wgoff, slot + 16384, true, m_prev(sbase, r), [&] {
          fence_regs(a0);
          pack_half(kB, a0, 32, 1);
          attn_send(kB, 0, xch, warp, halo_out + 8 * 256, mb < 15);
        });
        m_next(r);
      }
      PROF(14, tid == 0);
      sched_fence(zero);
      pack_half(kA, a0, 32, 0); pack_half(qA, a0, 0, 0); pack_half(qB, a0, 0, 1);
      m_step(a1, sbase, wgoff, r);
      attn_check<2>(wP, 2, remote, halo_in + 8 * 256, dl);
      uint4 kP[2];
      attn_recv<2>(kP, 0, xch, wg, warp, halo_in + 8 * 256, mb > 0);
      m_step(a1, sbase, wgoff, r);
      if (ASPLIT == 0) attn_check<2>(kP, 0, remote, halo_in + 8 * 256, dl);
      wgmma_wait<0>();
      PROF(15, tid == 0);
      float o[2][5][4];
      mbar_wait(sbase + B_STFREE, 0, dl);
      attn_core<ASPLIT>(qA, qB, kA, kB, wA, wB, kP, wP, noprev, lane, o, [&] { attn_check<2>(kP, 0, remote, halo_in + 8 * 256, dl); });
      attn_store(o, 0, sbase, frag);
      attn_store(o, 1, sbase, frag);
      request_store(sbase + B_STREQ);
      bar_sync(NB_CONS, 256);
      PROF(16, tid == 0);
      auto residual = [&] {
        const uint32_t xs = m_wait(sbase, r), xe = sbase + B_EM + 8 * r.st;
        ring_next(r);
        #pragma unroll
        for (int t = 0; t < 2; t++) {
          #pragma unroll
          for (int jj = 4 * t; jj < 4 * t + 4; jj++) ldmatrix_x4(xs + t * 16384 + frag.o[jj & 3], x2[4 * jj], x2[4 * jj + 1], x2[4 * jj + 2], x2[4 * jj + 3]);
          if (t == 1) {
            uint32_t dep = 0;
            #pragma unroll
            for (int jj = 0; jj < 8; jj++) dep |= x2[4 * jj];
            mbar_arrive_e(xe + (dep & zero));
          }
          m_step(a1, sbase, wgoff, r);
        }
      };
      m_step(a1, sbase, wgoff, r);
      residual();
      float xf[64];
      #pragma unroll
      for (int t = 0; t < 2; t++) {
        sched_fence(zero);
        #pragma unroll
        for (int i = 16 * t; i < 16 * t + 16; i++) {
          xf[2 * i] = bf_lo(x2[i]); xf[2 * i + 1] = bf_hi(x2[i]);
          asm volatile("" : "+f"(xf[2 * i]), "+f"(xf[2 * i + 1]));
        }
        m_step(a1, sbase, wgoff, r);
      }
      mma_step(a1, sbase + SM_STG + wgoff, m_wait(sbase, r) + 16384, false, m_prev(sbase, r));
      m_next(r);
      PROF(17, tid == 0);
      const uint32_t vec = sbase + SM_VEC + qd * 16;
      uint4 ga[8];
      #pragma unroll 1
      for (int i = 0; i < 5 - WTAIL; i++) m_step(a1, sbase, wgoff, r);
      mbar_wait(sbase + B_VEC, 0, dl);
      #pragma unroll
      for (int t = 0; t < 2; t++) {
        m_step(a1, sbase, wgoff, r);
        if (t == 0) mbar_wait(sbase + B_STFREE, 1, dl); else sched_fence(zero);
        #pragma unroll
        for (int q = 4 * t; q < 4 * t + 4; q++) ga[q] = lds128(vec + 1024 + q * 64);
      }
      uint4* sm = mail0->st2 + (mb * 8 + wid) * 64 + g;
      asm volatile("" : "+l"(sm));
      if (wg == 1) bar_sync(NB_ORD, 256);
      #pragma unroll 1
      for (int i = 0; i < WTAIL; i++) { const uint32_t slot = m_wait(sbase, r); mma_solo<true>(a1, slot + wgoff, slot + 16384, false, m_prev(sbase, r)); m_next(r); }
      if (wg == 0) bar_arrive(NB_ORD, 256);
      wgmma_wait<0>();
      mbar_arrive_e(m_prev(sbase, r));
      fence_regs(a1);
      PROF(18, tid == 0); PROF(23, tid == 128);
      float s[2], q2[2], sa[4] = {0.f, 0.f, 0.f, 0.f}, qa[4] = {0.f, 0.f, 0.f, 0.f};
      #pragma unroll
      for (int i = 0; i < 64; i++) {
        const uint4& gv = ga[i >> 3];
        xf[i] = fmaf(__uint_as_float((i & 4) ? ((i & 1) ? gv.w : gv.z) : ((i & 1) ? gv.y : gv.x)), a1[i], xf[i]);
        sa[i & 3] += xf[i]; qa[i & 3] = fmaf(xf[i], xf[i], qa[i & 3]);
      }
      #pragma unroll
      for (int h = 0; h < 2; h++) { s[h] = sa[2 * h] + sa[2 * h + 1]; q2[h] = qa[2 * h] + qa[2 * h + 1]; }
      #pragma unroll
      for (int o2 = 1; o2 <= 2; o2 <<= 1)
        #pragma unroll
        for (int h = 0; h < 2; h++) { s[h] += __shfl_xor_sync(0xffffffffu, s[h], o2); q2[h] += __shfl_xor_sync(0xffffffffu, q2[h], o2); }
      st_nonzero_v4(sm + j * 8, __float_as_uint(s[0]), __float_as_uint(q2[0]), __float_as_uint(s[1]), __float_as_uint(q2[1]), qd == 0);
      sched_fence(zero);
      #pragma unroll
      for (int i = 0; i < 32; i++) { x2[i] = pack_bf16(xf[2 * i], xf[2 * i + 1]); asm volatile("" : "+r"(x2[i])); }
      PROF(19, tid == 0); PROF(24, tid == 128);
      uint4 sb[4], cb[4];
      #pragma unroll
      for (int q = 0; q < 4; q++) { sb[q] = lds128(vec + 256 + q * 64); cb[q] = lds128(vec + 512 + q * 64); }
      uint4 p0, p1;
      while (true) {
        p0 = ld_rlx_v4(sm + qd * 16); p1 = ld_rlx_v4(sm + qd * 16 + 8);
        if (poll_done(min(min4(p0), min4(p1)) != 0, dl)) break;
      }
      PROF(20, tid == 0); PROF(25, tid == 128);
      s[0] = __uint_as_float(p0.x) + __uint_as_float(p1.x); q2[0] = __uint_as_float(p0.y) + __uint_as_float(p1.y);
      s[1] = __uint_as_float(p0.z) + __uint_as_float(p1.z); q2[1] = __uint_as_float(p0.w) + __uint_as_float(p1.w);
      #pragma unroll
      for (int o2 = 1; o2 <= 2; o2 <<= 1)
        #pragma unroll
        for (int h = 0; h < 2; h++) { s[h] += __shfl_xor_sync(0xffffffffu, s[h], o2); q2[h] += __shfl_xor_sync(0xffffffffu, q2[h], o2); }
      #pragma unroll
      for (int h = 0; h < 2; h++) {
        const float m = s[h] * (1.f / D_);
        ln_row(ln, h, m, fast_rsqrt(fmaxf(q2[h] * (1.f / D_) - m * m, 0.f) + 1e-5f));
      }
      #pragma unroll
      for (int jj = 0; jj < 8; jj++) {
        const uint32_t cl = (jj & 1) ? cb[jj >> 1].z : cb[jj >> 1].x, ch = (jj & 1) ? cb[jj >> 1].w : cb[jj >> 1].y;
        const uint32_t sl = (jj & 1) ? sb[jj >> 1].z : sb[jj >> 1].x, sh = (jj & 1) ? sb[jj >> 1].w : sb[jj >> 1].y;
        stmatrix_x4(sbase + SM_STG + (jj >> 2) * 16384 + frag.o[jj & 3], ln_mod(x2[4 * jj], ln, 0, cl, sl), ln_mod(x2[4 * jj + 1], ln, 1, cl, sl),
                    ln_mod(x2[4 * jj + 2], ln, 0, ch, sh), ln_mod(x2[4 * jj + 3], ln, 1, ch, sh));
        if (jj == 3) { request_store(sbase + B_STH + 8 * wg); sched_fence(zero); }
      }
      request_store(sbase + B_STREQ);
      bar_sync(NB_WG + wg, 128);
      PROF(21, tid == 0); PROF(26, tid == 128);
    }

    undef_regs(a0);
    #pragma unroll
    for (int t = 0; t < 2; t++) {
      const uint32_t slot = m_wait(sbase, r);
      if (t == 0) mma_solo<false>(a0, sbase + SM_STG + wgoff, slot, true, 0);
      else mma_solo<true>(a0, sbase + SM_STG + 16384 + wgoff, slot, false, m_prev(sbase, r));
      mma_solo<false>(a1, sbase + SM_STG + t * 16384 + wgoff, slot + 16384, t == 0, 0);
      m_next(r);
    }
    PROF(22, tid == 0); PROF(27, tid == 128);
    #pragma unroll 1
    for (int i = 0; i < 3; i++) {
      if (wg == 1) mbar_wait(sbase + B_F1 + 8 * i, 0, dl);
      if (i < 2) { const uint32_t slot = m_wait(sbase, r); mma_solo<true>(a0, slot + wgoff, slot + 16384, false, m_prev(sbase, r)); m_next(r); }
    }
    uint32_t held = 0;
    #pragma unroll 1
    for (int pr = 0; pr < 3; pr++) {
      #pragma unroll 1
      for (int i = 0; i < 5; i++) { g_quad(a0, a1, held, sbase, wgoff, r); held = 0; }
      held = g_ppqq<false, true>(a0, a1, false, 0, sbase, wgoff, r, [&](int i) { if (i >= 2) g_piece<0>(a0, i - 2, pr, sbase, frag, dl); });
      held = g_ppqq<true, true>(a1, a0, true, held, sbase, wgoff, r,
                                [&](int i) { if (i < 2) g_piece<0>(a0, i + 2, pr, sbase, frag, dl); else g_piece<1>(a1, i - 2, pr, sbase, frag, dl); });
      if (pr == 2) break;
      held = g_ppqq<true, true>(a0, a1, true, held, sbase, wgoff, r, [&](int i) { if (i < 2) g_piece<1>(a1, i + 2, pr, sbase, frag, dl); });
    }
    g_ppqq<true, false>(a0, a1, false, held, sbase, wgoff, r, [&](int i) { g_piece<1>(a1, i + 2, 2, sbase, frag, dl); });
    #pragma unroll 1
    for (int i = 4; i < 15; i++) m_step(a0, sbase, wgoff, r);
    m_step(a0, sbase, wgoff, r);
    #pragma unroll
    for (int jj = 0; jj < 4; jj++) { m_step(a1, sbase, wgoff, r, jj == 0); g_piece<0>(a0, jj, 3, sbase, frag, dl); }
    #pragma unroll 1
    for (int i = 4; i < 56 - DTAIL; i++) m_step(a1, sbase, wgoff, r);
    if (DTAIL) {
      if (wg == 1) { wgmma_wait<0>(); mbar_arrive_e(m_prev(sbase, r)); bar_sync(NB_ORD, 256); }
      #pragma unroll 1
      for (int i = 0; i < DTAIL; i++) {
        const uint32_t slot = m_wait(sbase, r);
        mma_solo<false>(a1, slot + wgoff, slot + 16384, false, 0);
        ring_next(r);
      }
      if (wg == 0) bar_arrive(NB_ORD, 256);
    }
    {
      mbar_wait(sbase + B_HFREE, 0, dl);
      mbar_wait(sbase + B_HFREE + 8, 1, dl);
      mbar_wait(sbase + B_VEC + 8, 0, dl);
      uint4 gb[4];
      #pragma unroll
      for (int q = 0; q < 4; q++) gb[q] = lds128(sbase + SM_VEC + 768 + qd * 16 + q * 64);
      wgmma_wait<0>();
      fence_regs(a1);
      PROF(50, tid == 128);
      #pragma unroll
      for (int t = 0; t < 2; t++) {
        #pragma unroll
        for (int jj = 4 * t; jj < 4 * t + 4; jj++) {
          const uint32_t gl = (jj & 1) ? gb[jj >> 1].z : gb[jj >> 1].x, gh = (jj & 1) ? gb[jj >> 1].w : gb[jj >> 1].y;
          const int i = 8 * jj;
          stmatrix_x4(sbase + SM_STG + t * 16384 + frag.o[jj & 3],
                      fma_bf2(gl, pack_bf16(a1[i], a1[i + 1]), x2[4 * jj]), fma_bf2(gl, pack_bf16(a1[i + 2], a1[i + 3]), x2[4 * jj + 1]),
                      fma_bf2(gh, pack_bf16(a1[i + 4], a1[i + 5]), x2[4 * jj + 2]), fma_bf2(gh, pack_bf16(a1[i + 6], a1[i + 7]), x2[4 * jj + 3]));
        }
        fence_proxy_async_smem();
        tma_store_3d(&maps.out, slab + t * 16384, j * 128 + t * 64, mb * 64 + warp * 16, wg);
      }
      bulk_commit();
      st_rlx(tid == 0 ? flags + FO_EPOCH : &mail0->flags[FL_EPOCH], e1, j == 0 && (tid == 0 || (tid == 1 && mb == 0)));
      bulk_wait_read0();
      PROFN(51, tid == 128);
    }
  }
}

typedef CUresult (*PFN_encodeTiled)(CUtensorMap*, CUtensorMapDataType, cuuint32_t, void*, const cuuint64_t*, const cuuint64_t*,
                                    const cuuint32_t*, const cuuint32_t*, CUtensorMapInterleave, CUtensorMapSwizzle,
                                    CUtensorMapL2promotion, CUtensorMapFloatOOBfill);

void encode(PFN_encodeTiled fn, CUtensorMap* m, const void* ptr, int rank, const cuuint64_t* dims, const cuuint64_t* strides,
            const cuuint32_t* box) {
  const cuuint32_t es[5] = {1, 1, 1, 1, 1};
  fn(m, CU_TENSOR_MAP_DATA_TYPE_BFLOAT16, rank, const_cast<void*>(ptr), dims, strides, box, es, CU_TENSOR_MAP_INTERLEAVE_NONE,
     CU_TENSOR_MAP_SWIZZLE_128B, CU_TENSOR_MAP_L2_PROMOTION_L2_256B, CU_TENSOR_MAP_FLOAT_OOB_FILL_NONE);
}
void map2d(PFN_encodeTiled fn, CUtensorMap* m, const void* ptr, int cols, int rows, int boxrows) {
  const cuuint64_t dims[2] = {(cuuint64_t)cols, (cuuint64_t)rows}, strides[1] = {(cuuint64_t)cols * 2};
  const cuuint32_t box[2] = {64, (cuuint32_t)boxrows};
  encode(fn, m, ptr, 2, dims, strides, box);
}
void map_w2chunk(PFN_encodeTiled fn, CUtensorMap* m, const void* ptr, int cols, int rows) {
  const cuuint64_t dims[3] = {64, (cuuint64_t)rows, (cuuint64_t)cols / 64}, strides[2] = {(cuuint64_t)cols * 2, 128};
  const cuuint32_t box[3] = {64, 64, 2};
  encode(fn, m, ptr, 3, dims, strides, box);
}
void map_parity(PFN_encodeTiled fn, CUtensorMap* m, const void* ptr, int boxpairs, int boxpar) {
  const cuuint64_t dims[3] = {D_, S_ / 2, 2}, strides[2] = {D_ * 4, D_ * 2};
  const cuuint32_t box[3] = {64, (cuuint32_t)boxpairs, (cuuint32_t)boxpar};
  encode(fn, m, ptr, 3, dims, strides, box);
}

}

extern "C" void kernel_launch(void* const* d_in, const int* in_sizes, int n_in, void* d_out, int out_size) {
  (void)in_sizes; (void)n_in; (void)out_size;
  const bf16* x = (const bf16*)d_in[0];
  const bf16* wqkv = (const bf16*)d_in[1];
  const bf16* wo = (const bf16*)d_in[2];
  const bf16* w1 = (const bf16*)d_in[4];
  const bf16* w3 = (const bf16*)d_in[5];
  const bf16* w2 = (const bf16*)d_in[6];
  const bf16* cvec = (const bf16*)d_in[7];
  const bf16* w_mod = (const bf16*)d_in[8];

  static PFN_encodeTiled fn = nullptr;
  static Maps maps;
  static const void* cached[8] = {};
  static int sms = 0;
  static void* mail = nullptr;
  if (!fn) {
    void* p = nullptr; cudaDriverEntryPointQueryResult st;
    cudaGetDriverEntryPoint("cuTensorMapEncodeTiled", &p, cudaEnableDefault, &st);
    fn = (PFN_encodeTiled)p;
    cudaFuncSetAttribute(fused_block_kernel<0>, cudaFuncAttributeMaxDynamicSharedMemorySize, SM_TOTAL + SM_PROF);
    cudaFuncSetAttribute(fused_block_kernel<1>, cudaFuncAttributeMaxDynamicSharedMemorySize, SM_TOTAL + SM_PROF);
    cudaFuncSetAttribute(fused_block_kernel<2>, cudaFuncAttributeMaxDynamicSharedMemorySize, SM_TOTAL + SM_PROF);
    cudaGetSymbolAddress(&mail, g_mail);
    int dev = 0;
    cudaGetDevice(&dev);
    cudaDeviceGetAttribute(&sms, cudaDevAttrMultiProcessorCount, dev);
  }
  const void* cur[8] = {x, wqkv, wo, w1, w3, w2, d_out, w_mod};
  bool same = true;
  for (int i = 0; i < 8; i++) same = same && cached[i] == cur[i];
  if (!same) {
    void *o, *hh;
    cudaGetSymbolAddress(&hh, g_hh); cudaGetSymbolAddress(&o, g_o);
    map2d(fn, &maps.h64, o, D_, S_, 64);
    map_parity(fn, &maps.x, x, 64, 2); map_parity(fn, &maps.out, d_out, 16, 1);
    map2d(fn, &maps.o, o, D_, S_, 128);
    {
      const cuuint64_t dims[3] = {512, (cuuint64_t)S_, 7}, strides[2] = {1024, (cuuint64_t)S_ * 1024};
      const cuuint32_t box[3] = {64, 128, 1};
      encode(fn, &maps.hh, hh, 3, dims, strides, box);
    }
    {
      const cuuint64_t dims[4] = {64, 1024, 16, 2}, strides[3] = {3072 * 2, 128, 2048};
      const cuuint64_t dimv[4] = {64, 1024, 8, 2}, stridev[3] = {3072 * 2, 128, 1024};
      const cuuint32_t box[4] = {64, 64, 1, 2};
      encode(fn, &maps.wqk, wqkv, 4, dims, strides, box);
      encode(fn, &maps.wvv, wqkv + 2048, 4, dimv, stridev, box);
      const cuuint64_t dim1[4] = {1024, 128, 8, 2}, stride1[3] = {3072 * 2, 128 * 3072 * 2, 2048};
      const cuuint32_t box1[4] = {64, 16, 4, 2};
      encode(fn, &maps.wq1, wqkv, 4, dim1, stride1, box1);
    }
    map_w2chunk(fn, &maps.wo, wo, D_, D_); map_w2chunk(fn, &maps.w2, w2, D_, F_);
    map2d(fn, &maps.w1, w1, F_, D_, 64); map2d(fn, &maps.w3, w3, F_, D_, 64);
    map2d(fn, &maps.wmod, w_mod, 6 * D_, D_, 256);
    for (int i = 0; i < 8; i++) cached[i] = cur[i];
  }
  if (sms == NCTA + NAUX) {
    fused_block_kernel<0><<<NCTA + NAUX, 384, SM_TOTAL + SM_PROF>>>(x, cvec, w_mod, (Mail*)mail, 0, maps);
  } else {
    fused_block_kernel<1><<<NAUX, 384, SM_TOTAL + SM_PROF>>>(x, cvec, w_mod, (Mail*)mail, 0, maps);
    fused_block_kernel<2><<<NCTA, 384, SM_TOTAL + SM_PROF>>>(x, cvec, w_mod, (Mail*)mail, 0, maps);
  }
}
```

```cpp
#include <cuda.h>
#include <cuda_runtime.h>
#include <cuda_bf16.h>
#include <stdint.h>

namespace {

typedef __nv_bfloat16 bf16;

constexpr int S_ = 2048, D_ = 1024, F_ = 3584;
constexpr int NCTA = 128, NAUX = 4;

__device__ __align__(1024) bf16 g_o[S_ * D_];
__device__ __align__(1024) bf16 g_hh[S_ * F_];
constexpr int FO_EPOCH = 0, FO_CNT = 1;
constexpr int FL_EPOCH = 16 * 32, FL_LN1 = FL_EPOCH + 2, FL_O = FL_EPOCH + 3, FL_H2 = FL_EPOCH + 4;
struct Mail {
  unsigned flags[32 * 32];
  float mod[8 * 6 * D_];
  uint2 ln1[16 * 8 * 16];
  uint4 st2[16 * 8 * 8 * 8];
  uint4 halo[2][16 * 16 * 2 * 4 * 32];
};
__device__ __align__(1024) Mail g_mail;

template <int mode>
__device__ __forceinline__ int cta_role() {
  if (mode) return mode == 1 ? NCTA + (blockIdx.x & 3) : blockIdx.x & 127;
  uint32_t sm;
  asm("mov.u32 %0, %%smid;" : "=r"(sm));
  sm = (sm & ~3u) == 12 ? sm + 108 : (sm & ~3u) == 120 ? sm - 108 : sm;
  const int t = sm >> 1;
  int r;
  if (t < 32) r = (t & 7) * 16 + (t >> 3) * 2 + (sm & 1);
  else if (t < 60) r = (1 + (t - 32) % 7) * 16 + 8 + ((t - 32) / 7) * 2 + (sm & 1);
  else if (t < 62) r = NCTA + sm - 120;
  else r = sm - 116;
  return r;
}
#define PROF(slot, on) do {} while (0)
#define PROFN(slot, on) do {} while (0)
#define PROF_OUT(role, t) do {} while (0)
constexpr uint32_t SM_PROF = 0;

__device__ __forceinline__ uint32_t smem_u32(const void* p) { return (uint32_t)__cvta_generic_to_shared(p); }
#define ELECT "{\n.reg .pred p;\nelect.sync _|p, 0xffffffff;\n@p "
__device__ __forceinline__ void mbar_init_e(uint32_t bar, uint32_t count) {
  asm volatile(ELECT "mbarrier.init.shared::cta.b64 [%0], %1;\n}" :: "r"(bar), "r"(count) : "memory");
}
__device__ __forceinline__ void mbar_expect_tx_e(uint32_t bar, uint32_t bytes) {
  asm volatile(ELECT "mbarrier.arrive.expect_tx.shared::cta.b64 _, [%0], %1;\n}" :: "r"(bar), "r"(bytes) : "memory");
}
__device__ __forceinline__ void mbar_arrive_e(uint32_t bar) {
  asm volatile(ELECT "mbarrier.arrive.shared::cta.b64 _, [%0];\n}" :: "r"(bar) : "memory");
}
__device__ __forceinline__ uint32_t clock32() { uint32_t t; asm volatile("mov.u32 %0, %%clock;" : "=r"(t)); return t; }
#define WAIT_TAIL "setp.ne.and.u32 p, %2, 0, !p;\n@p bra LAB_WAIT;\n}"
__device__ __forceinline__ void mbar_wait(uint32_t bar, uint32_t parity, uint32_t dl) {
  asm volatile("{\n.reg .pred p;\n.reg .b32 t;\nLAB_WAIT:\nmbarrier.try_wait.parity.shared::cta.b64 p, [%0], %1;\n" WAIT_TAIL
               :: "r"(bar), "r"(parity), "r"(dl) : "memory");
}
__device__ __forceinline__ void mbar_sleep(uint32_t bar, uint32_t parity, uint32_t dl) {
  asm volatile("{\n.reg .pred p;\n.reg .b32 t;\nLAB_WAIT:\nmbarrier.try_wait.parity.shared::cta.b64 p, [%0], %1, 20000;\n" WAIT_TAIL
               :: "r"(bar), "r"(parity), "r"(dl) : "memory");
}
__device__ __forceinline__ bool poll_done(bool ok, uint32_t dl) {
  return __all_sync(0xffffffffu, ok || (int)(clock32() - dl) >= 0);
}
__device__ __forceinline__ unsigned ld_relaxed(const unsigned* p) {
  unsigned v; asm volatile("ld.relaxed.gpu.global.u32 %0, [%1];" : "=r"(v) : "l"(p) : "memory"); return v;
}
__device__ __forceinline__ void red_add_e(unsigned* p, unsigned v) {
  asm volatile(ELECT "red.relaxed.gpu.global.add.u32 [%0], %1;\n}" :: "l"(p), "r"(v) : "memory");
}
__device__ __forceinline__ void wait_flag(const unsigned* p, unsigned target, uint32_t dl) {
  asm volatile("{\n.reg .pred p;\n.reg .b32 t;\n"
               "LAB_WAIT:\n"
               "ld.relaxed.gpu.global.u32 t, [%0];\n"
               "sub.s32 t, t, %1;\n"
               "setp.ge.s32 p, t, 0;\n"
               "@p bra LAB_DONE;\n"
               "mov.u32 t, %%clock;\n"
               "sub.s32 t, t, %2;\n"
               "setp.lt.s32 p, t, 0;\n"
               "@p bra LAB_WAIT;\n"
               "LAB_DONE:\n}" :: "l"(p), "r"(target), "r"(dl) : "memory");
}
__device__ __forceinline__ void wait_until(uint32_t t) { while ((int)(clock32() - t) < 0) {} }
__device__ __forceinline__ void fence_proxy_async_smem() { asm volatile("fence.proxy.async.shared::cta;" ::: "memory"); }

constexpr uint64_t EVICT_FIRST = 0x12F0000000000000ull;
template <bool STREAM = false>
__device__ __forceinline__ void tma_load_2d(uint32_t dst, const CUtensorMap* m, uint32_t bar, int c0, int c1) {
  if (STREAM)
    asm volatile(ELECT "cp.async.bulk.tensor.2d.shared::cluster.global.mbarrier::complete_tx::bytes.L2::cache_hint [%0], [%1, {%3, %4}], [%2], %5;\n}"
                 :: "r"(dst), "l"(m), "r"(bar), "r"(c0), "r"(c1), "l"(EVICT_FIRST) : "memory");
  else
    asm volatile(ELECT "cp.async.bulk.tensor.2d.shared::cluster.global.mbarrier::complete_tx::bytes [%0], [%1, {%3, %4}], [%2];\n}"
                 :: "r"(dst), "l"(m), "r"(bar), "r"(c0), "r"(c1) : "memory");
}
template <bool STREAM = false>
__device__ __forceinline__ void tma_load_3d(uint32_t dst, const CUtensorMap* m, uint32_t bar, int c0, int c1, int c2) {
  if (STREAM)
    asm volatile(ELECT "cp.async.bulk.tensor.3d.shared::cluster.global.mbarrier::complete_tx::bytes.L2::cache_hint [%0], [%1, {%3, %4, %5}], [%2], %6;\n}"
                 :: "r"(dst), "l"(m), "r"(bar), "r"(c0), "r"(c1), "r"(c2), "l"(EVICT_FIRST) : "memory");
  else
    asm volatile(ELECT "cp.async.bulk.tensor.3d.shared::cluster.global.mbarrier::complete_tx::bytes [%0], [%1, {%3, %4, %5}], [%2];\n}"
                 :: "r"(dst), "l"(m), "r"(bar), "r"(c0), "r"(c1), "r"(c2) : "memory");
}
template <bool STREAM = false>
__device__ __forceinline__ void tma_load_4d(uint32_t dst, const CUtensorMap* m, uint32_t bar, int c0, int c1, int c2, int c3) {
  if (STREAM)
    asm volatile(ELECT "cp.async.bulk.tensor.4d.shared::cluster.global.mbarrier::complete_tx::bytes.L2::cache_hint [%0], [%1, {%3, %4, %5, %6}], [%2], %7;\n}"
                 :: "r"(dst), "l"(m), "r"(bar), "r"(c0), "r"(c1), "r"(c2), "r"(c3), "l"(EVICT_FIRST) : "memory");
  else
    asm volatile(ELECT "cp.async.bulk.tensor.4d.shared::cluster.global.mbarrier::complete_tx::bytes [%0], [%1, {%3, %4, %5, %6}], [%2];\n}"
                 :: "r"(dst), "l"(m), "r"(bar), "r"(c0), "r"(c1), "r"(c2), "r"(c3) : "memory");
}
__device__ __forceinline__ void tma_store_2d(const CUtensorMap* m, uint32_t src, int c0, int c1) {
  asm volatile(ELECT "cp.async.bulk.tensor.2d.global.shared::cta.bulk_group [%0, {%2, %3}], [%1];\n}"
               :: "l"(m), "r"(src), "r"(c0), "r"(c1) : "memory");
}
__device__ __forceinline__ void tma_store_3d(const CUtensorMap* m, uint32_t src, int c0, int c1, int c2) {
  asm volatile(ELECT "cp.async.bulk.tensor.3d.global.shared::cta.bulk_group [%0, {%2, %3, %4}], [%1];\n}"
               :: "l"(m), "r"(src), "r"(c0), "r"(c1), "r"(c2) : "memory");
}
__device__ __forceinline__ void bulk_load(uint32_t dst, const void* src, uint32_t bytes, uint32_t bar) {
  asm volatile(ELECT "cp.async.bulk.shared::cluster.global.mbarrier::complete_tx::bytes [%0], [%1], %2, [%3];\n}"
               :: "r"(dst), "l"(src), "r"(bytes), "r"(bar) : "memory");
}
__device__ __forceinline__ void bulk_prefetch(const void* src, uint32_t bytes) {
  asm volatile(ELECT "cp.async.bulk.prefetch.L2.global [%0], %1;\n}" :: "l"(src), "r"(bytes) : "memory");
}
__device__ __forceinline__ void bulk_commit() { asm volatile("cp.async.bulk.commit_group;" ::: "memory"); }
__device__ __forceinline__ void bulk_wait0() { asm volatile("cp.async.bulk.wait_group 0;" ::: "memory"); }
__device__ __forceinline__ void bulk_wait_read0() { asm volatile("cp.async.bulk.wait_group.read 0;" ::: "memory"); }
__device__ __forceinline__ void prefetch_tmap(const CUtensorMap* m) { asm volatile(ELECT "prefetch.tensormap [%0];\n}" :: "l"(m) : "memory"); }
__device__ __forceinline__ void wgmma_fence() { asm volatile("wgmma.fence.sync.aligned;" ::: "memory"); }
__device__ __forceinline__ void wgmma_commit() { asm volatile("wgmma.commit_group.sync.aligned;" ::: "memory"); }
template <int N> __device__ __forceinline__ void wgmma_wait() { asm volatile("wgmma.wait_group.sync.aligned %0;" :: "n"(N) : "memory"); }
template <int R> __device__ __forceinline__ void reg_alloc() { asm volatile("setmaxnreg.inc.sync.aligned.u32 %0;" :: "n"(R)); }
template <int R> __device__ __forceinline__ void reg_dealloc() { asm volatile("setmaxnreg.dec.sync.aligned.u32 %0;" :: "n"(R)); }
__device__ __forceinline__ void bar_sync(int id, int n) { asm volatile("bar.sync %0, %1;" :: "r"(id), "r"(n) : "memory"); }
__device__ __forceinline__ void bar_arrive(int id, int n) { asm volatile("bar.arrive %0, %1;" :: "r"(id), "r"(n) : "memory"); }
__device__ __forceinline__ void sched_fence(int zero) {
  asm volatile("{\n.reg .pred p;\n.reg .b32 t;\nsetp.eq.s32 p, %0, 0;\n@p bra.uni LAB_S;\n"
               "LAB_F:\nmov.u32 t, %%clock;\nsetp.eq.u32 p, t, 0;\n@p bra LAB_F;\nLAB_S:\n}" :: "r"(zero) : "memory");
}
template <int N> __device__ __forceinline__ void fence_regs(float (&a)[N]) {
  #pragma unroll
  for (int i = 0; i < N; i++) asm volatile("" : "+f"(a[i]) :: "memory");
}
template <int N> __device__ __forceinline__ void undef_regs(float (&a)[N]) {
  #pragma unroll
  for (int i = 0; i < N; i++) asm volatile("" : "=f"(a[i]));
}

__device__ __forceinline__ uint64_t desc_from_lo(uint32_t lo) { return (uint64_t)lo | ((uint64_t)0x40000040u << 32); }
__device__ __forceinline__ uint32_t pack_bf16(float lo, float hi) {
  uint32_t r; asm("cvt.rn.bf16x2.f32 %0, %1, %2;" : "=r"(r) : "f"(hi), "f"(lo)); return r;
}
__device__ __forceinline__ uint32_t fma_bf2(uint32_t a, uint32_t b, uint32_t c) {
  uint32_t d; asm("fma.rn.bf16x2 %0, %1, %2, %3;" : "=r"(d) : "r"(a), "r"(b), "r"(c)); return d;
}
__device__ __forceinline__ float bf_lo(uint32_t v) { return __uint_as_float(v << 16); }
__device__ __forceinline__ float bf_hi(uint32_t v) { return __uint_as_float(v & 0xFFFF0000u); }
__device__ __forceinline__ float bf16_round(float x) { return bf_lo(pack_bf16(x, 0.f)); }
__device__ __forceinline__ void stmatrix_x4(uint32_t addr, uint32_t r0, uint32_t r1, uint32_t r2, uint32_t r3) {
  asm volatile("stmatrix.sync.aligned.m8n8.x4.shared.b16 [%0], {%1, %2, %3, %4};" :: "r"(addr), "r"(r0), "r"(r1), "r"(r2), "r"(r3) : "memory");
}
__device__ __forceinline__ void stmatrix_x4_t(uint32_t addr, uint32_t r0, uint32_t r1, uint32_t r2, uint32_t r3) {
  asm volatile("stmatrix.sync.aligned.m8n8.x4.trans.shared.b16 [%0], {%1, %2, %3, %4};" :: "r"(addr), "r"(r0), "r"(r1), "r"(r2), "r"(r3) : "memory");
}
__device__ __forceinline__ void stmatrix_x4_if(uint32_t addr, uint32_t r0, uint32_t r1, uint32_t r2, uint32_t r3, bool on) {
  asm volatile("{\n.reg .pred p;\nsetp.ne.b32 p, %5, 0;\n@p stmatrix.sync.aligned.m8n8.x4.shared.b16 [%0], {%1, %2, %3, %4};\n}"
               :: "r"(addr), "r"(r0), "r"(r1), "r"(r2), "r"(r3), "r"((int)on) : "memory");
}
__device__ __forceinline__ void ldmatrix_x4(uint32_t addr, uint32_t& r0, uint32_t& r1, uint32_t& r2, uint32_t& r3) {
  asm volatile("ldmatrix.sync.aligned.m8n8.x4.shared.b16 {%0, %1, %2, %3}, [%4];" : "=r"(r0), "=r"(r1), "=r"(r2), "=r"(r3) : "r"(addr) : "memory");
}
__device__ __forceinline__ void ldmatrix_x4_t(uint32_t addr, uint32_t (&r)[4]) {
  asm volatile("ldmatrix.sync.aligned.m8n8.x4.trans.shared.b16 {%0, %1, %2, %3}, [%4];" : "=r"(r[0]), "=r"(r[1]), "=r"(r[2]), "=r"(r[3]) : "r"(addr) : "memory");
}
__device__ __forceinline__ void st_rlx(void* p, uint32_t a, bool on) {
  asm volatile("{\n.reg .pred p;\nsetp.ne.b32 p, %2, 0;\n@p st.relaxed.gpu.global.u32 [%0], %1;\n}" :: "l"(p), "r"(a), "r"((int)on) : "memory");
}
__device__ __forceinline__ void st_rlx_v2(void* p, uint32_t a, uint32_t b, bool on) {
  asm volatile("{\n.reg .pred p;\nsetp.ne.b32 p, %3, 0;\n@p st.relaxed.gpu.global.v2.u32 [%0], {%1, %2};\n}" :: "l"(p), "r"(a), "r"(b), "r"((int)on) : "memory");
}
__device__ __forceinline__ uint2 ld_rlx_v2(const void* p) {
  uint2 v; asm volatile("ld.relaxed.gpu.global.v2.u32 {%0,%1}, [%2];" : "=r"(v.x), "=r"(v.y) : "l"(p) : "memory"); return v;
}
__device__ __forceinline__ void st_rlx_v4(void* p, uint32_t a, uint32_t b, uint32_t c, uint32_t d, bool on) {
  asm volatile("{\n.reg .pred p;\nsetp.ne.b32 p, %5, 0;\n@p st.relaxed.gpu.global.v4.u32 [%0], {%1, %2, %3, %4};\n}"
               :: "l"(p), "r"(a), "r"(b), "r"(c), "r"(d), "r"((int)on) : "memory");
}
__device__ __forceinline__ void st_nonzero_v4(void* p, uint32_t a, uint32_t b, uint32_t c, uint32_t d, bool on) {
  st_rlx_v4(p, max(a, 1u), max(b, 1u), max(c, 1u), max(d, 1u), on);
}
__device__ __forceinline__ uint32_t min4(const uint4& v) { return min(min(v.x, v.y), min(v.z, v.w)); }
__device__ __forceinline__ uint4 ld_rlx_v4(const void* p) {
  uint4 v; asm volatile("ld.relaxed.gpu.global.v4.u32 {%0,%1,%2,%3}, [%4];" : "=r"(v.x), "=r"(v.y), "=r"(v.z), "=r"(v.w) : "l"(p) : "memory"); return v;
}
__device__ __forceinline__ uint32_t movmatrix_t(uint32_t a) {
  uint32_t d; asm volatile("movmatrix.sync.aligned.m8n8.trans.b16 %0, %1;" : "=r"(d) : "r"(a)); return d;
}
__device__ __forceinline__ void mma16(float (&c)[4], uint32_t a0, uint32_t a1, uint32_t a2, uint32_t a3, uint32_t b0, uint32_t b1) {
  asm volatile("mma.sync.aligned.m16n8k16.row.col.f32.bf16.bf16.f32 {%0,%1,%2,%3}, {%4,%5,%6,%7}, {%8,%9}, {%0,%1,%2,%3};"
               : "+f"(c[0]), "+f"(c[1]), "+f"(c[2]), "+f"(c[3]) : "r"(a0), "r"(a1), "r"(a2), "r"(a3), "r"(b0), "r"(b1));
}
__device__ __forceinline__ void sts128(uint32_t addr, uint32_t a, uint32_t b, uint32_t c, uint32_t d) {
  asm volatile("st.shared.v4.b32 [%0], {%1,%2,%3,%4};" :: "r"(addr), "r"(a), "r"(b), "r"(c), "r"(d) : "memory");
}
__device__ __forceinline__ uint4 lds128(uint32_t addr) {
  uint4 v; asm volatile("ld.shared.v4.b32 {%0,%1,%2,%3}, [%4];" : "=r"(v.x), "=r"(v.y), "=r"(v.z), "=r"(v.w) : "r"(addr) : "memory"); return v;
}
__device__ __forceinline__ uint32_t lds32(uint32_t addr) {
  uint32_t v; asm volatile("ld.shared.b32 %0, [%1];" : "=r"(v) : "r"(addr) : "memory"); return v;
}
__device__ __forceinline__ float2 lds64f(uint32_t addr) {
  float2 v; asm volatile("ld.shared.v2.f32 {%0,%1}, [%2];" : "=f"(v.x), "=f"(v.y) : "r"(addr) : "memory"); return v;
}
__device__ __forceinline__ void sts64(uint32_t addr, uint32_t a, uint32_t b) {
  asm volatile("st.shared.v2.b32 [%0], {%1, %2};" :: "r"(addr), "r"(a), "r"(b) : "memory");
}
__device__ __forceinline__ float fast_ex2(float x) { float y; asm("ex2.approx.ftz.f32 %0, %1;" : "=f"(y) : "f"(x)); return y; }
__device__ __forceinline__ float fast_rcp(float x) { float y; asm("rcp.approx.ftz.f32 %0, %1;" : "=f"(y) : "f"(x)); return y; }
__device__ __forceinline__ float fast_rsqrt(float x) { float y; asm("rsqrt.approx.ftz.f32 %0, %1;" : "=f"(y) : "f"(x)); return y; }
__device__ __forceinline__ float silu_f(float g) { return g * fast_rcp(1.f + fast_ex2(g * -1.4426950408889634f)); }
__device__ __forceinline__ float swiglu(float h, float v) {
  float t; asm("tanh.approx.f32 %0, %1;" : "=f"(t) : "f"(h));
  const float p = h * v;
  return fmaf(p, t, p);
}

__device__ __forceinline__ void wgmma_m64n128k16_ss(float (&d)[64], uint64_t descA, uint64_t descB, int scaleD) {
  asm volatile("{\n.reg .pred p;\nsetp.ne.b32 p, %66, 0;\n"
    "wgmma.mma_async.sync.aligned.m64n128k16.f32.bf16.bf16 "
    "{%0, %1, %2, %3, %4, %5, %6, %7, %8, %9, %10, %11, %12, %13, %14, %15, "
    "%16, %17, %18, %19, %20, %21, %22, %23, %24, %25, %26, %27, %28, %29, %30, %31, "
    "%32, %33, %34, %35, %36, %37, %38, %39, %40, %41, %42, %43, %44, %45, %46, %47, "
    "%48, %49, %50, %51, %52, %53, %54, %55, %56, %57, %58, %59, %60, %61, %62, %63}, "
    "%64, %65, p, 1, 1, 0, 1;\n}\n"
    : "+f"(d[0]), "+f"(d[1]), "+f"(d[2]), "+f"(d[3]), "+f"(d[4]), "+f"(d[5]), "+f"(d[6]), "+f"(d[7]),
      "+f"(d[8]), "+f"(d[9]), "+f"(d[10]), "+f"(d[11]), "+f"(d[12]), "+f"(d[13]), "+f"(d[14]), "+f"(d[15]),
      "+f"(d[16]), "+f"(d[17]), "+f"(d[18]), "+f"(d[19]), "+f"(d[20]), "+f"(d[21]), "+f"(d[22]), "+f"(d[23]),
      "+f"(d[24]), "+f"(d[25]), "+f"(d[26]), "+f"(d[27]), "+f"(d[28]), "+f"(d[29]), "+f"(d[30]), "+f"(d[31]),
      "+f"(d[32]), "+f"(d[33]), "+f"(d[34]), "+f"(d[35]), "+f"(d[36]), "+f"(d[37]), "+f"(d[38]), "+f"(d[39]),
      "+f"(d[40]), "+f"(d[41]), "+f"(d[42]), "+f"(d[43]), "+f"(d[44]), "+f"(d[45]), "+f"(d[46]), "+f"(d[47]),
      "+f"(d[48]), "+f"(d[49]), "+f"(d[50]), "+f"(d[51]), "+f"(d[52]), "+f"(d[53]), "+f"(d[54]), "+f"(d[55]),
      "+f"(d[56]), "+f"(d[57]), "+f"(d[58]), "+f"(d[59]), "+f"(d[60]), "+f"(d[61]), "+f"(d[62]), "+f"(d[63])
    : "l"(descA), "l"(descB), "r"(scaleD));
}
__device__ __forceinline__ void wgmma_m64n256k16_rs(float (&d)[128], uint32_t a0, uint32_t a1, uint32_t a2, uint32_t a3, uint64_t descB, int scaleD) {
  asm volatile("{\n.reg .pred p;\nsetp.ne.b32 p, %133, 0;\n"
    "wgmma.mma_async.sync.aligned.m64n256k16.f32.bf16.bf16 "
    "{%0, %1, %2, %3, %4, %5, %6, %7, %8, %9, %10, %11, %12, %13, %14, %15, "
    "%16, %17, %18, %19, %20, %21, %22, %23, %24, %25, %26, %27, %28, %29, %30, %31, "
    "%32, %33, %34, %35, %36, %37, %38, %39, %40, %41, %42, %43, %44, %45, %46, %47, "
    "%48, %49, %50, %51, %52, %53, %54, %55, %56, %57, %58, %59, %60, %61, %62, %63, "
    "%64, %65, %66, %67, %68, %69, %70, %71, %72, %73, %74, %75, %76, %77, %78, %79, "
    "%80, %81, %82, %83, %84, %85, %86, %87, %88, %89, %90, %91, %92, %93, %94, %95, "
    "%96, %97, %98, %99, %100, %101, %102, %103, %104, %105, %106, %107, %108, %109, %110, %111, "
    "%112, %113, %114, %115, %116, %117, %118, %119, %120, %121, %122, %123, %124, %125, %126, %127}, "
    "{%128, %129, %130, %131}, %132, p, 1, 1, 1;\n}\n"
    : "+f"(d[0]), "+f"(d[1]), "+f"(d[2]), "+f"(d[3]), "+f"(d[4]), "+f"(d[5]), "+f"(d[6]), "+f"(d[7]),
      "+f"(d[8]), "+f"(d[9]), "+f"(d[10]), "+f"(d[11]), "+f"(d[12]), "+f"(d[13]), "+f"(d[14]), "+f"(d[15]),
      "+f"(d[16]), "+f"(d[17]), "+f"(d[18]), "+f"(d[19]), "+f"(d[20]), "+f"(d[21]), "+f"(d[22]), "+f"(d[23]),
      "+f"(d[24]), "+f"(d[25]), "+f"(d[26]), "+f"(d[27]), "+f"(d[28]), "+f"(d[29]), "+f"(d[30]), "+f"(d[31]),
      "+f"(d[32]), "+f"(d[33]), "+f"(d[34]), "+f"(d[35]), "+f"(d[36]), "+f"(d[37]), "+f"(d[38]), "+f"(d[39]),
      "+f"(d[40]), "+f"(d[41]), "+f"(d[42]), "+f"(d[43]), "+f"(d[44]), "+f"(d[45]), "+f"(d[46]), "+f"(d[47]),
      "+f"(d[48]), "+f"(d[49]), "+f"(d[50]), "+f"(d[51]), "+f"(d[52]), "+f"(d[53]), "+f"(d[54]), "+f"(d[55]),
      "+f"(d[56]), "+f"(d[57]), "+f"(d[58]), "+f"(d[59]), "+f"(d[60]), "+f"(d[61]), "+f"(d[62]), "+f"(d[63]),
      "+f"(d[64]), "+f"(d[65]), "+f"(d[66]), "+f"(d[67]), "+f"(d[68]), "+f"(d[69]), "+f"(d[70]), "+f"(d[71]),
      "+f"(d[72]), "+f"(d[73]), "+f"(d[74]), "+f"(d[75]), "+f"(d[76]), "+f"(d[77]), "+f"(d[78]), "+f"(d[79]),
      "+f"(d[80]), "+f"(d[81]), "+f"(d[82]), "+f"(d[83]), "+f"(d[84]), "+f"(d[85]), "+f"(d[86]), "+f"(d[87]),
      "+f"(d[88]), "+f"(d[89]), "+f"(d[90]), "+f"(d[91]), "+f"(d[92]), "+f"(d[93]), "+f"(d[94]), "+f"(d[95]),
      "+f"(d[96]), "+f"(d[97]), "+f"(d[98]), "+f"(d[99]), "+f"(d[100]), "+f"(d[101]), "+f"(d[102]), "+f"(d[103]),
      "+f"(d[104]), "+f"(d[105]), "+f"(d[106]), "+f"(d[107]), "+f"(d[108]), "+f"(d[109]), "+f"(d[110]), "+f"(d[111]),
      "+f"(d[112]), "+f"(d[113]), "+f"(d[114]), "+f"(d[115]), "+f"(d[116]), "+f"(d[117]), "+f"(d[118]), "+f"(d[119]),
      "+f"(d[120]), "+f"(d[121]), "+f"(d[122]), "+f"(d[123]), "+f"(d[124]), "+f"(d[125]), "+f"(d[126]), "+f"(d[127])
    : "r"(a0), "r"(a1), "r"(a2), "r"(a3), "l"(descB), "r"(scaleD));
}

constexpr uint32_t MSLOT = 32768, QSLOT = 49152;
constexpr int NM = 6;
constexpr uint32_t SM_X0 = 3 * QSLOT;
constexpr uint32_t SM_XR = SM_X0 + 16384;
constexpr uint32_t SM_STG = 196608;
constexpr uint32_t SM_XCH = SM_STG + 16384;
constexpr uint32_t SM_BAR = SM_STG + 32768;
constexpr uint32_t SM_VEC = SM_BAR + 512;
constexpr uint32_t SM_MODT = SM_VEC;
constexpr uint32_t SM_TOTAL = SM_VEC + 2048;
constexpr uint32_t B_X = SM_BAR  , B_EQ = B_X + 64, B_EM = B_EQ + 32, B_STREQ = B_EM + 48, B_HREQ = B_STREQ + 8  , B_LN = B_HREQ + 16,
                   B_FQ = B_LN + 8, B_FM = B_FQ + 32, B_MOD = B_FM + 48  , B_GATE = B_MOD + 64, B_STFREE = B_GATE + 8, B_VEC = B_STFREE + 8  ,
                   B_FLG = B_VEC + 16  , B_H2A = B_FLG + 24, B_HFREE = B_FLG + 96  ,
                   B_RST = B_HFREE + 16, B_F1 = B_RST + 8  , B_STH = B_F1 + 24  , B_END = B_STH + 16;
static_assert(B_END <= SM_VEC, "barriers");
constexpr int NB_WG = 1  , NB_CONS = 3, NB_ORD = 4  ;
#define TUNE(name, value) constexpr int name = value
TUNE(PF_BYTES, 256);
TUNE(X_GAP, 250);
TUNE(AUX_HOLD, 3200);
TUNE(AUX_URG, 4);
TUNE(AUX_SLOW, 84);
TUNE(AUX_GAP, 500);
TUNE(MSEP, 6);
TUNE(ASPLIT, 2);
TUNE(WTAIL, 4);
TUNE(WPRE, 2);
TUNE(DTAIL, 4);

struct Maps {
  CUtensorMap x, out;
  CUtensorMap h64;
  CUtensorMap o, hh;
  CUtensorMap wqk, wvv, wq1, wo, w1, w3, w2;
  CUtensorMap wmod;
#define MAP_H2 o
};

struct Ring { int st; uint32_t ph; int prev; uint32_t dl;
};
__device__ __forceinline__ void ring_next(Ring& r) { if (++r.st == NM) { r.st = 0; r.ph ^= 1; } }

__device__ __forceinline__ void retire_prev(uint32_t rel, bool on) {
  wgmma_commit();
  wgmma_wait<1>();
  if (on) mbar_arrive_e(rel);
}
struct Nop { __device__ __forceinline__ void operator()() const {} };
template <bool REL = true, class F = Nop>
__device__ __forceinline__ void mma_step(float (&acc)[64], uint32_t a, uint32_t b, bool first, uint32_t rel, F urgent = F()) {
  const uint32_t alo = (a >> 4) + (1u << 16), blo = (b >> 4) + (512u << 16);
  wgmma_fence();
  #pragma unroll
  for (int k = 0; k < 4; k++) {
    wgmma_m64n128k16_ss(acc, desc_from_lo(alo + k * 2), desc_from_lo(blo + k * 128), k > 0 || !first);
    if (k == 0) { retire_prev(rel, REL); urgent(); }
  }
  wgmma_commit();
}
template <bool REL>
__device__ __forceinline__ void mma_solo(float (&acc)[64], uint32_t a, uint32_t b, bool first, uint32_t rel) {
  const uint32_t alo = (a >> 4) + (1u << 16), blo = (b >> 4) + (512u << 16);
  wgmma_fence();
  #pragma unroll
  for (int k = 0; k < 4; k++) {
    wgmma_m64n128k16_ss(acc, desc_from_lo(alo + k * 2), desc_from_lo(blo + k * 128), k > 0 || !first);
    if (REL && k == 2) retire_prev(rel, true);
  }
  wgmma_commit();
}
__device__ __forceinline__ uint32_t m_wait(uint32_t sbase, const Ring& r) {
  mbar_wait(sbase + B_FM + 8 * r.st, r.ph, r.dl);
  return sbase + r.st * MSLOT;
}
__device__ __forceinline__ uint32_t m_prev(uint32_t sbase, const Ring& r) { return sbase + B_EM + 8 * r.prev; }
__device__ __forceinline__ void m_next(Ring& r) {
  r.prev = r.st; ring_next(r);
}
__device__ __forceinline__ void m_step(float (&acc)[64], uint32_t sbase, uint32_t wgoff, Ring& r, bool first = false) {
  const uint32_t slot = m_wait(sbase, r);
  mma_step(acc, slot + wgoff, slot + 16384, first, m_prev(sbase, r));
  m_next(r);
}

struct LnRow { uint32_t rs[2], nb[2]; };
__device__ __forceinline__ void ln_row(LnRow& l, int h, float mean, float rstd) {
  l.rs[h] = pack_bf16(rstd, rstd);
  const float nb = -mean * bf_lo(l.rs[h]);
  l.nb[h] = pack_bf16(nb, nb);
}
__device__ __forceinline__ uint32_t ln_mod(uint32_t x, const LnRow& l, int h, uint32_t c1, uint32_t s) {
  return fma_bf2(fma_bf2(x, l.rs[h], l.nb[h]), c1, s);
}

__device__ __forceinline__ uint32_t q_wait(int u, uint32_t sbase, uint32_t dl) {
  mbar_wait(sbase + B_FQ + 8 * (u & 3), (u >> 2) & 1, dl);
  return sbase + (u & 3) * QSLOT;
}
__device__ __forceinline__ uint32_t q_empty(int u, uint32_t sbase) { return sbase + B_EQ + 8 * (u & 3); }
struct Frag4 { uint32_t o[4]; };
__device__ __forceinline__ void q_load(uint32_t (&A)[16], uint4 (&p)[4], int kk, uint32_t tile, const Frag4& f, uint32_t t) {
  ldmatrix_x4(tile + f.o[kk], A[4 * kk], A[4 * kk + 1], A[4 * kk + 2], A[4 * kk + 3]);
  p[kk] = lds128(t + kk * 64);
}
__device__ __forceinline__ void q_norm(uint32_t (&A)[16], const uint4 (&p)[4], int kk, const LnRow& l) {
  A[4 * kk + 0] = ln_mod(A[4 * kk + 0], l, 0, p[kk].x, p[kk].z); A[4 * kk + 1] = ln_mod(A[4 * kk + 1], l, 1, p[kk].x, p[kk].z);
  A[4 * kk + 2] = ln_mod(A[4 * kk + 2], l, 0, p[kk].y, p[kk].w); A[4 * kk + 3] = ln_mod(A[4 * kk + 3], l, 1, p[kk].y, p[kk].w);
}
template <bool NEXT>
__device__ __forceinline__ void q_step_rs(float (&acc)[128], uint32_t (&A)[16], uint32_t (&N)[16], uint4 (&p)[4], int u, uint32_t sbase,
                                          const Frag4& f, uint32_t tab, const LnRow& l, uint32_t rot, bool keep, bool first, uint32_t dl, int wg, int zero) {
  const uint32_t slot = first ? sbase : q_wait(u, sbase, dl);
  const uint32_t blo = ((slot + 16384) >> 4) + (512u << 16) + rot * 128 + (zero << (u >> 2)), t = tab + ((u + 1) & 7) * 256;
  #pragma unroll
  for (int kk = 0; kk < 4; kk++) q_norm(A, p, kk, l);
  #pragma unroll
  for (int i = 0; i < 16; i++) asm volatile("" : "+r"(A[i]));
  if (!first) sched_fence(zero);
  if (first) {
    mbar_wait(sbase + B_GATE, 0, dl);
    PROF(6, threadIdx.x == 0);
  }
  if (!(first && wg == 0)) bar_sync(NB_ORD + wg, 256);
  wgmma_fence();
  #pragma unroll
  for (int kk = 0; kk < 4; kk++) {
    wgmma_m64n256k16_rs(acc, A[4 * kk], A[4 * kk + 1], A[4 * kk + 2], A[4 * kk + 3], desc_from_lo(blo ^ (kk * 128)), kk > 0 || !first);
    if (kk == 0) retire_prev(q_empty(u - 1, sbase), !first);
    if (NEXT && kk == 1) {
      if ((u & 1) && u < MSEP) mbar_wait(sbase + B_MOD + 4 * (u + 1), 0, dl);
      #pragma unroll
      for (int q = 0; q < 4; q++) q_load(N, p, q, slot, f, t);
    }
    if (kk == 3 && (NEXT || wg == 0)) bar_arrive(NB_ORD + (wg ^ 1), 256);
    if (kk == 1) stmatrix_x4_if(sbase + SM_STG + (u >> 3) * 16384 + (f.o[0] ^ (((u >> 1 & 3) ^ rot) << 5)), A[0], A[1], A[2], A[3], keep);
  }
  wgmma_commit();
}

typedef uint32_t Frag8[8];
template <int N> __device__ __forceinline__ void pack_half(Frag8& f, const float (&acc)[N], int off, int half) {
  #pragma unroll
  for (int e = 0; e < 8; e++) { f[e] = pack_bf16(acc[off + 4 * e + 2 * half], acc[off + 4 * e + 2 * half + 1]); asm volatile("" : "+r"(f[e])); }
}
__device__ __forceinline__ void transpose8(Frag8& f) {
  #pragma unroll
  for (int e = 0; e < 8; e++) f[e] = movmatrix_t(f[e]);
}
__device__ __forceinline__ void attn_send(const Frag8& f, int kv, uint32_t xch, int warp, uint4* halo_out, bool has_next) {
  if (warp == 3) {
    st_nonzero_v4(halo_out + kv * 64, f[0], f[1], f[2], f[3], has_next); st_nonzero_v4(halo_out + kv * 64 + 32, f[4], f[5], f[6], f[7], has_next);
  } else {
    sts128(xch + 2048 + kv * 1024, f[0], f[1], f[2], f[3]); sts128(xch + 2048 + kv * 1024 + 512, f[4], f[5], f[6], f[7]);
  }
}
template <int N>
__device__ __forceinline__ void attn_recv(uint4* p, int first, uint32_t xch, int wg, int warp, const uint4* halo_in, bool has_prev) {
  bar_sync(NB_WG + wg, 128);
  #pragma unroll
  for (int e = 0; e < N; e++)
    asm volatile("{\n.reg .pred p, q;\nsetp.ne.b32 p, %6, 0;\nsetp.ne.b32 q, %7, 0;\n"
                 "mov.b32 %0, 0;\nmov.b32 %1, 0;\nmov.b32 %2, 0;\nmov.b32 %3, 0;\n"
                 "@p ld.shared.v4.b32 {%0,%1,%2,%3}, [%4];\n@q ld.relaxed.gpu.global.v4.u32 {%0,%1,%2,%3}, [%5];\n}"
                 : "=&r"(p[e].x), "=&r"(p[e].y), "=&r"(p[e].z), "=&r"(p[e].w)
                 : "r"(xch + (first + e) * 512), "l"(halo_in + (first + e) * 32), "r"((int)(warp > 0)), "r"((int)(warp == 0 && has_prev)) : "memory");
}
template <int N>
__device__ __forceinline__ void attn_check(uint4* p, int first, bool remote, const uint4* halo_in, uint32_t dl) {
  if (remote) {
    while (true) {
      uint32_t m = ~0u;
      #pragma unroll
      for (int e = 0; e < N; e++) m = min(m, min4(p[e]));
      if (poll_done(m != 0, dl)) break;
      #pragma unroll
      for (int e = 0; e < N; e++) p[e] = ld_rlx_v4(halo_in + (first + e) * 32);
    }
  }
}
template <int SPLIT, class F>
__device__ __forceinline__ void attn_core(const Frag8& qA, const Frag8& qB, const Frag8& kA, const Frag8& kB, const Frag8& vA, const Frag8& vB,
                                          const uint4* kP, const uint4* vP, bool noprev, int lane, float (&o)[2][5][4], F late) {
  const int g = lane >> 2, qd = lane & 3;
  const bool s0 = 2 * qd > g, s1 = 2 * qd + 1 > g;
  const uint32_t msk = (s0 ? 0xFFFFu : 0u) | (s1 ? 0xFFFF0000u : 0u);
  float s[2][3][4];
  uint32_t pr[2][2];
  auto scores = [&](int h, int nb) {
    s[h][nb][0] = s[h][nb][1] = s[h][nb][2] = s[h][nb][3] = 0.f;
    #pragma unroll
    for (int kk = 0; kk < 2; kk++) {
      const int e = 4 * h + 2 * kk;
      mma16(s[h][nb], qA[e], qB[e], qA[e + 1], qB[e + 1], nb == 1 ? kA[e] : nb == 2 ? kB[e] : kk ? kP[h].z : kP[h].x,
            nb == 1 ? kA[e + 1] : nb == 2 ? kB[e + 1] : kk ? kP[h].w : kP[h].y);
    }
  };
  auto rows = [&](int h, int y) {
    constexpr float SC = 0.17677669529663687f * 1.4426950408889634f;
    const float l0 = s0 ? (y == 0 && noprev ? -INFINITY : s[h][y][2 * y]) : s[h][y + 1][2 * y];
    const float l1 = s1 ? (y == 0 && noprev ? -INFINITY : s[h][y][2 * y + 1]) : s[h][y + 1][2 * y + 1];
    float m = fmaxf(l0, l1);
    m = fmaxf(m, __shfl_xor_sync(0xffffffffu, m, 1));
    m = fmaxf(m, __shfl_xor_sync(0xffffffffu, m, 2));
    const uint32_t p = pr[h][y] = pack_bf16(fast_ex2((l0 - m) * SC), fast_ex2((l1 - m) * SC));
    #pragma unroll
    for (int m2 = 0; m2 < 2; m2++) {
      const int e = 4 * h + 2 * m2;
      float (&d)[4] = o[h][2 * m2 + y];
      d[0] = d[1] = d[2] = d[3] = 0.f;
      if (y == 0) mma16(d, m2 ? vP[h].z : vP[h].x, m2 ? vP[h].w : vP[h].y, vA[e], vA[e + 1], p & msk, p & ~msk);
      else mma16(d, vA[e], vA[e + 1], vB[e], vB[e + 1], p & msk, p & ~msk);
    }
  };
  #pragma unroll
  for (int h = 0; h < 2; h++) { scores(h, 1); scores(h, 2); if (SPLIT == 0) scores(h, 0); }
  if (SPLIT == 2) { rows(0, 1); rows(1, 1); }
  if (SPLIT) { late(); scores(0, 0); scores(1, 0); }
  #pragma unroll
  for (int h = 0; h < 2; h++) {
    if (SPLIT < 2) rows(h, 1);
    rows(h, 0);
    o[h][4][0] = o[h][4][1] = o[h][4][2] = o[h][4][3] = 0.f;
    mma16(o[h][4], 0x3F803F80u, 0u, 0u, 0x3F803F80u, pr[h][0], pr[h][1]);
  }
}
__device__ __forceinline__ void attn_store(const float (&o)[2][5][4], int h, uint32_t sbase, const Frag4& f) {
  float r[4];
  #pragma unroll
  for (int e = 0; e < 4; e++) r[e] = fast_rcp(o[h][4][e]);
  #pragma unroll
  for (int m = 0; m < 2; m++) {
    const float (&lo)[4] = o[h][2 * m], (&hi)[4] = o[h][2 * m + 1];
    stmatrix_x4_t(sbase + SM_STG + f.o[2 * h + m], pack_bf16(lo[0] * r[0], lo[1] * r[1]), pack_bf16(hi[0] * r[2], hi[1] * r[3]),
                  pack_bf16(lo[2] * r[0], lo[3] * r[1]), pack_bf16(hi[2] * r[2], hi[3] * r[3]));
  }
}

__device__ __forceinline__ void request_store(uint32_t bar) {
  fence_proxy_async_smem();
  mbar_arrive_e(bar);
}

__device__ __forceinline__ void g_quad(float (&a0)[64], float (&a1)[64], uint32_t rel2, uint32_t sbase, uint32_t wgoff, Ring& r) {
  const uint32_t x = m_wait(sbase, r);
  mma_step(a0, x + wgoff, x + 16384, false, m_prev(sbase, r), [&] { if (rel2) mbar_arrive_e(rel2); });
  m_next(r);
  const uint32_t xe = m_prev(sbase, r), y = m_wait(sbase, r);
  mma_step<false>(a1, x + wgoff, y, false, 0);
  m_next(r);
  const uint32_t z = m_wait(sbase, r);
  mma_step(a1, z + wgoff, y + 16384, false, xe);
  mma_step(a0, z + wgoff, z + 16384, false, m_prev(sbase, r));
  m_next(r);
}
template <int T>
__device__ __forceinline__ void g_piece(float (&prv)[64], int jj, int use, uint32_t sbase, const Frag4& f, uint32_t dl) {
  if (jj == 0) { mbar_wait(sbase + B_HFREE + 8 * T, use & 1, dl); fence_regs(prv); PROF(33 + 2 * use + T, threadIdx.x == 0); }
  uint32_t p[4];
  #pragma unroll
  for (int e = 0; e < 4; e++) {
    const int i = jj * 8 + e * 2;
    p[e] = pack_bf16(swiglu(prv[i], prv[i + 32]), swiglu(prv[i + 1], prv[i + 33]));
  }
  stmatrix_x4(sbase + SM_STG + T * 16384 + f.o[jj], p[0], p[1], p[2], p[3]);
  if (jj == 3) request_store(sbase + B_HREQ + 8 * T);
}
template <bool REL2, bool Q, class F>
__device__ __forceinline__ uint32_t g_ppqq(float (&p)[64], float (&q)[64], bool firstq, uint32_t rel2, uint32_t sbase, uint32_t wgoff, Ring& r, F after) {
  const uint32_t x = m_wait(sbase, r);
  mma_step(p, x + wgoff, x + 16384, false, m_prev(sbase, r), [&] { if (REL2) mbar_arrive_e(rel2); });
  m_next(r);
  after(0);
  const uint32_t xe = m_prev(sbase, r), z = m_wait(sbase, r);
  mma_step<!Q>(p, z + wgoff, z + 16384, false, xe);
  m_next(r);
  after(1);
  if (!Q) return 0;
  const uint32_t ze = m_prev(sbase, r), y = m_wait(sbase, r);
  mma_step<false>(q, x + wgoff, y, firstq, 0);
  after(2);
  mma_step(q, z + wgoff, y + 16384, false, xe);
  m_next(r);
  after(3);
  return ze;
}

__device__ __forceinline__ uint32_t bad2(uint32_t a, uint32_t b, unsigned par) {
  uint32_t d; asm("lop3.b32 %0, %1, %2, %3, 0x7E;" : "=r"(d) : "r"(a), "r"(b), "r"(par)); return d;
}
__device__ __forceinline__ uint32_t bad4(const uint4& v, unsigned par) { return bad2(v.x, v.y, par) | bad2(v.z, v.w, par); }
__device__ __forceinline__ uint32_t hi_halves(uint32_t lo, uint32_t hi) { return __byte_perm(lo, hi, 0x7632); }

__device__ __forceinline__ void gather_table(const float* src, uint32_t dst, uint32_t bar, unsigned par, uint32_t dl) {
  asm volatile("{\n.reg .pred p, e;\n.reg .b32 s<4>, c<4>, t<4>, w<4>;\n"
               "elect.sync _|e, 0xffffffff;\n"
               "LAB_POLL:\n"
               "ld.relaxed.gpu.global.v4.u32 {s0, s1, s2, s3}, [%0];\n"
               "ld.relaxed.gpu.global.v4.u32 {c0, c1, c2, c3}, [%0 + 4096];\n"
               "prmt.b32 w0, c0, c1, 0x7632;\nprmt.b32 w1, c2, c3, 0x7632;\nprmt.b32 w2, s0, s1, 0x7632;\nprmt.b32 w3, s2, s3, 0x7632;\n"
               "st.shared.v4.b32 [%1], {w0, w1, w2, w3};\n"
               "lop3.b32 t0, s0, s1, %3, 0x7E;\nlop3.b32 t1, s2, s3, %3, 0x7E;\nlop3.b32 t2, c0, c1, %3, 0x7E;\nlop3.b32 t3, c2, c3, %3, 0x7E;\n"
               "lop3.b32 t0, t0, t1, 1, 0xA8;\nlop3.b32 t2, t2, t3, 1, 0xA8;\n"
               "or.b32 t0, t0, t2;\n"
               "setp.eq.u32 p, t0, 0;\n"
               "vote.sync.all.pred p, p, 0xffffffff;\n"
               "@p bra.uni LAB_OK;\n"
               "mov.u32 t0, %%clock;\nsub.s32 t0, t0, %4;\nsetp.lt.s32 p, t0, 0;\n"
               "vote.sync.all.pred p, p, 0xffffffff;\n"
               "@p bra.uni LAB_POLL;\n"
               "LAB_OK:\n"
               "@e mbarrier.arrive.shared::cta.b64 _, [%2];\n}"
               :: "l"(src), "r"(dst), "r"(bar), "r"(par), "r"(dl) : "memory");
}

__device__ __forceinline__ int aux_col(int a, int u) { return u < 8 ? (a & 1) * 1024 + (2 * u + (a >> 1)) * 64 : 2048 + ((u - 8) * 4 + a) * 64; }
constexpr int NA = 7;
constexpr uint32_t A_FULL = SM_BAR, A_EMPTY = SM_BAR + 64, A_SUM = SM_BAR + 128, A_FREE = SM_BAR + 136, SM_RED = SM_VEC;
__device__ __forceinline__ void aux_role(const Maps& maps, const bf16* __restrict__ cvec, Mail* mail0, int zero, int a, uint32_t sbase, int wid) {
  const int tid = threadIdx.x, lane = tid & 31;
  const uint32_t dl = (clock32() + 800000000u) | 1;
  int st = 0; uint32_t ph = 0;
  if (wid == 8) {
    prefetch_tmap(&maps.wmod);
    #pragma unroll
    for (int i = 0; i < 18; i++) mbar_init_e(sbase + A_FULL + 8 * i, i < 8 ? 1 : i < 17 ? 8 : 2);
    fence_proxy_async_smem();
    bar_arrive(0, 352);
    PROF(39, lane == 0);
    #pragma unroll
    for (int i = 0; i < NA; i++) {
      mbar_expect_tx_e(sbase + A_FULL + 8 * i, 32768);
      tma_load_2d(sbase + i * MSLOT, &maps.wmod, sbase + A_FULL + 8 * i, aux_col(a, i >> 2), (i & 3) * 256);
    }
    PROF(40, lane == 0);
    #pragma unroll 1
    for (int i = NA; i < 96; i++) {
      if (i >= AUX_SLOW) wait_until(clock32() + AUX_GAP);
      if (i == 8) wait_until(dl - 800000000u + AUX_HOLD);
      mbar_wait(sbase + A_EMPTY + 8 * st, ph, dl);
      mbar_expect_tx_e(sbase + A_FULL + 8 * st, 32768);
      tma_load_2d<true>(sbase + st * MSLOT, &maps.wmod, sbase + A_FULL + 8 * st, aux_col(a, i >> 2), (i & 3) * 256);
      if (++st == NA) { st = 0; ph ^= 1; }
    }
  } else if (wid < 8) {
    const int g = lane >> 2, qd = lane & 3;
    uint32_t sc[16];
    const uint2 c = *reinterpret_cast<const uint2*>(cvec + tid * 4);
    sts64(sbase + SM_RED + tid * 8, pack_bf16(silu_f(bf_lo(c.x)), silu_f(bf_hi(c.x))), pack_bf16(silu_f(bf_lo(c.y)), silu_f(bf_hi(c.y))));
    bar_sync(0, 352);
    #pragma unroll
    for (int i = 0; i < 16; i++) sc[i] = lds32(sbase + SM_RED + ((i >> 2) * 256 + wid * 32 + (i & 3) * 8 + qd * 2) * 2);
    bar_sync(NB_CONS, 256);
    PROF(38, tid == 0);
    const uint32_t aoff = (wid * 32 + (lane & 7) + (lane >> 4) * 8) * 128 + ((((lane >> 3) & 1) ^ (lane & 7)) << 4);
    uint32_t w[2][8][4];
    auto fetch = [&](uint32_t (&f)[8][4]) {
      mbar_wait(sbase + A_FULL + 8 * st, ph, dl);
      #pragma unroll
      for (int e = 0; e < 8; e++) ldmatrix_x4_t((sbase + st * MSLOT + aoff + (e >> 2) * 2048) ^ ((e & 3) << 5), f[e]);
      if (++st == NA) { st = 0; ph ^= 1; }
    };
    #pragma unroll 1
    for (int u = 0; u < 24; u++) {
      float acc[4][4];
      #pragma unroll
      for (int m = 0; m < 4; m++) acc[m][0] = acc[m][1] = acc[m][2] = acc[m][3] = 0.f;
      fetch(w[0]);
      #pragma unroll
      for (int q = 0; q < 4; q++) {
        PROF(30 + (u & 1) * 4 + q, u < 2 && tid == 0);
        const uint32_t rel = sbase + A_EMPTY + 8 * (st == 0 ? NA - 1 : st - 1);
        if (q < 3) fetch(w[(q + 1) & 1]);
        uint32_t dep = 0;
        #pragma unroll
        for (int e = 0; e < 8; e++) dep |= w[q & 1][e][0];
        mbar_arrive_e(rel + (dep & zero));
        if (q == 1) mbar_wait(sbase + A_FREE, (u & 1) ^ 1, dl);
        #pragma unroll
        for (int e = 0; e < 8; e++) {
          const uint32_t (&f)[4] = w[q & 1][e];
          mma16(acc[e & 3], f[0], f[1], f[2], f[3], sc[4 * q + 2 * (e >> 2)], sc[4 * q + 2 * (e >> 2) + 1]);
        }
      }
      const float v0 = qd & 2 ? (qd & 1 ? acc[3][0] : acc[2][0]) : (qd & 1 ? acc[1][0] : acc[0][0]);
      const float v1 = qd & 2 ? (qd & 1 ? acc[3][2] : acc[2][2]) : (qd & 1 ? acc[1][2] : acc[0][2]);
      sts64(sbase + SM_RED + wid * 256 + (qd * 8 + g) * 8, __float_as_uint(v0), __float_as_uint(v1));
      mbar_arrive_e(sbase + A_SUM);
      if (u < AUX_URG) mbar_wait(sbase + A_FREE, u & 1, dl);
    }
  } else if (wid < 11) {
    float* const mail = &mail0->mod[(wid - 9) * 4 * 6 * D_ + 2 * lane];
    unsigned par = ld_relaxed(&mail0->flags[FL_EPOCH + (lane >> 5)]);
    bar_sync(0, 352);
    par = (par + 1) & 1;
    #pragma unroll 1
    for (int u = 0; u < 24; u++) {
      const int col = aux_col(a, u);
      const float add = (col >> 10) == 1 || (col >> 10) == 4 ? 1.f : 0.f;
      const float mul = col < 3 * D_ ? 1.f : col < 5 * D_ ? 0.5f : 2.f;
      mbar_wait(sbase + A_SUM, u & 1, dl);
      float2 v[8];
      #pragma unroll
      for (int w = 0; w < 8; w++) v[w] = lds64f(sbase + SM_RED + w * 256 + lane * 8);
      const float t0 = ((v[0].x + v[1].x) + (v[2].x + v[3].x)) + ((v[4].x + v[5].x) + (v[6].x + v[7].x));
      const float t1 = ((v[0].y + v[1].y) + (v[2].y + v[3].y)) + ((v[4].y + v[5].y) + (v[6].y + v[7].y));
      mbar_arrive_e(sbase + A_FREE + (__float_as_uint(t0 + t1) & zero));
      const uint32_t w = pack_bf16((add + bf16_round(t0)) * mul, (add + bf16_round(t1)) * mul), o = __shfl_xor_sync(0xffffffffu, w, 1);
      const uint32_t m0 = (lane & 1) ? (o & 0xFFFF0000u) : (w << 16), m1 = (lane & 1) ? (w & 0xFFFF0000u) : (o << 16);
      #pragma unroll
      for (int c = 0; c < 4; c++) st_rlx_v2(mail + c * 6 * D_ + col, m0 | par, m1 | par, true);
      PROF(1 + u, tid == 288);
    }
    const int t = a * 64 + tid - 288;
    #pragma unroll 1
    for (int i = t; i < 16 * 16 * 256; i += 256) mail0->halo[par ^ 1][i] = make_uint4(0, 0, 0, 0);
  }
}

template <int MODE>
__global__ void __launch_bounds__(384, 1)
fused_block_kernel(const bf16* __restrict__ x, const bf16* __restrict__ cvec, const bf16* __restrict__ wmod, Mail* mail0, int zero,
                   const __grid_constant__ Maps maps) {
  extern __shared__ __align__(1024) uint8_t smem_raw[];
  const uint32_t sbase = smem_u32(smem_raw);
  const int tid = threadIdx.x, lane = tid & 31;
  PROFN(0, tid == 0);
  const int wid = __shfl_sync(0xffffffffu, tid >> 5, 0);
  const int b = cta_role<MODE>();
  if (b >= NCTA) { aux_role(maps, cvec, mail0, zero, b - NCTA, sbase, wid); return; }
  const int jg = b >> 6, mb = jg ? 31 - (b >> 2) : (b >> 2), j = 4 * jg + (b & 3);
  const uint32_t dl = (clock32() + 800000000u) | 1;
  unsigned* const flags = &mail0->flags[mb * 32];
  const int row0 = mb * 128;

  if (wid >= 8) {
    if (wid == 8) {
      #pragma unroll
      for (int i = 0; i < 8; i++) mbar_init_e(sbase + B_X + 8 * i, 1);
      fence_proxy_async_smem();
      mbar_expect_tx_e(sbase + B_X, 4096);
      bulk_load(sbase + SM_XR, x + (size_t)(row0 + j * 16) * D_, 4096, sbase + B_X);
    } else if (wid == 11) {
      #pragma unroll
      for (int i = 0; i < 12; i++) prefetch_tmap(&maps.x + i);
    } else if (wid == 9) {
      #pragma unroll
      for (uint32_t bar = B_EQ; bar < B_FM; bar += 8) mbar_init_e(sbase + bar, bar < B_FQ ? 8 : bar == B_FQ + 8 || bar == B_FQ + 24 ? 2 : 1);
      fence_proxy_async_smem();
    } else {
      #pragma unroll
      for (uint32_t bar = B_FM; bar < B_END; bar += 8) mbar_init_e(sbase + bar, bar < B_STH ? 1 : 4);
      fence_proxy_async_smem();
    }
    bar_sync(0, 384);
    reg_dealloc<40>();
    PROF(92, tid == 256);
    if (wid == 8) {
      uint32_t tnext = clock32();
      #pragma unroll 1
      for (int q = 1; q < 8; q++) {
        wait_until(tnext);
        mbar_expect_tx_e(sbase + B_X + 8 * q, 4096);
        bulk_load(sbase + SM_XR + q * 4096, x + (size_t)(row0 + j * 16 + 2 * q) * D_, 4096, sbase + B_X + 8 * q);
        tnext += X_GAP;
      }
      #pragma unroll 1
      for (int u = 0; u < 16; u++) {
        const int st = u & 3;
        if (u == 1) mbar_wait(sbase + B_X + 56, 0, dl);
        if (u == 2) { mbar_wait(sbase + B_GATE, 0, dl); PROFN(60, lane == 0); }
        if (u == 3) mbar_wait(sbase + B_EQ, 0, dl);
        mbar_wait(sbase + B_EQ + 8 * st, ((u >> 2) & 1) ^ 1, dl);
        const uint32_t slot = sbase + st * QSLOT, fb = sbase + B_FQ + 8 * st;
        mbar_expect_tx_e(fb, u == 0 ? 65536 : u == 15 ? 32768 : 49152);
        if ((u & 1) && (u < MSEP || u == 15)) mbar_arrive_e(fb);
        if (u == 0) tma_load_3d(sbase + SM_X0, &maps.x, fb, 0, mb * 64, 0);
        tma_load_4d<true>(slot + 16384, &maps.wqk, fb, 0, u * 64, j, 0);
        tma_load_4d<true>(slot + 32768, &maps.wvv, fb, 0, u * 64, j, 0);
        if (u < 15) tma_load_3d(slot, &maps.x, fb, u * 64 + 64, mb * 64, 0);
      }
      const unsigned e1 = 1 + ld_relaxed(flags + FO_EPOCH);
      Ring r{0, 1, 0, dl};
      uint32_t slot, fb;
      auto acquire = [&](uint32_t bytes) {
        mbar_wait(sbase + B_EM + 8 * r.st, r.ph, dl);
        slot = sbase + r.st * MSLOT; fb = sbase + B_FM + 8 * r.st;
        mbar_expect_tx_e(fb, bytes);
        ring_next(r);
      };
      #pragma unroll 1
      for (int kt = 0; kt < 16; kt++) {
        if (kt < 5) mbar_wait(sbase + B_EQ + 8 * (kt - (kt >= 2)), 1, dl);
        if ((kt & 7) == 0) { PROF(46, lane == 0 && kt == 8); mbar_wait(sbase + B_FLG + kt, 0, dl); PROF(47, lane == 0 && kt == 8); }
        acquire(32768);
        tma_load_4d<true>(slot + 16384, &maps.wq1, fb, (j + 8) * 64, (kt & 1) * 64 + (kt & 6) * 8, (kt >> 3) * 4, 0);
        tma_load_3d(slot, &maps.hh, fb, (kt & 7) * 64, row0, kt >> 3);
      }
      PROF(82, lane == 0);
      mbar_wait(sbase + B_FLG + 16, 0, dl);
      PROF(83, lane == 0);
      #pragma unroll 1
      for (int kt = 0; kt < 8; kt++) {
        if (kt == 4) {
          acquire(32768);
          tma_load_3d(slot, &maps.x, fb, j * 128, mb * 64, 0);
          tma_load_3d(slot + 16384, &maps.x, fb, j * 128 + 64, mb * 64, 0);
        }
        acquire(32768);
        tma_load_3d<true>(slot + 16384, &maps.wo, fb, 0, kt * 64, 2 * j);
        tma_load_2d(slot, &maps.o, fb, kt * 64, row0);
      }
      acquire(16384);
      tma_load_3d<true>(slot + 16384, &maps.wo, fb, 0, (8 + j) * 64, 2 * j);
      const uint32_t oth = (0x2107654u + (0x1110000u << (4 * (j & 3)) & 0x1110000u)) ^ ((j & 4) ? 0x4444444u : 0u);
      auto deferred = [&](const CUtensorMap* map, const unsigned* flag, Ring ra, int n, int col0, int step) {
        uint32_t dst = sbase + ra.st * MSLOT, bar = sbase + B_FM + 8 * ra.st, col = col0 + (~j & 4) * step;
        asm volatile("" : "+r"(dst), "+r"(bar), "+r"(col));
        wait_flag(flag, e1 * NCTA, dl);
        tma_load_2d(dst, map, bar, col, row0);
        #pragma unroll 1
        for (int i = 1; i < n; i++) { ring_next(ra); tma_load_2d(sbase + ra.st * MSLOT, map, sbase + B_FM + 8 * ra.st, col + i * step, row0); }
      };
      {
        const Ring ra = r;
        #pragma unroll 1
        for (int i = 0; i < 7; i++) {
          const int kt = 8 + (oth >> (4 * i) & 7);
          acquire(32768);
          tma_load_3d<true>(slot + 16384, &maps.wo, fb, 0, kt * 64, 2 * j);
          if (i == WPRE - 1) { deferred(&maps.o, &mail0->flags[FL_O], ra, WPRE, 512, 64); PROFN(61, lane == 0); }
          if (i >= WPRE) tma_load_2d(slot, &maps.o, fb, kt * 64, row0);
        }
      }
      uint64_t ord = (uint64_t)(2 * oth) | (uint64_t)(2 * oth + 0x1111111u) << 28;
      auto load_b = [&](uint32_t dst, int col, int kt) {
        tma_load_2d<true>(dst, &maps.w1, fb, col, kt * 64);
        tma_load_2d<true>(dst + 8192, &maps.w3, fb, col, kt * 64);
      };
      Ring ra = r;
      #pragma unroll 1
      for (int i = -2; i < 5; i++) {
        const int kt = i < 0 ? 2 * j + i + 2 : 2 * ((~j & 4) + min(i, 3));
        if (i == 0) ra = r;
        if (i == 4) { deferred(&maps.h64, &mail0->flags[FL_H2], ra, 3, 0, 128); PROF(89, lane == 0); }
        acquire(i >= 0 && i < 3 ? 24576 : 32768);
        load_b(slot + 16384, i < 0 || i == 3 ? (8 + j) * 64 : j * 64, kt);
        if (i < 0 || i == 3) load_b(slot, i < 0 ? j * 64 : (8 + j) * 64, i < 0 ? kt : kt - 2);
      }
      #pragma unroll
      for (int i = 0; i < 3; i++) mbar_expect_tx_e(sbase + B_F1 + 8 * i, 8192);
      wait_flag(&mail0->flags[FL_H2 + 1], e1 * NCTA, dl);
      #pragma unroll 1
      for (int i = 0; i < 3; i++) { tma_load_2d(sbase + ra.st * MSLOT + 8192, &maps.h64, sbase + B_F1 + 8 * i, ((~j & 4) + i) * 128, row0 + 64); ring_next(ra); }
      tma_load_2d(slot, &maps.MAP_H2, fb, ((~j & 4) + 3) * 128, row0);
      PROFN(62, lane == 0);
      mbar_arrive_e(sbase + B_H2A);
      #pragma unroll 1
      for (int q = 2; q < 31; q++) {
        const int pr = q >> 3, w = q & 7, col = (16 * pr + j) * 64 + (w == 7 ? 512 : 0), y = pr == 3 ? 0 : w == 0 || w >= 6 ? 2 : 1;
        if (q == 7) ord = (j & 4) ? 0xFEDCBA9875316420ull : 0x76543210FDB9ECA8ull;
        const uint32_t kk = (uint32_t)(ord >> (w == 7 ? 0 : 8 * w + (pr == 0 ? 0 : 8)));
        const int k0 = kk & 15, k1 = kk >> 4 & 15;
        #pragma unroll
        for (int t = 1; t <= 2; t++) {
          if (t == 2 && q == 3) mbar_wait(sbase + B_FLG + 32, 0, dl);
          acquire(32768);
          load_b(slot + 16384, col, t == 1 ? k0 : k1);
          tma_load_2d(slot, &maps.MAP_H2, fb, (t == 1 ? k0 : k1) * 64, row0);
          if (t == y) {
            acquire(32768);
            load_b(slot, col + 512, k0);
            load_b(slot + 16384, col + 512, k1);
          }
        }
      }
      #pragma unroll 1
      for (int kt = 0; kt < 56; kt++) {
        if ((kt & 7) == 0) mbar_wait(sbase + B_FLG + 40 + kt, 0, dl);
        acquire(32768);
        tma_load_3d(slot + 16384, &maps.w2, fb, 0, kt * 64, 2 * j);
        tma_load_3d(slot, &maps.hh, fb, (kt & 7) * 64, row0, kt >> 3);
      }
    } else {
      const unsigned e1 = 1 + ld_relaxed(wid == 9 ? flags + FO_EPOCH : &mail0->flags[FL_EPOCH]), par = e1 & 1;
      auto publish_h2a = [&](int w) {
        mbar_wait(sbase + B_STH + 8 * w, 0, dl);
        tma_store_2d(&maps.h64, sbase + SM_STG + w * 8192, j * 128, row0 + w * 64);
        bulk_commit();
        bulk_wait0();
        red_add_e(&mail0->flags[FL_H2 + w], 1);
        PROF(84 + 4 * w, lane == 0);
      };
      if (wid == 9) {
        #pragma unroll 1
        for (int n = 0; n < 12; n++) {
          if (n == 4) {
            publish_h2a(0);
            mbar_wait(sbase + B_H2A, 0, dl);
          }
          if (n == 3) mbar_wait(sbase + B_RST, 0, dl);
          const int ht = (n - 5) & 1;
          if (n >= 1 && n <= 4) mbar_wait(sbase + B_STREQ, n & 1, dl);
          else mbar_sleep(n == 0 ? sbase + B_STREQ : sbase + B_HREQ + 8 * ht, n == 0 ? 0 : ((n - 5) >> 1) & 1, dl);
          if (n == 0) fence_proxy_async_smem();
          if (n == 2 || n == 3) tma_store_2d(&maps.o, sbase + SM_STG, (j + 8 * (n - 2)) * 64, row0);
          else if (n == 4) tma_store_2d(&maps.MAP_H2, sbase + SM_STG + 16384, j * 128 + 64, row0);
          else tma_store_3d(&maps.hh, sbase + SM_STG + (n < 2 ? n : ht) * 16384, j * 64, row0, n < 2 ? n : n - 5);
          bulk_commit();
          bulk_wait0();
          red_add_e(n == 3 ? &mail0->flags[FL_O] : flags + FO_CNT + n, 1);
          mbar_arrive_e(n < 4 ? sbase + B_STFREE : sbase + B_HFREE + 8 * ht);
          if (n == 4) mbar_arrive_e(sbase + B_HFREE);
          PROFN(70 + n, lane == 0 && n > 0); PROF(85, lane == 0 && n == 0);
          if (n != 3) { wait_flag(flags + FO_CNT + n, e1 * 8, dl); mbar_arrive_e(sbase + B_FLG + 8 * n); }
        }
      } else {
        const float* const mail = &mail0->mod[(b & 7) * 6 * D_ + lane * 4];
        if (wid == 10) {
          #pragma unroll 1
          for (int p = 0; p < 8; p++) {
            if (p >= 2) mbar_wait(p == 2 ? q_empty(0, sbase) : q_empty(2 * p - 5, sbase), p == 2 ? 0 : ((2 * p - 5) >> 2) & 1, dl);
            gather_table(mail + p * 128, sbase + SM_MODT + (p & 3) * 512 + ((lane * 16) ^ ((j >> 1) << 6)), 2 * p - 1 < MSEP ? sbase + B_MOD + 8 * p : sbase + B_FQ + 8 * ((2 * p - 1) & 3), par, dl);
            PROF(63 + p, lane == 0 && p < 7);
          }
          const uint32_t vdst = sbase + SM_VEC + (lane >> 3) * 64 + (lane & 3) * 16 + ((lane >> 2) & 1) * 8;
          #pragma unroll 1
          for (int v = 0; v < 2; v++) {
            mbar_sleep(sbase + B_FLG + 16 + 24 * v, 0, dl);
            uint4 m[3];
            while (true) {
              #pragma unroll
              for (int e = 0; e < 3; e++) m[e] = ld_rlx_v4(mail + (2 + v + e) * 1024 + j * 128);
              if (poll_done(((bad4(m[0], par) | bad4(m[1], par) | bad4(m[2], par)) & 1) == 0, dl)) break;
              __nanosleep(200);
            }
            #pragma unroll
            for (int e = 0; e < 3; e++) sts64(vdst + (v + e) * 256, hi_halves(m[e].x, m[e].y), hi_halves(m[e].z, m[e].w));
            if (v == 0) sts128(sbase + SM_VEC + 1024 + lane * 16, m[0].x & ~1u, m[0].y & ~1u, m[0].z & ~1u, m[0].w & ~1u);
            mbar_arrive_e(sbase + B_VEC + 8 * v);
            PROF(70, lane == 0 && v == 0);
          }
        } else {
          mbar_wait(sbase + B_LN, 0, dl);
          red_add_e(&mail0->flags[FL_LN1], 1);
          wait_flag(&mail0->flags[FL_LN1], e1 * NCTA, dl);
          mbar_arrive_e(sbase + B_GATE);
          PROF(41, lane == 0);
          mbar_sleep(sbase + B_FLG, 0, dl);
          #pragma unroll
          for (int e = 0; e < 2; e++) st_rlx_v4(mail0->st2 + ((mb * 8 + e * 4 + (lane >> 3)) * 8 + j) * 8 + (lane & 7), 0, 0, 0, 0, true);
          __threadfence();
          mbar_arrive_e(sbase + B_RST);
          PROF(86, lane == 0);
          mbar_sleep(sbase + B_VEC, 0, dl);
          publish_h2a(1);
        }
      }
    }
  } else {
    const int wg = wid >> 2, warp = wid & 3;
    const int g = lane >> 2, qd = lane & 3;
    bulk_prefetch(wmod + (size_t)(b * 8 + wid) * (6 * D_), PF_BYTES);
    bulk_prefetch(wmod + (size_t)(b * 8 + wid) * (6 * D_) + D_, PF_BYTES);
    bar_sync(0, 384);
    bulk_prefetch(wmod + (size_t)(b * 8 + wid) * (6 * D_) + PF_BYTES / 2, PF_BYTES);
    bulk_prefetch(wmod + (size_t)(b * 8 + wid) * (6 * D_) + PF_BYTES / 2 + D_, PF_BYTES);
    const unsigned e1 = 1 + ld_relaxed(flags + FO_EPOCH), par = e1 & 1;
    reg_alloc<232>();
    PROF(1, tid == 0);
    const uint32_t wgoff = wg * 8192;
    const uint32_t frag0 = wid * 2048 + (lane & 15) * 128 + (((lane >> 4) ^ (lane & 7)) << 4);
    const uint32_t slab = sbase + SM_STG + wid * 2048;

    LnRow ln;
    {
      uint2* const lmail = &mail0->ln1[(mb * 8 + (wid & 1) * 4 + (j >> 1)) * 16 + (j & 1) * 8 + (wid >> 1) + (lane & 1) * 4];
      float sm = 0.f, qm = 0.f, so = 0.f, qo = 0.f;
      #pragma unroll
      for (int h = 0; h < 2; h++) {
        sm = so; qm = qo;
        float s[2] = {0.f, 0.f}, q2[2] = {0.f, 0.f};
        mbar_wait(sbase + B_X + 8 * (4 * h + (wid >> 1)), 0, dl);
        PROF(3, tid == 224); PROF(93, tid == 0);
        #pragma unroll
        for (int c = 0; c < 4; c++) {
          const uint4 v = lds128(sbase + SM_XR + h * 16384 + wid * 2048 + c * 512 + lane * 16);
          const uint32_t vv[4] = {v.x, v.y, v.z, v.w};
          #pragma unroll
          for (int e = 0; e < 4; e++) {
            const float lo = bf_lo(vv[e]), hi = bf_hi(vv[e]);
            s[0] += lo; s[1] += hi; q2[0] = fmaf(lo, lo, q2[0]); q2[1] = fmaf(hi, hi, q2[1]);
          }
        }
        so = s[0] + s[1]; qo = q2[0] + q2[1];
      }
      const bool odd = lane & 1;
      { const float a = odd ? so : sm, c = odd ? qo : qm;
        sm = a + __shfl_xor_sync(0xffffffffu, odd ? sm : so, 1); qm = c + __shfl_xor_sync(0xffffffffu, odd ? qm : qo, 1); }
      #pragma unroll
      for (int o = 2; o < 32; o <<= 1) { sm += __shfl_xor_sync(0xffffffffu, sm, o); qm += __shfl_xor_sync(0xffffffffu, qm, o); }
      sm *= (1.f / D_);
      ln_row(ln, 0, sm, fast_rsqrt(fmaxf(qm * (1.f / D_) - sm * sm, 0.f) + 1e-5f));
      st_rlx_v2(lmail, (ln.rs[0] << 16) | par, (ln.nb[0] << 16) | par, lane < 2);
      mbar_arrive_e(sbase + B_LN);
      PROF(4, tid == 224);
    }

    uint4* const halo_out = mail0->halo[par] + ((mb * 16 + j) * 2 + wg) * 128 + lane;
    const uint4* const halo_in = halo_out - 16 * 256;
    const uint32_t xch = sbase + SM_XCH + (tid >> 5) * 2048 + lane * 16;
    const bool noprev = mb == 0 && warp == 0, remote = mb > 0 && warp == 0;
    float a0[64], a1[64];
    uint32_t x2[32];
    Ring r{zero, 0, 0, dl};
    Frag8 qA, qB, kA, kB, vA, vB, wA, wB;
    {
      float acc[128];
      uint32_t A0[16], A1[16];
      undef_regs(acc);
      const uint32_t tab = sbase + SM_MODT + qd * 16;
      uint4 p[4];
      const uint32_t rot = j >> 1;
      Frag4 fq;
      #pragma unroll
      for (int q = 0; q < 4; q++) fq.o[q] = frag0 ^ ((q ^ rot) << 5);
      mbar_wait(sbase + B_LN, 0, dl);
      const uint2* const lin = &mail0->ln1[(mb * 8 + wid) * 16 + g];
      uint2 v0, v1;
      q_wait(0, sbase, dl);
      #pragma unroll
      for (int kk = 0; kk < 4; kk++) ldmatrix_x4(sbase + SM_X0 + fq.o[kk], A0[4 * kk], A0[4 * kk + 1], A0[4 * kk + 2], A0[4 * kk + 3]);
      do { v0 = ld_rlx_v2(lin); v1 = ld_rlx_v2(lin + 8); } while (!poll_done(((bad2(v0.x, v0.y, par) | bad2(v1.x, v1.y, par)) & 1) == 0, dl));
      ln.rs[0] = hi_halves(v0.x, v0.x); ln.nb[0] = hi_halves(v0.y, v0.y); ln.rs[1] = hi_halves(v1.x, v1.x); ln.nb[1] = hi_halves(v1.y, v1.y);
      mbar_wait(sbase + B_MOD, 0, dl);
      #pragma unroll
      for (int kk = 0; kk < 4; kk++) p[kk] = lds128(tab + kk * 64);
      PROF(5, tid == 0);
      q_step_rs<true>(acc, A0, A1, p, 0, sbase, fq, tab, ln, rot, !(j & 1), true, dl, wg, zero);
      #pragma unroll
      for (int u = 1; u < 15; u += 2) {
        q_step_rs<true>(acc, A1, A0, p, u, sbase, fq, tab, ln, rot, j & 1, false, dl, wg, zero);
        q_step_rs<true>(acc, A0, A1, p, u + 1, sbase, fq, tab, ln, rot, !(j & 1), false, dl, wg, zero);
        if (u == 7) mbar_arrive_e(sbase + B_STREQ);
      }
      q_step_rs<false>(acc, A1, A0, p, 15, sbase, fq, tab, ln, rot, j & 1, false, dl, wg, zero);
      PROF(7, tid == 0);
      mbar_wait(sbase + B_STFREE, 0, dl);
      request_store(sbase + B_STREQ);
      wgmma_wait<0>();
      undef_regs(a0);
      { const uint32_t slot = m_wait(sbase, r); mma_step(a0, slot + wgoff, slot + 16384, true, q_empty(15, sbase)); m_next(r); }
      fence_regs(acc);
      PROF(8, tid == 0);
      sched_fence(zero);
      pack_half(vB, acc, 64, 1); transpose8(vB);
      m_step(a0, sbase, wgoff, r);
      sched_fence(zero);
      pack_half(kB, acc, 32, 1);
      attn_send(vB, 1, xch - 16384, warp, halo_out, mb < 15); attn_send(kB, 0, xch - 16384, warp, halo_out, mb < 15);
      m_step(a0, sbase, wgoff, r);
      sched_fence(zero);
      pack_half(qA, acc, 0, 0); pack_half(qB, acc, 0, 1); pack_half(kA, acc, 32, 0); pack_half(wB, acc, 96, 1); pack_half(wA, acc, 96, 0);
      m_step(a0, sbase, wgoff, r);
      sched_fence(zero);
      pack_half(vA, acc, 64, 0); transpose8(vA);
    }
    uint4 wP[2];
    Frag4 frag;
    #pragma unroll
    for (int q = 0; q < 4; q++) frag.o[q] = frag0 ^ (q << 5);
    {
      m_step(a0, sbase, wgoff, r);
      uint4 pv[4];
      attn_recv<4>(pv, 0, xch - 16384, wg, warp, halo_in, mb > 0);
      m_step(a0, sbase, wgoff, r);
      mbar_wait(sbase + B_STFREE, 1, dl);
      transpose8(wB);
      m_step(a0, sbase, wgoff, r);
      attn_check<4>(pv, 0, remote, halo_in, dl);
      wgmma_wait<0>();
      PROF(9, tid == 0);
      float o[2][5][4];
      sched_fence(zero);
      attn_core<0>(qA, qB, kA, kB, vA, vB, pv, pv + 2, noprev, lane, o, Nop());
      attn_store(o, 0, sbase, frag);
      attn_store(o, 1, sbase, frag);
      request_store(sbase + B_STREQ);
      bar_sync(NB_CONS, 256);
      PROF(10, tid == 0);
      m_step(a0, sbase, wgoff, r);
      sched_fence(zero);
      attn_send(wB, 1, xch, warp, halo_out + 8 * 256, mb < 15);
      m_step(a0, sbase, wgoff, r);
      sched_fence(zero);
      transpose8(wA);
      #pragma unroll 1
      for (int i = 9; i < 15; i++) m_step(a0, sbase, wgoff, r);
      attn_recv<2>(wP, 2, xch, wg, warp, halo_in + 8 * 256, mb > 0);
      m_step(a0, sbase, wgoff, r);
    }
    {
      undef_regs(a1);
      {
        const uint32_t slot = m_wait(sbase, r);
        mma_step(a1, slot + wgoff, slot + 16384, true, m_prev(sbase, r), [&] {
          fence_regs(a0);
          pack_half(kB, a0, 32, 1);
          attn_send(kB, 0, xch, warp, halo_out + 8 * 256, mb < 15);
        });
        m_next(r);
      }
      PROF(14, tid == 0);
      sched_fence(zero);
      pack_half(kA, a0, 32, 0); pack_half(qA, a0, 0, 0); pack_half(qB, a0, 0, 1);
      m_step(a1, sbase, wgoff, r);
      attn_check<2>(wP, 2, remote, halo_in + 8 * 256, dl);
      uint4 kP[2];
      attn_recv<2>(kP, 0, xch, wg, warp, halo_in + 8 * 256, mb > 0);
      m_step(a1, sbase, wgoff, r);
      if (ASPLIT == 0) attn_check<2>(kP, 0, remote, halo_in + 8 * 256, dl);
      wgmma_wait<0>();
      PROF(15, tid == 0);
      float o[2][5][4];
      mbar_wait(sbase + B_STFREE, 0, dl);
      attn_core<ASPLIT>(qA, qB, kA, kB, wA, wB, kP, wP, noprev, lane, o, [&] { attn_check<2>(kP, 0, remote, halo_in + 8 * 256, dl); });
      attn_store(o, 0, sbase, frag);
      attn_store(o, 1, sbase, frag);
      request_store(sbase + B_STREQ);
      bar_sync(NB_CONS, 256);
      PROF(16, tid == 0);
      auto residual = [&] {
        const uint32_t xs = m_wait(sbase, r), xe = sbase + B_EM + 8 * r.st;
        ring_next(r);
        #pragma unroll
        for (int t = 0; t < 2; t++) {
          #pragma unroll
          for (int jj = 4 * t; jj < 4 * t + 4; jj++) ldmatrix_x4(xs + t * 16384 + frag.o[jj & 3], x2[4 * jj], x2[4 * jj + 1], x2[4 * jj + 2], x2[4 * jj + 3]);
          if (t == 1) {
            uint32_t dep = 0;
            #pragma unroll
            for (int jj = 0; jj < 8; jj++) dep |= x2[4 * jj];
            mbar_arrive_e(xe + (dep & zero));
          }
          m_step(a1, sbase, wgoff, r);
        }
      };
      m_step(a1, sbase, wgoff, r);
      residual();
      #pragma unroll 1
      for (int i = 6; i < 8; i++) m_step(a1, sbase, wgoff, r);
      mma_step(a1, sbase + SM_STG + wgoff, m_wait(sbase, r) + 16384, false, m_prev(sbase, r));
      m_next(r);
      PROF(17, tid == 0);
      const uint32_t vec = sbase + SM_VEC + qd * 16;
      uint4 ga[8];
      #pragma unroll 1
      for (int i = 0; i < 5 - WTAIL; i++) m_step(a1, sbase, wgoff, r);
      mbar_wait(sbase + B_VEC, 0, dl);
      #pragma unroll
      for (int t = 0; t < 2; t++) {
        m_step(a1, sbase, wgoff, r);
        if (t == 0) mbar_wait(sbase + B_STFREE, 1, dl); else sched_fence(zero);
        #pragma unroll
        for (int q = 4 * t; q < 4 * t + 4; q++) ga[q] = lds128(vec + 1024 + q * 64);
      }
      uint4* sm = mail0->st2 + (mb * 8 + wid) * 64 + g;
      asm volatile("" : "+l"(sm));
      if (wg == 1) bar_sync(NB_ORD, 256);
      #pragma unroll 1
      for (int i = 0; i < WTAIL; i++) { const uint32_t slot = m_wait(sbase, r); mma_solo<true>(a1, slot + wgoff, slot + 16384, false, m_prev(sbase, r)); m_next(r); }
      if (wg == 0) bar_arrive(NB_ORD, 256);
      wgmma_wait<0>();
      mbar_arrive_e(m_prev(sbase, r));
      fence_regs(a1);
      PROF(18, tid == 0); PROF(23, tid == 128);
      float s[2], q2[2], sa[4] = {0.f, 0.f, 0.f, 0.f}, qa[4] = {0.f, 0.f, 0.f, 0.f};
      #pragma unroll
      for (int i = 0; i < 64; i++) {
        const uint4& gv = ga[i >> 3];
        a1[i] = fmaf(__uint_as_float((i & 4) ? ((i & 1) ? gv.w : gv.z) : ((i & 1) ? gv.y : gv.x)), a1[i], (i & 1) ? bf_hi(x2[i >> 1]) : bf_lo(x2[i >> 1]));
        sa[i & 3] += a1[i]; qa[i & 3] = fmaf(a1[i], a1[i], qa[i & 3]);
      }
      #pragma unroll
      for (int h = 0; h < 2; h++) { s[h] = sa[2 * h] + sa[2 * h + 1]; q2[h] = qa[2 * h] + qa[2 * h + 1]; }
      #pragma unroll
      for (int o2 = 1; o2 <= 2; o2 <<= 1)
        #pragma unroll
        for (int h = 0; h < 2; h++) { s[h] += __shfl_xor_sync(0xffffffffu, s[h], o2); q2[h] += __shfl_xor_sync(0xffffffffu, q2[h], o2); }
      st_nonzero_v4(sm + j * 8, __float_as_uint(s[0]), __float_as_uint(q2[0]), __float_as_uint(s[1]), __float_as_uint(q2[1]), qd == 0);
      sched_fence(zero);
      #pragma unroll
      for (int i = 0; i < 32; i++) { x2[i] = pack_bf16(a1[2 * i], a1[2 * i + 1]); asm volatile("" : "+r"(x2[i])); }
      PROF(19, tid == 0); PROF(24, tid == 128);
      uint4 sb[4], cb[4];
      #pragma unroll
      for (int q = 0; q < 4; q++) { sb[q] = lds128(vec + 256 + q * 64); cb[q] = lds128(vec + 512 + q * 64); }
      uint4 p0, p1;
      while (true) {
        p0 = ld_rlx_v4(sm + qd * 16); p1 = ld_rlx_v4(sm + qd * 16 + 8);
        if (poll_done(min(min4(p0), min4(p1)) != 0, dl)) break;
      }
      PROF(20, tid == 0); PROF(25, tid == 128);
      s[0] = __uint_as_float(p0.x) + __uint_as_float(p1.x); q2[0] = __uint_as_float(p0.y) + __uint_as_float(p1.y);
      s[1] = __uint_as_float(p0.z) + __uint_as_float(p1.z); q2[1] = __uint_as_float(p0.w) + __uint_as_float(p1.w);
      #pragma unroll
      for (int o2 = 1; o2 <= 2; o2 <<= 1)
        #pragma unroll
        for (int h = 0; h < 2; h++) { s[h] += __shfl_xor_sync(0xffffffffu, s[h], o2); q2[h] += __shfl_xor_sync(0xffffffffu, q2[h], o2); }
      #pragma unroll
      for (int h = 0; h < 2; h++) {
        const float m = s[h] * (1.f / D_);
        ln_row(ln, h, m, fast_rsqrt(fmaxf(q2[h] * (1.f / D_) - m * m, 0.f) + 1e-5f));
      }
      undef_regs(a0); undef_regs(a1);
      auto own_step = [&](int t) {
        const uint32_t slot = m_wait(sbase, r);
        if (t == 0) mma_solo<false>(a0, sbase + SM_STG + wgoff, slot, true, 0);
        else mma_solo<true>(a0, sbase + SM_STG + 16384 + wgoff, slot, false, m_prev(sbase, r));
        mma_solo<false>(a1, sbase + SM_STG + t * 16384 + wgoff, slot + 16384, t == 0, 0);
        m_next(r);
      };
      #pragma unroll
      for (int jj = 0; jj < 8; jj++) {
        const uint32_t cl = (jj & 1) ? cb[jj >> 1].z : cb[jj >> 1].x, ch = (jj & 1) ? cb[jj >> 1].w : cb[jj >> 1].y;
        const uint32_t sl = (jj & 1) ? sb[jj >> 1].z : sb[jj >> 1].x, sh = (jj & 1) ? sb[jj >> 1].w : sb[jj >> 1].y;
        stmatrix_x4(sbase + SM_STG + (jj >> 2) * 16384 + frag.o[jj & 3], ln_mod(x2[4 * jj], ln, 0, cl, sl), ln_mod(x2[4 * jj + 1], ln, 1, cl, sl),
                    ln_mod(x2[4 * jj + 2], ln, 0, ch, sh), ln_mod(x2[4 * jj + 3], ln, 1, ch, sh));
        if (jj == 3) { request_store(sbase + B_STH + 8 * wg); sched_fence(zero); }
      }
      request_store(sbase + B_STREQ);
      bar_sync(NB_WG + wg, 128);
      PROF(21, tid == 0); PROF(26, tid == 128);
      own_step(0);
      own_step(1);
    }

    PROF(22, tid == 0); PROF(27, tid == 128);
    #pragma unroll 1
    for (int i = 0; i < 3; i++) {
      if (wg == 1) mbar_wait(sbase + B_F1 + 8 * i, 0, dl);
      if (i < 2) { const uint32_t slot = m_wait(sbase, r); mma_solo<true>(a0, slot + wgoff, slot + 16384, false, m_prev(sbase, r)); m_next(r); }
    }
    uint32_t held = 0;
    #pragma unroll 1
    for (int pr = 0; pr < 3; pr++) {
      #pragma unroll 1
      for (int i = 0; i < 5; i++) { g_quad(a0, a1, held, sbase, wgoff, r); held = 0; }
      held = g_ppqq<false, true>(a0, a1, false, 0, sbase, wgoff, r, [&](int i) { if (i >= 2) g_piece<0>(a0, i - 2, pr, sbase, frag, dl); });
      held = g_ppqq<true, true>(a1, a0, true, held, sbase, wgoff, r,
                                [&](int i) { if (i < 2) g_piece<0>(a0, i + 2, pr, sbase, frag, dl); else g_piece<1>(a1, i - 2, pr, sbase, frag, dl); });
      if (pr == 2) break;
      held = g_ppqq<true, true>(a0, a1, true, held, sbase, wgoff, r, [&](int i) { if (i < 2) g_piece<1>(a1, i + 2, pr, sbase, frag, dl); });
    }
    g_ppqq<true, false>(a0, a1, false, held, sbase, wgoff, r, [&](int i) { g_piece<1>(a1, i + 2, 2, sbase, frag, dl); });
    #pragma unroll 1
    for (int i = 4; i < 15; i++) m_step(a0, sbase, wgoff, r);
    m_step(a0, sbase, wgoff, r);
    #pragma unroll
    for (int jj = 0; jj < 4; jj++) { m_step(a1, sbase, wgoff, r, jj == 0); g_piece<0>(a0, jj, 3, sbase, frag, dl); }
    #pragma unroll 1
    for (int i = 4; i < 56 - DTAIL; i++) m_step(a1, sbase, wgoff, r);
    if (DTAIL) {
      if (wg == 1) { wgmma_wait<0>(); mbar_arrive_e(m_prev(sbase, r)); bar_sync(NB_ORD, 256); }
      #pragma unroll 1
      for (int i = 0; i < DTAIL; i++) {
        const uint32_t slot = m_wait(sbase, r);
        mma_solo<false>(a1, slot + wgoff, slot + 16384, false, 0);
        ring_next(r);
      }
      if (wg == 0) bar_arrive(NB_ORD, 256);
    }
    {
      mbar_wait(sbase + B_HFREE, 0, dl);
      mbar_wait(sbase + B_HFREE + 8, 1, dl);
      mbar_wait(sbase + B_VEC + 8, 0, dl);
      uint4 gb[4];
      #pragma unroll
      for (int q = 0; q < 4; q++) gb[q] = lds128(sbase + SM_VEC + 768 + qd * 16 + q * 64);
      wgmma_wait<0>();
      fence_regs(a1);
      PROF(50, tid == 128);
      #pragma unroll
      for (int t = 0; t < 2; t++) {
        #pragma unroll
        for (int jj = 4 * t; jj < 4 * t + 4; jj++) {
          const uint32_t gl = (jj & 1) ? gb[jj >> 1].z : gb[jj >> 1].x, gh = (jj & 1) ? gb[jj >> 1].w : gb[jj >> 1].y;
          const int i = 8 * jj;
          stmatrix_x4(sbase + SM_STG + t * 16384 + frag.o[jj & 3],
                      fma_bf2(gl, pack_bf16(a1[i], a1[i + 1]), x2[4 * jj]), fma_bf2(gl, pack_bf16(a1[i + 2], a1[i + 3]), x2[4 * jj + 1]),
                      fma_bf2(gh, pack_bf16(a1[i + 4], a1[i + 5]), x2[4 * jj + 2]), fma_bf2(gh, pack_bf16(a1[i + 6], a1[i + 7]), x2[4 * jj + 3]));
        }
        fence_proxy_async_smem();
        tma_store_3d(&maps.out, slab + t * 16384, j * 128 + t * 64, mb * 64 + warp * 16, wg);
      }
      bulk_commit();
      st_rlx(tid == 0 ? flags + FO_EPOCH : &mail0->flags[FL_EPOCH], e1, j == 0 && (tid == 0 || (tid == 1 && mb == 0)));
      bulk_wait_read0();
      PROFN(51, tid == 128);
    }
  }
}

typedef CUresult (*PFN_encodeTiled)(CUtensorMap*, CUtensorMapDataType, cuuint32_t, void*, const cuuint64_t*, const cuuint64_t*,
                                    const cuuint32_t*, const cuuint32_t*, CUtensorMapInterleave, CUtensorMapSwizzle,
                                    CUtensorMapL2promotion, CUtensorMapFloatOOBfill);

void encode(PFN_encodeTiled fn, CUtensorMap* m, const void* ptr, int rank, const cuuint64_t* dims, const cuuint64_t* strides,
            const cuuint32_t* box) {
  const cuuint32_t es[5] = {1, 1, 1, 1, 1};
  fn(m, CU_TENSOR_MAP_DATA_TYPE_BFLOAT16, rank, const_cast<void*>(ptr), dims, strides, box, es, CU_TENSOR_MAP_INTERLEAVE_NONE,
     CU_TENSOR_MAP_SWIZZLE_128B, CU_TENSOR_MAP_L2_PROMOTION_L2_256B, CU_TENSOR_MAP_FLOAT_OOB_FILL_NONE);
}
void map2d(PFN_encodeTiled fn, CUtensorMap* m, const void* ptr, int cols, int rows, int boxrows) {
  const cuuint64_t dims[2] = {(cuuint64_t)cols, (cuuint64_t)rows}, strides[1] = {(cuuint64_t)cols * 2};
  const cuuint32_t box[2] = {64, (cuuint32_t)boxrows};
  encode(fn, m, ptr, 2, dims, strides, box);
}
void map_w2chunk(PFN_encodeTiled fn, CUtensorMap* m, const void* ptr, int cols, int rows) {
  const cuuint64_t dims[3] = {64, (cuuint64_t)rows, (cuuint64_t)cols / 64}, strides[2] = {(cuuint64_t)cols * 2, 128};
  const cuuint32_t box[3] = {64, 64, 2};
  encode(fn, m, ptr, 3, dims, strides, box);
}
void map_parity(PFN_encodeTiled fn, CUtensorMap* m, const void* ptr, int boxpairs, int boxpar) {
  const cuuint64_t dims[3] = {D_, S_ / 2, 2}, strides[2] = {D_ * 4, D_ * 2};
  const cuuint32_t box[3] = {64, (cuuint32_t)boxpairs, (cuuint32_t)boxpar};
  encode(fn, m, ptr, 3, dims, strides, box);
}

}

extern "C" void kernel_launch(void* const* d_in, const int* in_sizes, int n_in, void* d_out, int out_size) {
  (void)in_sizes; (void)n_in; (void)out_size;
  const bf16* x = (const bf16*)d_in[0];
  const bf16* wqkv = (const bf16*)d_in[1];
  const bf16* wo = (const bf16*)d_in[2];
  const bf16* w1 = (const bf16*)d_in[4];
  const bf16* w3 = (const bf16*)d_in[5];
  const bf16* w2 = (const bf16*)d_in[6];
  const bf16* cvec = (const bf16*)d_in[7];
  const bf16* w_mod = (const bf16*)d_in[8];

  static PFN_encodeTiled fn = nullptr;
  static Maps maps;
  static const void* cached[8] = {};
  static int sms = 0;
  static void* mail = nullptr;
  if (!fn) {
    void* p = nullptr; cudaDriverEntryPointQueryResult st;
    cudaGetDriverEntryPoint("cuTensorMapEncodeTiled", &p, cudaEnableDefault, &st);
    fn = (PFN_encodeTiled)p;
    cudaFuncSetAttribute(fused_block_kernel<0>, cudaFuncAttributeMaxDynamicSharedMemorySize, SM_TOTAL + SM_PROF);
    cudaFuncSetAttribute(fused_block_kernel<1>, cudaFuncAttributeMaxDynamicSharedMemorySize, SM_TOTAL + SM_PROF);
    cudaFuncSetAttribute(fused_block_kernel<2>, cudaFuncAttributeMaxDynamicSharedMemorySize, SM_TOTAL + SM_PROF);
    cudaGetSymbolAddress(&mail, g_mail);
    int dev = 0;
    cudaGetDevice(&dev);
    cudaDeviceGetAttribute(&sms, cudaDevAttrMultiProcessorCount, dev);
  }
  const void* cur[8] = {x, wqkv, wo, w1, w3, w2, d_out, w_mod};
  bool same = true;
  for (int i = 0; i < 8; i++) same = same && cached[i] == cur[i];
  if (!same) {
    void *o, *hh;
    cudaGetSymbolAddress(&hh, g_hh); cudaGetSymbolAddress(&o, g_o);
    map2d(fn, &maps.h64, o, D_, S_, 64);
    map_parity(fn, &maps.x, x, 64, 2); map_parity(fn, &maps.out, d_out, 16, 1);
    map2d(fn, &maps.o, o, D_, S_, 128);
    {
      const cuuint64_t dims[3] = {512, (cuuint64_t)S_, 7}, strides[2] = {1024, (cuuint64_t)S_ * 1024};
      const cuuint32_t box[3] = {64, 128, 1};
      encode(fn, &maps.hh, hh, 3, dims, strides, box);
    }
    {
      const cuuint64_t dims[4] = {64, 1024, 16, 2}, strides[3] = {3072 * 2, 128, 2048};
      const cuuint64_t dimv[4] = {64, 1024, 8, 2}, stridev[3] = {3072 * 2, 128, 1024};
      const cuuint32_t box[4] = {64, 64, 1, 2};
      encode(fn, &maps.wqk, wqkv, 4, dims, strides, box);
      encode(fn, &maps.wvv, wqkv + 2048, 4, dimv, stridev, box);
      const cuuint64_t dim1[4] = {1024, 128, 8, 2}, stride1[3] = {3072 * 2, 128 * 3072 * 2, 2048};
      const cuuint32_t box1[4] = {64, 16, 4, 2};
      encode(fn, &maps.wq1, wqkv, 4, dim1, stride1, box1);
    }
    map_w2chunk(fn, &maps.wo, wo, D_, D_); map_w2chunk(fn, &maps.w2, w2, D_, F_);
    map2d(fn, &maps.w1, w1, F_, D_, 64); map2d(fn, &maps.w3, w3, F_, D_, 64);
    map2d(fn, &maps.wmod, w_mod, 6 * D_, D_, 256);
    for (int i = 0; i < 8; i++) cached[i] = cur[i];
  }
  if (sms == NCTA + NAUX) {
    fused_block_kernel<0><<<NCTA + NAUX, 384, SM_TOTAL + SM_PROF>>>(x, cvec, w_mod, (Mail*)mail, 0, maps);
  } else {
    fused_block_kernel<1><<<NAUX, 384, SM_TOTAL + SM_PROF>>>(x, cvec, w_mod, (Mail*)mail, 0, maps);
    fused_block_kernel<2><<<NCTA, 384, SM_TOTAL + SM_PROF>>>(x, cvec, w_mod, (Mail*)mail, 0, maps);
  }
}
```
